```python
import torch

def _softmax(x, axis=-1):
    return torch.softmax(x, dim=axis)
def _gelu(x):
    return torch.nn.functional.gelu(x, approximate="tanh")
def _silu(x):
    return torch.nn.functional.silu(x)
def _sigmoid(x):
    return torch.sigmoid(x)
def _layernorm(x, axis=-1, eps=1e-5):
    m = x.mean(dim=axis, keepdim=True)
    v = x.var(dim=axis, keepdim=True, unbiased=False)
    return (x - m) / torch.sqrt(v + eps)
def _scatter_add(tgt, idx, src, axis=0):
    return tgt.clone().index_add_(axis, idx, src)
def _segment_sum(src, seg, n):
    out = torch.zeros((n,) + src.shape[1:], dtype=src.dtype)
    return out.index_add_(0, seg, src)
def _pad(x, pw):
    flat = tuple(v for pair in reversed(pw) for v in pair)
    return torch.nn.functional.pad(x, flat)

kernel_name = 'standalone__normalfloat_lut_af4__prompt'

def setup_inputs():

    _w = (lambda a: (lambda t: t.to(torch.bfloat16) if t.is_floating_point() else t)(torch.as_tensor(a)))
    B, S, D, F = 1, 2048, 1024, 3584
    G = -1 if -1 > 0 else D
    D = (D // G) * G
    ng = D // G
    nf4 = torch.tensor([
        -1.0, -0.6961928009986877, -0.5250730514526367, -0.39491748809814453,
        -0.28444138169288635, -0.18477343022823334, -0.09105003625154495, 0.0,
        0.07958029955625534, 0.16093020141124725, 0.24611230194568634,
        0.33791524171829224, 0.44070982933044434, 0.5626170039176941,
        0.7229568362236023, 1.0,
    ], dtype=float)
    qw = torch.randint(0, 16, (D, F)).to(torch.int64)
    return {
        "x": _w((lambda *s: torch.randn(*s, dtype=torch.bfloat16) * 0.05)(B, S, D)),
        "qw": _w(qw),
        "lut": _w(nf4),
        "scales": _w(torch.abs((lambda *s: torch.randn(*s, dtype=torch.bfloat16) * 0.05)(ng, F)).to(float) + 0.01),
    }

def reference(x, qw, lut, scales):
    B, S, D = x.shape
    ng, F = scales.shape
    G = D // ng
    deq = lut[qw]
    s = (lambda x, n, axis: torch.repeat_interleave(x, n, dim=axis))(scales, G, axis=0)
    w = (lambda x, dt: x.to(dt))(deq, x.dtype) * (lambda x, dt: x.to(dt))(s, x.dtype)
    return torch.einsum("bsd,df->bsf", x, w)
```

```cpp
#include <cuda_runtime.h>
#include <cuda_bf16.h>
#include <cuda.h>
#include <stdint.h>
#include <stdio.h>
#include <math.h>

namespace {

constexpr int kM = 2048, kN = 3584, kK = 1024;
constexpr int FT = 128;
constexpr int N0 = 232, N1 = 208;
constexpr int BK = 64, KSTEPS = kK / BK;
constexpr int NSLOTS = 6;
constexpr int SLOT_BYTES = N0 * 128;
constexpr int TBL_OFF = NSLOTS * SLOT_BYTES + 1024;
constexpr int RAW_OFF = TBL_OFF + 32768;
constexpr int BAR_OFF = RAW_OFF + 4 * 4096;
constexpr int TS_OFF = BAR_OFF + 256;
constexpr int SMEM_TOTAL = BAR_OFF + 256;
constexpr int NUM_THREADS = 384;
constexpr int NUM_CTAS = 132;
constexpr int NUM_AUX = 3;
constexpr int NQ = kK / 32, NUM_UNITS = NQ * (kN / 32);
constexpr int W1_FG = 64, W2_FG = kN / 32 - W1_FG;
constexpr int NSL = 2 * KSTEPS;
#define NBOR 2
#define CREGS 224
#define DLY_R0 500
#define DLY_R 400
#define R_KNEE 4
#define DLY_R2 450
#define PF_KIND 0
#define PF_DIST 2
#define PF_LEAD 700
#define DLY_X0 1000
#define DLY_XS 900
#define DLY_POLL 2800
#define DLY_PS 500
#define ND0 1
#define FPAIR 2
#define RAMP1 9
#define RAMP2 23
#define NSPIN0 8
#define NSPIN1 8
#define NALU 2
#define RSTOP (16 + NBOR)
#define EH 48
#define BX0 24
#define BX1 16
#define STQ 1
#define NEARLY 4
#define NGATE 8
#define DLY_ST0 800
#define DLY_ST 800
#define XPROMO CU_TENSOR_MAP_L2_PROMOTION_L2_128B
constexpr int E0 = 120, E1 = N0 - E0, S0 = 112, S1 = N1 - S0, CA = 64, CB = 48, CC = 32;
constexpr unsigned SPIN_LIMIT = 1u << 22;

__device__ unsigned long long g_ll[(size_t)(kN / FT) * NQ * FT * 4];
__device__ __align__(256) unsigned int g_epoch[64] = {16, 16, 16, 16, 16, 16, 16, 16, 16, 16, 16, 16, 16, 16, 16, 16,
                                                      16, 16, 16, 16, 16, 16, 16, 16, 16, 16, 16, 16, 16, 16, 16, 16};

#define TS(idx) do {} while (0)
#define TSW(idx) do {} while (0)
#define TSG(idx) do {} while (0)

template <int I> struct IC { static constexpr int value = I; };
template <int B, int E, class F> __device__ __forceinline__ void static_for(F&& f) {
    if constexpr (B < E) { f(IC<B>{}); static_for<B + 1, E>(f); }
}

__device__ __forceinline__ uint32_t smem_u32(const void* p) { return (uint32_t)__cvta_generic_to_shared(p); }
__device__ __forceinline__ uint32_t keep(uint32_t v, int lane) {
    asm volatile("shfl.sync.idx.b32 %0, %0, %1, 0x1f, 0xffffffff;" : "+r"(v) : "r"(lane));
    return v;
}
template <class T> __device__ __forceinline__ T* keep(T* p, int lane) {
    const uint64_t v = (uint64_t)p;
    return (T*)(((uint64_t)keep((uint32_t)(v >> 32), lane) << 32) | keep((uint32_t)v, lane));
}
__device__ __forceinline__ void mbar_init(uint32_t bar, uint32_t count) {
    asm volatile("mbarrier.init.shared::cta.b64 [%0], %1;" ::"r"(bar), "r"(count) : "memory");
}
__device__ __forceinline__ void mbar_arrive_expect_tx(uint32_t bar, uint32_t bytes) {
    asm volatile("mbarrier.arrive.expect_tx.shared::cta.b64 _, [%0], %1;" ::"r"(bar), "r"(bytes) : "memory");
}
__device__ __forceinline__ uint32_t clock32() { uint64_t c; asm volatile("mov.u64 %0, %%clock64;" : "=l"(c)); return (uint32_t)c; }
__device__ __forceinline__ void mbar_arrive(uint32_t bar) {
    asm volatile("mbarrier.arrive.shared::cta.b64 _, [%0];" ::"r"(bar) : "memory");
}
__device__ __forceinline__ uint32_t mapa(uint32_t a, uint32_t rank) {
    uint32_t r;
    asm("mapa.shared::cluster.u32 %0, %1, %2;" : "=r"(r) : "r"(a), "r"(rank));
    return r;
}
__device__ __forceinline__ void mbar_arrive_pair(uint32_t cbar, uint32_t base) {
    asm volatile("{\n.reg .pred p;\nsetp.ne.u32 p, %1, 0;\n@p mbarrier.arrive.shared::cluster.b64 _, [%0];\n}\n"
                 ::"r"(cbar), "r"(base) : "memory");
}
__device__ __forceinline__ void mbar_arrive_cluster_n(uint32_t cbar, uint32_t n) {
    asm volatile("mbarrier.arrive.shared::cluster.b64 _, [%0], %1;" ::"r"(cbar), "r"(n) : "memory");
}
__device__ __forceinline__ void delay_until(uint32_t t0, int clks) {
    while (__any_sync(0xffffffffu, (int)(clock32() - t0) < clks)) {}
}
__device__ __forceinline__ void mbar_wait(uint32_t bar, uint32_t parity) {
    asm volatile(
        "{\n.reg .pred p;\n.reg .u32 i;\n"
        "mbarrier.try_wait.parity.shared::cta.b64 p, [%0], %1;\n"
        "@p bra D_%=;\n"
        "mov.u32 i, 0;\n"
        "L_%=:\n"
        "mbarrier.try_wait.parity.shared::cta.b64 p, [%0], %1;\n"
        "@p bra D_%=;\n"
        "add.u32 i, i, 1;\n"
        "setp.lt.u32 p, i, %2;\n"
        "@p bra L_%=;\n"
        "D_%=:\n}\n"
        ::"r"(bar), "r"(parity), "n"(SPIN_LIMIT) : "memory");
}
__device__ __forceinline__ void tma_load_2d_mc(uint32_t dst, const CUtensorMap* map, uint32_t bar, int c0, int c1,
                                               uint16_t mask) {
    asm volatile(
        "cp.async.bulk.tensor.2d.shared::cluster.global.mbarrier::complete_tx::bytes.multicast::cluster"
        " [%0], [%1, {%3, %4}], [%2], %5;"
        ::"r"(dst), "l"(map), "r"(bar), "r"(c0), "r"(c1), "h"(mask) : "memory");
}
__device__ __forceinline__ void tma_store_2d(const CUtensorMap* map, uint32_t src, int c0, int c1) {
    asm volatile("cp.async.bulk.tensor.2d.global.shared::cta.bulk_group [%0, {%2, %3}], [%1];"
                 ::"l"(map), "r"(src), "r"(c0), "r"(c1) : "memory");
}
__device__ __forceinline__ void prefetch_map(const CUtensorMap* map) {
    asm volatile("prefetch.tensormap [%0];" ::"l"(map) : "memory");
}
constexpr uint32_t SMEM_BASE = 1024;
__host__ __device__ constexpr uint64_t make_desc(uint32_t saddr) {
    return (uint64_t)((saddr & 0x3FFFF) >> 4) | ((uint64_t)1 << 16) | ((uint64_t)(1024 >> 4) << 32) | ((uint64_t)1 << 62);
}
__device__ __forceinline__ void wgmma_fence() { asm volatile("wgmma.fence.sync.aligned;" ::: "memory"); }
__device__ __forceinline__ void wgmma_commit() { asm volatile("wgmma.commit_group.sync.aligned;" ::: "memory"); }
template <int N> __device__ __forceinline__ void wgmma_wait() {
    asm volatile("wgmma.wait_group.sync.aligned %0;" ::"n"(N) : "memory");
}
__device__ __forceinline__ uint32_t pack_bf16x2(float lo, float hi) {
    uint32_t r;
    asm("cvt.rn.bf16x2.f32 %0, %1, %2;" : "=r"(r) : "f"(hi), "f"(lo));
    return r;
}
__device__ __forceinline__ uint32_t lds32(uint32_t addr) {
    uint32_t v;
    asm("ld.shared.u32 %0, [%1];" : "=r"(v) : "r"(addr));
    return v;
}
__device__ __forceinline__ uint32_t dp4a_u(uint32_t a, uint32_t b, uint32_t c) {
    uint32_t d;
    asm("dp4a.u32.u32 %0, %1, %2, %3;" : "=r"(d) : "r"(a), "r"(b), "r"(c));
    return d;
}
__device__ __forceinline__ uint32_t prmt(uint32_t a, uint32_t b, uint32_t s) {
    uint32_t d;
    asm("prmt.b32 %0, %1, %2, %3;" : "=r"(d) : "r"(a), "r"(b), "r"(s));
    return d;
}
template <int ID, int NT> __device__ __forceinline__ void named_bar_sync() {
    asm volatile("bar.sync %0, %1;" ::"n"(ID), "n"(NT) : "memory");
}
template <int ID, int NT> __device__ __forceinline__ void named_bar_arrive() {
    asm volatile("bar.arrive %0, %1;" ::"n"(ID), "n"(NT) : "memory");
}
__device__ __forceinline__ void bar_sync_id(int id, int nt) { asm volatile("bar.sync %0, %1;" ::"r"(id), "r"(nt) : "memory"); }
__device__ __forceinline__ void bar_arrive_id(int id, int nt) { asm volatile("bar.arrive %0, %1;" ::"r"(id), "r"(nt) : "memory"); }
__device__ __forceinline__ void cluster_arrive_relaxed() { asm volatile("barrier.cluster.arrive.relaxed.aligned;" ::: "memory"); }
__device__ __forceinline__ void cluster_wait() { asm volatile("barrier.cluster.wait.acquire.aligned;" ::: "memory"); }
__device__ __forceinline__ uint4 ldg_stream(const int* p) {
    uint4 v;
    asm volatile("ld.global.L1::no_allocate.L2::128B.v4.u32 {%0, %1, %2, %3}, [%4];"
                 : "=r"(v.x), "=r"(v.y), "=r"(v.z), "=r"(v.w) : "l"(p));
    return v;
}
__device__ __forceinline__ uint32_t ldg_u16(const unsigned short* p) {
    uint32_t v;
    asm volatile("ld.global.nc.u16 %0, [%1];" : "=r"(v) : "l"(p));
    return v;
}
__device__ __forceinline__ unsigned ld_ca_u32(const unsigned* p) {
    unsigned v;
    asm volatile("ld.global.ca.u32 %0, [%1];" : "=r"(v) : "l"(p) : "memory");
    return v;
}
typedef unsigned long long u64;
__device__ __forceinline__ void ll_store(u64* p, uint32_t w, uint32_t tag) {
    asm volatile("{\n.reg .b64 a;\nmov.b64 a, {%1, %2};\nst.relaxed.gpu.global.b64 [%0], a;\n}\n"
                 ::"l"(p), "r"(w), "r"(tag) : "memory");
}

template <int N, int OFF, bool ACC, int NA> struct WG;
template <int OFF, int NA> struct WG<232, OFF, false, NA> {
    static __device__ __forceinline__ void mma(float (&d)[NA], uint32_t a0, uint32_t a1, uint32_t a2, uint32_t a3, uint64_t descB) {
        asm volatile(
            "{\n"
            ".reg .pred p;\n"
            "setp.ne.b32 p, %121, 0;\n"
            "wgmma.mma_async.sync.aligned.m64n232k16.f32.bf16.bf16 "
            "{%0, %1, %2, %3, %4, %5, %6, %7, %8, %9, %10, %11, %12, %13, %14, %15, %16, %17, %18, %19, %20, %21, %22, %23, %24, %25, %26, %27, %28, %29, %30, %31, %32, %33, %34, %35, %36, %37, %38, %39, %40, %41, %42, %43, %44, %45, %46, %47, %48, %49, %50, %51, %52, %53, %54, %55, %56, %57, %58, %59, %60, %61, %62, %63, %64, %65, %66, %67, %68, %69, %70, %71, %72, %73, %74, %75, %76, %77, %78, %79, %80, %81, %82, %83, %84, %85, %86, %87, %88, %89, %90, %91, %92, %93, %94, %95, %96, %97, %98, %99, %100, %101, %102, %103, %104, %105, %106, %107, %108, %109, %110, %111, %112, %113, %114, %115}, "
            "{%116, %117, %118, %119}, %120, p, 1, 1, 0;\n"
            "}\n"
            : "=f"(d[OFF + 0]), "=f"(d[OFF + 1]), "=f"(d[OFF + 2]), "=f"(d[OFF + 3]), "=f"(d[OFF + 4]), "=f"(d[OFF + 5]), "=f"(d[OFF + 6]), "=f"(d[OFF + 7]), "=f"(d[OFF + 8]), "=f"(d[OFF + 9]), "=f"(d[OFF + 10]), "=f"(d[OFF + 11]), "=f"(d[OFF + 12]), "=f"(d[OFF + 13]), "=f"(d[OFF + 14]), "=f"(d[OFF + 15]), "=f"(d[OFF + 16]), "=f"(d[OFF + 17]), "=f"(d[OFF + 18]), "=f"(d[OFF + 19]), "=f"(d[OFF + 20]), "=f"(d[OFF + 21]), "=f"(d[OFF + 22]), "=f"(d[OFF + 23]), "=f"(d[OFF + 24]), "=f"(d[OFF + 25]), "=f"(d[OFF + 26]), "=f"(d[OFF + 27]), "=f"(d[OFF + 28]), "=f"(d[OFF + 29]), "=f"(d[OFF + 30]), "=f"(d[OFF + 31]), "=f"(d[OFF + 32]), "=f"(d[OFF + 33]), "=f"(d[OFF + 34]), "=f"(d[OFF + 35]), "=f"(d[OFF + 36]), "=f"(d[OFF + 37]), "=f"(d[OFF + 38]), "=f"(d[OFF + 39]), "=f"(d[OFF + 40]), "=f"(d[OFF + 41]), "=f"(d[OFF + 42]), "=f"(d[OFF + 43]), "=f"(d[OFF + 44]), "=f"(d[OFF + 45]), "=f"(d[OFF + 46]), "=f"(d[OFF + 47]), "=f"(d[OFF + 48]), "=f"(d[OFF + 49]), "=f"(d[OFF + 50]), "=f"(d[OFF + 51]), "=f"(d[OFF + 52]), "=f"(d[OFF + 53]), "=f"(d[OFF + 54]), "=f"(d[OFF + 55]), "=f"(d[OFF + 56]), "=f"(d[OFF + 57]), "=f"(d[OFF + 58]), "=f"(d[OFF + 59]), "=f"(d[OFF + 60]), "=f"(d[OFF + 61]), "=f"(d[OFF + 62]), "=f"(d[OFF + 63]), "=f"(d[OFF + 64]), "=f"(d[OFF + 65]), "=f"(d[OFF + 66]), "=f"(d[OFF + 67]), "=f"(d[OFF + 68]), "=f"(d[OFF + 69]), "=f"(d[OFF + 70]), "=f"(d[OFF + 71]), "=f"(d[OFF + 72]), "=f"(d[OFF + 73]), "=f"(d[OFF + 74]), "=f"(d[OFF + 75]), "=f"(d[OFF + 76]), "=f"(d[OFF + 77]), "=f"(d[OFF + 78]), "=f"(d[OFF + 79]), "=f"(d[OFF + 80]), "=f"(d[OFF + 81]), "=f"(d[OFF + 82]), "=f"(d[OFF + 83]), "=f"(d[OFF + 84]), "=f"(d[OFF + 85]), "=f"(d[OFF + 86]), "=f"(d[OFF + 87]), "=f"(d[OFF + 88]), "=f"(d[OFF + 89]), "=f"(d[OFF + 90]), "=f"(d[OFF + 91]), "=f"(d[OFF + 92]), "=f"(d[OFF + 93]), "=f"(d[OFF + 94]), "=f"(d[OFF + 95]), "=f"(d[OFF + 96]), "=f"(d[OFF + 97]), "=f"(d[OFF + 98]), "=f"(d[OFF + 99]), "=f"(d[OFF + 100]), "=f"(d[OFF + 101]), "=f"(d[OFF + 102]), "=f"(d[OFF + 103]), "=f"(d[OFF + 104]), "=f"(d[OFF + 105]), "=f"(d[OFF + 106]), "=f"(d[OFF + 107]), "=f"(d[OFF + 108]), "=f"(d[OFF + 109]), "=f"(d[OFF + 110]), "=f"(d[OFF + 111]), "=f"(d[OFF + 112]), "=f"(d[OFF + 113]), "=f"(d[OFF + 114]), "=f"(d[OFF + 115])
            : "r"(a0), "r"(a1), "r"(a2), "r"(a3), "l"(descB), "n"(0));
    }
};
template <int OFF, int NA> struct WG<232, OFF, true, NA> {
    static __device__ __forceinline__ void mma(float (&d)[NA], uint32_t a0, uint32_t a1, uint32_t a2, uint32_t a3, uint64_t descB) {
        asm volatile(
            "{\n"
            ".reg .pred p;\n"
            "setp.ne.b32 p, %121, 0;\n"
            "wgmma.mma_async.sync.aligned.m64n232k16.f32.bf16.bf16 "
            "{%0, %1, %2, %3, %4, %5, %6, %7, %8, %9, %10, %11, %12, %13, %14, %15, %16, %17, %18, %19, %20, %21, %22, %23, %24, %25, %26, %27, %28, %29, %30, %31, %32, %33, %34, %35, %36, %37, %38, %39, %40, %41, %42, %43, %44, %45, %46, %47, %48, %49, %50, %51, %52, %53, %54, %55, %56, %57, %58, %59, %60, %61, %62, %63, %64, %65, %66, %67, %68, %69, %70, %71, %72, %73, %74, %75, %76, %77, %78, %79, %80, %81, %82, %83, %84, %85, %86, %87, %88, %89, %90, %91, %92, %93, %94, %95, %96, %97, %98, %99, %100, %101, %102, %103, %104, %105, %106, %107, %108, %109, %110, %111, %112, %113, %114, %115}, "
            "{%116, %117, %118, %119}, %120, p, 1, 1, 0;\n"
            "}\n"
            : "+f"(d[OFF + 0]), "+f"(d[OFF + 1]), "+f"(d[OFF + 2]), "+f"(d[OFF + 3]), "+f"(d[OFF + 4]), "+f"(d[OFF + 5]), "+f"(d[OFF + 6]), "+f"(d[OFF + 7]), "+f"(d[OFF + 8]), "+f"(d[OFF + 9]), "+f"(d[OFF + 10]), "+f"(d[OFF + 11]), "+f"(d[OFF + 12]), "+f"(d[OFF + 13]), "+f"(d[OFF + 14]), "+f"(d[OFF + 15]), "+f"(d[OFF + 16]), "+f"(d[OFF + 17]), "+f"(d[OFF + 18]), "+f"(d[OFF + 19]), "+f"(d[OFF + 20]), "+f"(d[OFF + 21]), "+f"(d[OFF + 22]), "+f"(d[OFF + 23]), "+f"(d[OFF + 24]), "+f"(d[OFF + 25]), "+f"(d[OFF + 26]), "+f"(d[OFF + 27]), "+f"(d[OFF + 28]), "+f"(d[OFF + 29]), "+f"(d[OFF + 30]), "+f"(d[OFF + 31]), "+f"(d[OFF + 32]), "+f"(d[OFF + 33]), "+f"(d[OFF + 34]), "+f"(d[OFF + 35]), "+f"(d[OFF + 36]), "+f"(d[OFF + 37]), "+f"(d[OFF + 38]), "+f"(d[OFF + 39]), "+f"(d[OFF + 40]), "+f"(d[OFF + 41]), "+f"(d[OFF + 42]), "+f"(d[OFF + 43]), "+f"(d[OFF + 44]), "+f"(d[OFF + 45]), "+f"(d[OFF + 46]), "+f"(d[OFF + 47]), "+f"(d[OFF + 48]), "+f"(d[OFF + 49]), "+f"(d[OFF + 50]), "+f"(d[OFF + 51]), "+f"(d[OFF + 52]), "+f"(d[OFF + 53]), "+f"(d[OFF + 54]), "+f"(d[OFF + 55]), "+f"(d[OFF + 56]), "+f"(d[OFF + 57]), "+f"(d[OFF + 58]), "+f"(d[OFF + 59]), "+f"(d[OFF + 60]), "+f"(d[OFF + 61]), "+f"(d[OFF + 62]), "+f"(d[OFF + 63]), "+f"(d[OFF + 64]), "+f"(d[OFF + 65]), "+f"(d[OFF + 66]), "+f"(d[OFF + 67]), "+f"(d[OFF + 68]), "+f"(d[OFF + 69]), "+f"(d[OFF + 70]), "+f"(d[OFF + 71]), "+f"(d[OFF + 72]), "+f"(d[OFF + 73]), "+f"(d[OFF + 74]), "+f"(d[OFF + 75]), "+f"(d[OFF + 76]), "+f"(d[OFF + 77]), "+f"(d[OFF + 78]), "+f"(d[OFF + 79]), "+f"(d[OFF + 80]), "+f"(d[OFF + 81]), "+f"(d[OFF + 82]), "+f"(d[OFF + 83]), "+f"(d[OFF + 84]), "+f"(d[OFF + 85]), "+f"(d[OFF + 86]), "+f"(d[OFF + 87]), "+f"(d[OFF + 88]), "+f"(d[OFF + 89]), "+f"(d[OFF + 90]), "+f"(d[OFF + 91]), "+f"(d[OFF + 92]), "+f"(d[OFF + 93]), "+f"(d[OFF + 94]), "+f"(d[OFF + 95]), "+f"(d[OFF + 96]), "+f"(d[OFF + 97]), "+f"(d[OFF + 98]), "+f"(d[OFF + 99]), "+f"(d[OFF + 100]), "+f"(d[OFF + 101]), "+f"(d[OFF + 102]), "+f"(d[OFF + 103]), "+f"(d[OFF + 104]), "+f"(d[OFF + 105]), "+f"(d[OFF + 106]), "+f"(d[OFF + 107]), "+f"(d[OFF + 108]), "+f"(d[OFF + 109]), "+f"(d[OFF + 110]), "+f"(d[OFF + 111]), "+f"(d[OFF + 112]), "+f"(d[OFF + 113]), "+f"(d[OFF + 114]), "+f"(d[OFF + 115])
            : "r"(a0), "r"(a1), "r"(a2), "r"(a3), "l"(descB), "n"(1));
    }
};
template <int OFF, int NA> struct WG<208, OFF, false, NA> {
    static __device__ __forceinline__ void mma(float (&d)[NA], uint32_t a0, uint32_t a1, uint32_t a2, uint32_t a3, uint64_t descB) {
        asm volatile(
            "{\n"
            ".reg .pred p;\n"
            "setp.ne.b32 p, %109, 0;\n"
            "wgmma.mma_async.sync.aligned.m64n208k16.f32.bf16.bf16 "
            "{%0, %1, %2, %3, %4, %5, %6, %7, %8, %9, %10, %11, %12, %13, %14, %15, %16, %17, %18, %19, %20, %21, %22, %23, %24, %25, %26, %27, %28, %29, %30, %31, %32, %33, %34, %35, %36, %37, %38, %39, %40, %41, %42, %43, %44, %45, %46, %47, %48, %49, %50, %51, %52, %53, %54, %55, %56, %57, %58, %59, %60, %61, %62, %63, %64, %65, %66, %67, %68, %69, %70, %71, %72, %73, %74, %75, %76, %77, %78, %79, %80, %81, %82, %83, %84, %85, %86, %87, %88, %89, %90, %91, %92, %93, %94, %95, %96, %97, %98, %99, %100, %101, %102, %103}, "
            "{%104, %105, %106, %107}, %108, p, 1, 1, 0;\n"
            "}\n"
            : "=f"(d[OFF + 0]), "=f"(d[OFF + 1]), "=f"(d[OFF + 2]), "=f"(d[OFF + 3]), "=f"(d[OFF + 4]), "=f"(d[OFF + 5]), "=f"(d[OFF + 6]), "=f"(d[OFF + 7]), "=f"(d[OFF + 8]), "=f"(d[OFF + 9]), "=f"(d[OFF + 10]), "=f"(d[OFF + 11]), "=f"(d[OFF + 12]), "=f"(d[OFF + 13]), "=f"(d[OFF + 14]), "=f"(d[OFF + 15]), "=f"(d[OFF + 16]), "=f"(d[OFF + 17]), "=f"(d[OFF + 18]), "=f"(d[OFF + 19]), "=f"(d[OFF + 20]), "=f"(d[OFF + 21]), "=f"(d[OFF + 22]), "=f"(d[OFF + 23]), "=f"(d[OFF + 24]), "=f"(d[OFF + 25]), "=f"(d[OFF + 26]), "=f"(d[OFF + 27]), "=f"(d[OFF + 28]), "=f"(d[OFF + 29]), "=f"(d[OFF + 30]), "=f"(d[OFF + 31]), "=f"(d[OFF + 32]), "=f"(d[OFF + 33]), "=f"(d[OFF + 34]), "=f"(d[OFF + 35]), "=f"(d[OFF + 36]), "=f"(d[OFF + 37]), "=f"(d[OFF + 38]), "=f"(d[OFF + 39]), "=f"(d[OFF + 40]), "=f"(d[OFF + 41]), "=f"(d[OFF + 42]), "=f"(d[OFF + 43]), "=f"(d[OFF + 44]), "=f"(d[OFF + 45]), "=f"(d[OFF + 46]), "=f"(d[OFF + 47]), "=f"(d[OFF + 48]), "=f"(d[OFF + 49]), "=f"(d[OFF + 50]), "=f"(d[OFF + 51]), "=f"(d[OFF + 52]), "=f"(d[OFF + 53]), "=f"(d[OFF + 54]), "=f"(d[OFF + 55]), "=f"(d[OFF + 56]), "=f"(d[OFF + 57]), "=f"(d[OFF + 58]), "=f"(d[OFF + 59]), "=f"(d[OFF + 60]), "=f"(d[OFF + 61]), "=f"(d[OFF + 62]), "=f"(d[OFF + 63]), "=f"(d[OFF + 64]), "=f"(d[OFF + 65]), "=f"(d[OFF + 66]), "=f"(d[OFF + 67]), "=f"(d[OFF + 68]), "=f"(d[OFF + 69]), "=f"(d[OFF + 70]), "=f"(d[OFF + 71]), "=f"(d[OFF + 72]), "=f"(d[OFF + 73]), "=f"(d[OFF + 74]), "=f"(d[OFF + 75]), "=f"(d[OFF + 76]), "=f"(d[OFF + 77]), "=f"(d[OFF + 78]), "=f"(d[OFF + 79]), "=f"(d[OFF + 80]), "=f"(d[OFF + 81]), "=f"(d[OFF + 82]), "=f"(d[OFF + 83]), "=f"(d[OFF + 84]), "=f"(d[OFF + 85]), "=f"(d[OFF + 86]), "=f"(d[OFF + 87]), "=f"(d[OFF + 88]), "=f"(d[OFF + 89]), "=f"(d[OFF + 90]), "=f"(d[OFF + 91]), "=f"(d[OFF + 92]), "=f"(d[OFF + 93]), "=f"(d[OFF + 94]), "=f"(d[OFF + 95]), "=f"(d[OFF + 96]), "=f"(d[OFF + 97]), "=f"(d[OFF + 98]), "=f"(d[OFF + 99]), "=f"(d[OFF + 100]), "=f"(d[OFF + 101]), "=f"(d[OFF + 102]), "=f"(d[OFF + 103])
            : "r"(a0), "r"(a1), "r"(a2), "r"(a3), "l"(descB), "n"(0));
    }
};
template <int OFF, int NA> struct WG<208, OFF, true, NA> {
    static __device__ __forceinline__ void mma(float (&d)[NA], uint32_t a0, uint32_t a1, uint32_t a2, uint32_t a3, uint64_t descB) {
        asm volatile(
            "{\n"
            ".reg .pred p;\n"
            "setp.ne.b32 p, %109, 0;\n"
            "wgmma.mma_async.sync.aligned.m64n208k16.f32.bf16.bf16 "
            "{%0, %1, %2, %3, %4, %5, %6, %7, %8, %9, %10, %11, %12, %13, %14, %15, %16, %17, %18, %19, %20, %21, %22, %23, %24, %25, %26, %27, %28, %29, %30, %31, %32, %33, %34, %35, %36, %37, %38, %39, %40, %41, %42, %43, %44, %45, %46, %47, %48, %49, %50, %51, %52, %53, %54, %55, %56, %57, %58, %59, %60, %61, %62, %63, %64, %65, %66, %67, %68, %69, %70, %71, %72, %73, %74, %75, %76, %77, %78, %79, %80, %81, %82, %83, %84, %85, %86, %87, %88, %89, %90, %91, %92, %93, %94, %95, %96, %97, %98, %99, %100, %101, %102, %103}, "
            "{%104, %105, %106, %107}, %108, p, 1, 1, 0;\n"
            "}\n"
            : "+f"(d[OFF + 0]), "+f"(d[OFF + 1]), "+f"(d[OFF + 2]), "+f"(d[OFF + 3]), "+f"(d[OFF + 4]), "+f"(d[OFF + 5]), "+f"(d[OFF + 6]), "+f"(d[OFF + 7]), "+f"(d[OFF + 8]), "+f"(d[OFF + 9]), "+f"(d[OFF + 10]), "+f"(d[OFF + 11]), "+f"(d[OFF + 12]), "+f"(d[OFF + 13]), "+f"(d[OFF + 14]), "+f"(d[OFF + 15]), "+f"(d[OFF + 16]), "+f"(d[OFF + 17]), "+f"(d[OFF + 18]), "+f"(d[OFF + 19]), "+f"(d[OFF + 20]), "+f"(d[OFF + 21]), "+f"(d[OFF + 22]), "+f"(d[OFF + 23]), "+f"(d[OFF + 24]), "+f"(d[OFF + 25]), "+f"(d[OFF + 26]), "+f"(d[OFF + 27]), "+f"(d[OFF + 28]), "+f"(d[OFF + 29]), "+f"(d[OFF + 30]), "+f"(d[OFF + 31]), "+f"(d[OFF + 32]), "+f"(d[OFF + 33]), "+f"(d[OFF + 34]), "+f"(d[OFF + 35]), "+f"(d[OFF + 36]), "+f"(d[OFF + 37]), "+f"(d[OFF + 38]), "+f"(d[OFF + 39]), "+f"(d[OFF + 40]), "+f"(d[OFF + 41]), "+f"(d[OFF + 42]), "+f"(d[OFF + 43]), "+f"(d[OFF + 44]), "+f"(d[OFF + 45]), "+f"(d[OFF + 46]), "+f"(d[OFF + 47]), "+f"(d[OFF + 48]), "+f"(d[OFF + 49]), "+f"(d[OFF + 50]), "+f"(d[OFF + 51]), "+f"(d[OFF + 52]), "+f"(d[OFF + 53]), "+f"(d[OFF + 54]), "+f"(d[OFF + 55]), "+f"(d[OFF + 56]), "+f"(d[OFF + 57]), "+f"(d[OFF + 58]), "+f"(d[OFF + 59]), "+f"(d[OFF + 60]), "+f"(d[OFF + 61]), "+f"(d[OFF + 62]), "+f"(d[OFF + 63]), "+f"(d[OFF + 64]), "+f"(d[OFF + 65]), "+f"(d[OFF + 66]), "+f"(d[OFF + 67]), "+f"(d[OFF + 68]), "+f"(d[OFF + 69]), "+f"(d[OFF + 70]), "+f"(d[OFF + 71]), "+f"(d[OFF + 72]), "+f"(d[OFF + 73]), "+f"(d[OFF + 74]), "+f"(d[OFF + 75]), "+f"(d[OFF + 76]), "+f"(d[OFF + 77]), "+f"(d[OFF + 78]), "+f"(d[OFF + 79]), "+f"(d[OFF + 80]), "+f"(d[OFF + 81]), "+f"(d[OFF + 82]), "+f"(d[OFF + 83]), "+f"(d[OFF + 84]), "+f"(d[OFF + 85]), "+f"(d[OFF + 86]), "+f"(d[OFF + 87]), "+f"(d[OFF + 88]), "+f"(d[OFF + 89]), "+f"(d[OFF + 90]), "+f"(d[OFF + 91]), "+f"(d[OFF + 92]), "+f"(d[OFF + 93]), "+f"(d[OFF + 94]), "+f"(d[OFF + 95]), "+f"(d[OFF + 96]), "+f"(d[OFF + 97]), "+f"(d[OFF + 98]), "+f"(d[OFF + 99]), "+f"(d[OFF + 100]), "+f"(d[OFF + 101]), "+f"(d[OFF + 102]), "+f"(d[OFF + 103])
            : "r"(a0), "r"(a1), "r"(a2), "r"(a3), "l"(descB), "n"(1));
    }
};
template <int OFF, int NA> struct WG<120, OFF, false, NA> {
    static __device__ __forceinline__ void mma(float (&d)[NA], uint32_t a0, uint32_t a1, uint32_t a2, uint32_t a3, uint64_t descB) {
        asm volatile(
            "{\n"
            ".reg .pred p;\n"
            "setp.ne.b32 p, %65, 0;\n"
            "wgmma.mma_async.sync.aligned.m64n120k16.f32.bf16.bf16 "
            "{%0, %1, %2, %3, %4, %5, %6, %7, %8, %9, %10, %11, %12, %13, %14, %15, %16, %17, %18, %19, %20, %21, %22, %23, %24, %25, %26, %27, %28, %29, %30, %31, %32, %33, %34, %35, %36, %37, %38, %39, %40, %41, %42, %43, %44, %45, %46, %47, %48, %49, %50, %51, %52, %53, %54, %55, %56, %57, %58, %59}, "
            "{%60, %61, %62, %63}, %64, p, 1, 1, 0;\n"
            "}\n"
            : "=f"(d[OFF + 0]), "=f"(d[OFF + 1]), "=f"(d[OFF + 2]), "=f"(d[OFF + 3]), "=f"(d[OFF + 4]), "=f"(d[OFF + 5]), "=f"(d[OFF + 6]), "=f"(d[OFF + 7]), "=f"(d[OFF + 8]), "=f"(d[OFF + 9]), "=f"(d[OFF + 10]), "=f"(d[OFF + 11]), "=f"(d[OFF + 12]), "=f"(d[OFF + 13]), "=f"(d[OFF + 14]), "=f"(d[OFF + 15]), "=f"(d[OFF + 16]), "=f"(d[OFF + 17]), "=f"(d[OFF + 18]), "=f"(d[OFF + 19]), "=f"(d[OFF + 20]), "=f"(d[OFF + 21]), "=f"(d[OFF + 22]), "=f"(d[OFF + 23]), "=f"(d[OFF + 24]), "=f"(d[OFF + 25]), "=f"(d[OFF + 26]), "=f"(d[OFF + 27]), "=f"(d[OFF + 28]), "=f"(d[OFF + 29]), "=f"(d[OFF + 30]), "=f"(d[OFF + 31]), "=f"(d[OFF + 32]), "=f"(d[OFF + 33]), "=f"(d[OFF + 34]), "=f"(d[OFF + 35]), "=f"(d[OFF + 36]), "=f"(d[OFF + 37]), "=f"(d[OFF + 38]), "=f"(d[OFF + 39]), "=f"(d[OFF + 40]), "=f"(d[OFF + 41]), "=f"(d[OFF + 42]), "=f"(d[OFF + 43]), "=f"(d[OFF + 44]), "=f"(d[OFF + 45]), "=f"(d[OFF + 46]), "=f"(d[OFF + 47]), "=f"(d[OFF + 48]), "=f"(d[OFF + 49]), "=f"(d[OFF + 50]), "=f"(d[OFF + 51]), "=f"(d[OFF + 52]), "=f"(d[OFF + 53]), "=f"(d[OFF + 54]), "=f"(d[OFF + 55]), "=f"(d[OFF + 56]), "=f"(d[OFF + 57]), "=f"(d[OFF + 58]), "=f"(d[OFF + 59])
            : "r"(a0), "r"(a1), "r"(a2), "r"(a3), "l"(descB), "n"(0));
    }
};
template <int OFF, int NA> struct WG<120, OFF, true, NA> {
    static __device__ __forceinline__ void mma(float (&d)[NA], uint32_t a0, uint32_t a1, uint32_t a2, uint32_t a3, uint64_t descB) {
        asm volatile(
            "{\n"
            ".reg .pred p;\n"
            "setp.ne.b32 p, %65, 0;\n"
            "wgmma.mma_async.sync.aligned.m64n120k16.f32.bf16.bf16 "
            "{%0, %1, %2, %3, %4, %5, %6, %7, %8, %9, %10, %11, %12, %13, %14, %15, %16, %17, %18, %19, %20, %21, %22, %23, %24, %25, %26, %27, %28, %29, %30, %31, %32, %33, %34, %35, %36, %37, %38, %39, %40, %41, %42, %43, %44, %45, %46, %47, %48, %49, %50, %51, %52, %53, %54, %55, %56, %57, %58, %59}, "
            "{%60, %61, %62, %63}, %64, p, 1, 1, 0;\n"
            "}\n"
            : "+f"(d[OFF + 0]), "+f"(d[OFF + 1]), "+f"(d[OFF + 2]), "+f"(d[OFF + 3]), "+f"(d[OFF + 4]), "+f"(d[OFF + 5]), "+f"(d[OFF + 6]), "+f"(d[OFF + 7]), "+f"(d[OFF + 8]), "+f"(d[OFF + 9]), "+f"(d[OFF + 10]), "+f"(d[OFF + 11]), "+f"(d[OFF + 12]), "+f"(d[OFF + 13]), "+f"(d[OFF + 14]), "+f"(d[OFF + 15]), "+f"(d[OFF + 16]), "+f"(d[OFF + 17]), "+f"(d[OFF + 18]), "+f"(d[OFF + 19]), "+f"(d[OFF + 20]), "+f"(d[OFF + 21]), "+f"(d[OFF + 22]), "+f"(d[OFF + 23]), "+f"(d[OFF + 24]), "+f"(d[OFF + 25]), "+f"(d[OFF + 26]), "+f"(d[OFF + 27]), "+f"(d[OFF + 28]), "+f"(d[OFF + 29]), "+f"(d[OFF + 30]), "+f"(d[OFF + 31]), "+f"(d[OFF + 32]), "+f"(d[OFF + 33]), "+f"(d[OFF + 34]), "+f"(d[OFF + 35]), "+f"(d[OFF + 36]), "+f"(d[OFF + 37]), "+f"(d[OFF + 38]), "+f"(d[OFF + 39]), "+f"(d[OFF + 40]), "+f"(d[OFF + 41]), "+f"(d[OFF + 42]), "+f"(d[OFF + 43]), "+f"(d[OFF + 44]), "+f"(d[OFF + 45]), "+f"(d[OFF + 46]), "+f"(d[OFF + 47]), "+f"(d[OFF + 48]), "+f"(d[OFF + 49]), "+f"(d[OFF + 50]), "+f"(d[OFF + 51]), "+f"(d[OFF + 52]), "+f"(d[OFF + 53]), "+f"(d[OFF + 54]), "+f"(d[OFF + 55]), "+f"(d[OFF + 56]), "+f"(d[OFF + 57]), "+f"(d[OFF + 58]), "+f"(d[OFF + 59])
            : "r"(a0), "r"(a1), "r"(a2), "r"(a3), "l"(descB), "n"(1));
    }
};
template <int OFF, int NA> struct WG<112, OFF, false, NA> {
    static __device__ __forceinline__ void mma(float (&d)[NA], uint32_t a0, uint32_t a1, uint32_t a2, uint32_t a3, uint64_t descB) {
        asm volatile(
            "{\n"
            ".reg .pred p;\n"
            "setp.ne.b32 p, %61, 0;\n"
            "wgmma.mma_async.sync.aligned.m64n112k16.f32.bf16.bf16 "
            "{%0, %1, %2, %3, %4, %5, %6, %7, %8, %9, %10, %11, %12, %13, %14, %15, %16, %17, %18, %19, %20, %21, %22, %23, %24, %25, %26, %27, %28, %29, %30, %31, %32, %33, %34, %35, %36, %37, %38, %39, %40, %41, %42, %43, %44, %45, %46, %47, %48, %49, %50, %51, %52, %53, %54, %55}, "
            "{%56, %57, %58, %59}, %60, p, 1, 1, 0;\n"
            "}\n"
            : "=f"(d[OFF + 0]), "=f"(d[OFF + 1]), "=f"(d[OFF + 2]), "=f"(d[OFF + 3]), "=f"(d[OFF + 4]), "=f"(d[OFF + 5]), "=f"(d[OFF + 6]), "=f"(d[OFF + 7]), "=f"(d[OFF + 8]), "=f"(d[OFF + 9]), "=f"(d[OFF + 10]), "=f"(d[OFF + 11]), "=f"(d[OFF + 12]), "=f"(d[OFF + 13]), "=f"(d[OFF + 14]), "=f"(d[OFF + 15]), "=f"(d[OFF + 16]), "=f"(d[OFF + 17]), "=f"(d[OFF + 18]), "=f"(d[OFF + 19]), "=f"(d[OFF + 20]), "=f"(d[OFF + 21]), "=f"(d[OFF + 22]), "=f"(d[OFF + 23]), "=f"(d[OFF + 24]), "=f"(d[OFF + 25]), "=f"(d[OFF + 26]), "=f"(d[OFF + 27]), "=f"(d[OFF + 28]), "=f"(d[OFF + 29]), "=f"(d[OFF + 30]), "=f"(d[OFF + 31]), "=f"(d[OFF + 32]), "=f"(d[OFF + 33]), "=f"(d[OFF + 34]), "=f"(d[OFF + 35]), "=f"(d[OFF + 36]), "=f"(d[OFF + 37]), "=f"(d[OFF + 38]), "=f"(d[OFF + 39]), "=f"(d[OFF + 40]), "=f"(d[OFF + 41]), "=f"(d[OFF + 42]), "=f"(d[OFF + 43]), "=f"(d[OFF + 44]), "=f"(d[OFF + 45]), "=f"(d[OFF + 46]), "=f"(d[OFF + 47]), "=f"(d[OFF + 48]), "=f"(d[OFF + 49]), "=f"(d[OFF + 50]), "=f"(d[OFF + 51]), "=f"(d[OFF + 52]), "=f"(d[OFF + 53]), "=f"(d[OFF + 54]), "=f"(d[OFF + 55])
            : "r"(a0), "r"(a1), "r"(a2), "r"(a3), "l"(descB), "n"(0));
    }
};
template <int OFF, int NA> struct WG<112, OFF, true, NA> {
    static __device__ __forceinline__ void mma(float (&d)[NA], uint32_t a0, uint32_t a1, uint32_t a2, uint32_t a3, uint64_t descB) {
        asm volatile(
            "{\n"
            ".reg .pred p;\n"
            "setp.ne.b32 p, %61, 0;\n"
            "wgmma.mma_async.sync.aligned.m64n112k16.f32.bf16.bf16 "
            "{%0, %1, %2, %3, %4, %5, %6, %7, %8, %9, %10, %11, %12, %13, %14, %15, %16, %17, %18, %19, %20, %21, %22, %23, %24, %25, %26, %27, %28, %29, %30, %31, %32, %33, %34, %35, %36, %37, %38, %39, %40, %41, %42, %43, %44, %45, %46, %47, %48, %49, %50, %51, %52, %53, %54, %55}, "
            "{%56, %57, %58, %59}, %60, p, 1, 1, 0;\n"
            "}\n"
            : "+f"(d[OFF + 0]), "+f"(d[OFF + 1]), "+f"(d[OFF + 2]), "+f"(d[OFF + 3]), "+f"(d[OFF + 4]), "+f"(d[OFF + 5]), "+f"(d[OFF + 6]), "+f"(d[OFF + 7]), "+f"(d[OFF + 8]), "+f"(d[OFF + 9]), "+f"(d[OFF + 10]), "+f"(d[OFF + 11]), "+f"(d[OFF + 12]), "+f"(d[OFF + 13]), "+f"(d[OFF + 14]), "+f"(d[OFF + 15]), "+f"(d[OFF + 16]), "+f"(d[OFF + 17]), "+f"(d[OFF + 18]), "+f"(d[OFF + 19]), "+f"(d[OFF + 20]), "+f"(d[OFF + 21]), "+f"(d[OFF + 22]), "+f"(d[OFF + 23]), "+f"(d[OFF + 24]), "+f"(d[OFF + 25]), "+f"(d[OFF + 26]), "+f"(d[OFF + 27]), "+f"(d[OFF + 28]), "+f"(d[OFF + 29]), "+f"(d[OFF + 30]), "+f"(d[OFF + 31]), "+f"(d[OFF + 32]), "+f"(d[OFF + 33]), "+f"(d[OFF + 34]), "+f"(d[OFF + 35]), "+f"(d[OFF + 36]), "+f"(d[OFF + 37]), "+f"(d[OFF + 38]), "+f"(d[OFF + 39]), "+f"(d[OFF + 40]), "+f"(d[OFF + 41]), "+f"(d[OFF + 42]), "+f"(d[OFF + 43]), "+f"(d[OFF + 44]), "+f"(d[OFF + 45]), "+f"(d[OFF + 46]), "+f"(d[OFF + 47]), "+f"(d[OFF + 48]), "+f"(d[OFF + 49]), "+f"(d[OFF + 50]), "+f"(d[OFF + 51]), "+f"(d[OFF + 52]), "+f"(d[OFF + 53]), "+f"(d[OFF + 54]), "+f"(d[OFF + 55])
            : "r"(a0), "r"(a1), "r"(a2), "r"(a3), "l"(descB), "n"(1));
    }
};
template <int OFF, int NA> struct WG<96, OFF, false, NA> {
    static __device__ __forceinline__ void mma(float (&d)[NA], uint32_t a0, uint32_t a1, uint32_t a2, uint32_t a3, uint64_t descB) {
        asm volatile(
            "{\n"
            ".reg .pred p;\n"
            "setp.ne.b32 p, %53, 0;\n"
            "wgmma.mma_async.sync.aligned.m64n96k16.f32.bf16.bf16 "
            "{%0, %1, %2, %3, %4, %5, %6, %7, %8, %9, %10, %11, %12, %13, %14, %15, %16, %17, %18, %19, %20, %21, %22, %23, %24, %25, %26, %27, %28, %29, %30, %31, %32, %33, %34, %35, %36, %37, %38, %39, %40, %41, %42, %43, %44, %45, %46, %47}, "
            "{%48, %49, %50, %51}, %52, p, 1, 1, 0;\n"
            "}\n"
            : "=f"(d[OFF + 0]), "=f"(d[OFF + 1]), "=f"(d[OFF + 2]), "=f"(d[OFF + 3]), "=f"(d[OFF + 4]), "=f"(d[OFF + 5]), "=f"(d[OFF + 6]), "=f"(d[OFF + 7]), "=f"(d[OFF + 8]), "=f"(d[OFF + 9]), "=f"(d[OFF + 10]), "=f"(d[OFF + 11]), "=f"(d[OFF + 12]), "=f"(d[OFF + 13]), "=f"(d[OFF + 14]), "=f"(d[OFF + 15]), "=f"(d[OFF + 16]), "=f"(d[OFF + 17]), "=f"(d[OFF + 18]), "=f"(d[OFF + 19]), "=f"(d[OFF + 20]), "=f"(d[OFF + 21]), "=f"(d[OFF + 22]), "=f"(d[OFF + 23]), "=f"(d[OFF + 24]), "=f"(d[OFF + 25]), "=f"(d[OFF + 26]), "=f"(d[OFF + 27]), "=f"(d[OFF + 28]), "=f"(d[OFF + 29]), "=f"(d[OFF + 30]), "=f"(d[OFF + 31]), "=f"(d[OFF + 32]), "=f"(d[OFF + 33]), "=f"(d[OFF + 34]), "=f"(d[OFF + 35]), "=f"(d[OFF + 36]), "=f"(d[OFF + 37]), "=f"(d[OFF + 38]), "=f"(d[OFF + 39]), "=f"(d[OFF + 40]), "=f"(d[OFF + 41]), "=f"(d[OFF + 42]), "=f"(d[OFF + 43]), "=f"(d[OFF + 44]), "=f"(d[OFF + 45]), "=f"(d[OFF + 46]), "=f"(d[OFF + 47])
            : "r"(a0), "r"(a1), "r"(a2), "r"(a3), "l"(descB), "n"(0));
    }
};
template <int OFF, int NA> struct WG<96, OFF, true, NA> {
    static __device__ __forceinline__ void mma(float (&d)[NA], uint32_t a0, uint32_t a1, uint32_t a2, uint32_t a3, uint64_t descB) {
        asm volatile(
            "{\n"
            ".reg .pred p;\n"
            "setp.ne.b32 p, %53, 0;\n"
            "wgmma.mma_async.sync.aligned.m64n96k16.f32.bf16.bf16 "
            "{%0, %1, %2, %3, %4, %5, %6, %7, %8, %9, %10, %11, %12, %13, %14, %15, %16, %17, %18, %19, %20, %21, %22, %23, %24, %25, %26, %27, %28, %29, %30, %31, %32, %33, %34, %35, %36, %37, %38, %39, %40, %41, %42, %43, %44, %45, %46, %47}, "
            "{%48, %49, %50, %51}, %52, p, 1, 1, 0;\n"
            "}\n"
            : "+f"(d[OFF + 0]), "+f"(d[OFF + 1]), "+f"(d[OFF + 2]), "+f"(d[OFF + 3]), "+f"(d[OFF + 4]), "+f"(d[OFF + 5]), "+f"(d[OFF + 6]), "+f"(d[OFF + 7]), "+f"(d[OFF + 8]), "+f"(d[OFF + 9]), "+f"(d[OFF + 10]), "+f"(d[OFF + 11]), "+f"(d[OFF + 12]), "+f"(d[OFF + 13]), "+f"(d[OFF + 14]), "+f"(d[OFF + 15]), "+f"(d[OFF + 16]), "+f"(d[OFF + 17]), "+f"(d[OFF + 18]), "+f"(d[OFF + 19]), "+f"(d[OFF + 20]), "+f"(d[OFF + 21]), "+f"(d[OFF + 22]), "+f"(d[OFF + 23]), "+f"(d[OFF + 24]), "+f"(d[OFF + 25]), "+f"(d[OFF + 26]), "+f"(d[OFF + 27]), "+f"(d[OFF + 28]), "+f"(d[OFF + 29]), "+f"(d[OFF + 30]), "+f"(d[OFF + 31]), "+f"(d[OFF + 32]), "+f"(d[OFF + 33]), "+f"(d[OFF + 34]), "+f"(d[OFF + 35]), "+f"(d[OFF + 36]), "+f"(d[OFF + 37]), "+f"(d[OFF + 38]), "+f"(d[OFF + 39]), "+f"(d[OFF + 40]), "+f"(d[OFF + 41]), "+f"(d[OFF + 42]), "+f"(d[OFF + 43]), "+f"(d[OFF + 44]), "+f"(d[OFF + 45]), "+f"(d[OFF + 46]), "+f"(d[OFF + 47])
            : "r"(a0), "r"(a1), "r"(a2), "r"(a3), "l"(descB), "n"(1));
    }
};
template <int OFF, int NA> struct WG<64, OFF, true, NA> {
    static __device__ __forceinline__ void mma(float (&d)[NA], uint32_t a0, uint32_t a1, uint32_t a2, uint32_t a3, uint64_t descB) {
        asm volatile(
            "{\n"
            ".reg .pred p;\n"
            "setp.ne.b32 p, %37, 0;\n"
            "wgmma.mma_async.sync.aligned.m64n64k16.f32.bf16.bf16 "
            "{%0, %1, %2, %3, %4, %5, %6, %7, %8, %9, %10, %11, %12, %13, %14, %15, %16, %17, %18, %19, %20, %21, %22, %23, %24, %25, %26, %27, %28, %29, %30, %31}, "
            "{%32, %33, %34, %35}, %36, p, 1, 1, 0;\n"
            "}\n"
            : "+f"(d[OFF + 0]), "+f"(d[OFF + 1]), "+f"(d[OFF + 2]), "+f"(d[OFF + 3]), "+f"(d[OFF + 4]), "+f"(d[OFF + 5]), "+f"(d[OFF + 6]), "+f"(d[OFF + 7]), "+f"(d[OFF + 8]), "+f"(d[OFF + 9]), "+f"(d[OFF + 10]), "+f"(d[OFF + 11]), "+f"(d[OFF + 12]), "+f"(d[OFF + 13]), "+f"(d[OFF + 14]), "+f"(d[OFF + 15]), "+f"(d[OFF + 16]), "+f"(d[OFF + 17]), "+f"(d[OFF + 18]), "+f"(d[OFF + 19]), "+f"(d[OFF + 20]), "+f"(d[OFF + 21]), "+f"(d[OFF + 22]), "+f"(d[OFF + 23]), "+f"(d[OFF + 24]), "+f"(d[OFF + 25]), "+f"(d[OFF + 26]), "+f"(d[OFF + 27]), "+f"(d[OFF + 28]), "+f"(d[OFF + 29]), "+f"(d[OFF + 30]), "+f"(d[OFF + 31])
            : "r"(a0), "r"(a1), "r"(a2), "r"(a3), "l"(descB), "n"(1));
    }
};
template <int OFF, int NA> struct WG<48, OFF, true, NA> {
    static __device__ __forceinline__ void mma(float (&d)[NA], uint32_t a0, uint32_t a1, uint32_t a2, uint32_t a3, uint64_t descB) {
        asm volatile(
            "{\n"
            ".reg .pred p;\n"
            "setp.ne.b32 p, %29, 0;\n"
            "wgmma.mma_async.sync.aligned.m64n48k16.f32.bf16.bf16 "
            "{%0, %1, %2, %3, %4, %5, %6, %7, %8, %9, %10, %11, %12, %13, %14, %15, %16, %17, %18, %19, %20, %21, %22, %23}, "
            "{%24, %25, %26, %27}, %28, p, 1, 1, 0;\n"
            "}\n"
            : "+f"(d[OFF + 0]), "+f"(d[OFF + 1]), "+f"(d[OFF + 2]), "+f"(d[OFF + 3]), "+f"(d[OFF + 4]), "+f"(d[OFF + 5]), "+f"(d[OFF + 6]), "+f"(d[OFF + 7]), "+f"(d[OFF + 8]), "+f"(d[OFF + 9]), "+f"(d[OFF + 10]), "+f"(d[OFF + 11]), "+f"(d[OFF + 12]), "+f"(d[OFF + 13]), "+f"(d[OFF + 14]), "+f"(d[OFF + 15]), "+f"(d[OFF + 16]), "+f"(d[OFF + 17]), "+f"(d[OFF + 18]), "+f"(d[OFF + 19]), "+f"(d[OFF + 20]), "+f"(d[OFF + 21]), "+f"(d[OFF + 22]), "+f"(d[OFF + 23])
            : "r"(a0), "r"(a1), "r"(a2), "r"(a3), "l"(descB), "n"(1));
    }
};
template <int OFF, int NA> struct WG<32, OFF, true, NA> {
    static __device__ __forceinline__ void mma(float (&d)[NA], uint32_t a0, uint32_t a1, uint32_t a2, uint32_t a3, uint64_t descB) {
        asm volatile(
            "{\n"
            ".reg .pred p;\n"
            "setp.ne.b32 p, %21, 0;\n"
            "wgmma.mma_async.sync.aligned.m64n32k16.f32.bf16.bf16 "
            "{%0, %1, %2, %3, %4, %5, %6, %7, %8, %9, %10, %11, %12, %13, %14, %15}, "
            "{%16, %17, %18, %19}, %20, p, 1, 1, 0;\n"
            "}\n"
            : "+f"(d[OFF + 0]), "+f"(d[OFF + 1]), "+f"(d[OFF + 2]), "+f"(d[OFF + 3]), "+f"(d[OFF + 4]), "+f"(d[OFF + 5]), "+f"(d[OFF + 6]), "+f"(d[OFF + 7]), "+f"(d[OFF + 8]), "+f"(d[OFF + 9]), "+f"(d[OFF + 10]), "+f"(d[OFF + 11]), "+f"(d[OFF + 12]), "+f"(d[OFF + 13]), "+f"(d[OFF + 14]), "+f"(d[OFF + 15])
            : "r"(a0), "r"(a1), "r"(a2), "r"(a3), "l"(descB), "n"(1));
    }
};

__device__ __forceinline__ int round_time(int r) { return DLY_R0 + r * DLY_R; }
__device__ __forceinline__ void unit_pos(uint32_t u, uint32_t& q, uint32_t& fg) {
    static_assert(W1_FG == 64 && W2_FG == 48, "unit order");
    const uint32_t r = u - NQ * W1_FG, q2 = (r * 1366) >> 16;
    q = u < NQ * W1_FG ? u >> 6 : q2;
    fg = u < NQ * W1_FG ? u & 63 : W1_FG + r - q2 * 48;
}
template <class T> __device__ __forceinline__ T* add_off(T* p, uint32_t bytes) {
    uint64_t r;
    asm("{\n.reg .b64 o;\ncvt.u64.u32 o, %2;\nadd.u64 %0, %1, o;\n}\n" : "=l"(r) : "l"(p), "r"(bytes));
    return (T*)r;
}
__device__ __forceinline__ uint32_t unit_src(uint32_t q, uint32_t fg) { return q * (32 * kN * 4) + fg * 128; }
__device__ __forceinline__ uint32_t lane_src(int lane) { return (lane >> 3) * (2 * kN * 4) + (lane & 7) * 16; }
__device__ __forceinline__ uint32_t unit_dst(uint32_t q, uint32_t fg) {
    return ((fg >> 2) * KSTEPS + (q >> 1)) * 8192 + (fg & 3) * 2048 + (q & 1) * 512;
}
__device__ __forceinline__ uint32_t lane_dst(int lane) { return ((lane >> 2) & 1) * 1024 + (lane & 3) * 128 + (lane >> 3) * 8; }
__device__ __forceinline__ constexpr int unit_row(int i) { return 16 * (i >> 2) + 8 * ((i >> 1) & 1) + (i & 1); }
__device__ __forceinline__ void load_unit(uint4 (&v)[8], const int* p) {
#pragma unroll
    for (int i = 0; i < 8; i++) v[i] = ldg_stream(p + (size_t)unit_row(i) * kN);
}
__device__ __forceinline__ uint32_t bytes4(uint32_t v0, uint32_t v1, uint32_t v2, uint32_t v3) {
    return prmt(prmt(v0, v1, 0x0040), prmt(v2, v3, 0x0040), 0x5410);
}
__device__ __forceinline__ void pk_gather(uint32_t (&e)[4], uint32_t (&o)[4], const uint4 (&v)[8]) {
    e[0] = bytes4(v[0].x, v[2].x, v[4].x, v[6].x); o[0] = bytes4(v[1].x, v[3].x, v[5].x, v[7].x);
    e[1] = bytes4(v[0].y, v[2].y, v[4].y, v[6].y); o[1] = bytes4(v[1].y, v[3].y, v[5].y, v[7].y);
    e[2] = bytes4(v[0].z, v[2].z, v[4].z, v[6].z); o[2] = bytes4(v[1].z, v[3].z, v[5].z, v[7].z);
    e[3] = bytes4(v[0].w, v[2].w, v[4].w, v[6].w); o[3] = bytes4(v[1].w, v[3].w, v[5].w, v[7].w);
}
__device__ __forceinline__ void pk_write(u64* p, const uint32_t (&e)[4], const uint32_t (&o)[4], uint32_t tag) {
#pragma unroll
    for (int c = 0; c < 4; c++) {
        uint32_t w;
        asm("lop3.b32 %0, %1, %2, 0x0f0f0f0f, 0xe4;" : "=r"(w) : "r"(e[c]), "r"(o[c] << 4));
        ll_store(p + 4 * c, w, tag);
    }
}

__device__ __forceinline__ void tile0_of(int c, int& fp, int& m0) {
    if (c < 18) { fp = c >= 9; m0 = min((c - 9 * fp) * N0, kM - N0); }
    else { fp = 2 + ((c - 18) >> 3); m0 = ((c - 18) & 7) * N0; }
}
__device__ __forceinline__ void tile1_of(int c, int& fp, int& m0) {
    if (c < 6) { fp = 2 + c; m0 = kM - N1; }
    else { fp = 8 + (c - 6) / 10; m0 = min(((c - 6) % 10) * N1, kM - N1); }
}

__device__ __forceinline__ void ll_fetch(u64 (&c)[4], const char* p) {
    asm volatile("ld.relaxed.gpu.global.b64 %0, [%4];\nld.relaxed.gpu.global.b64 %1, [%4 + 256];\n"
                 "ld.relaxed.gpu.global.b64 %2, [%4 + 512];\nld.relaxed.gpu.global.b64 %3, [%4 + 768];"
                 : "=l"(c[0]), "=l"(c[1]), "=l"(c[2]), "=l"(c[3]) : "l"(p) : "memory");
}
__device__ __forceinline__ void ll_copy(uint32_t dst, const char* src, uint32_t bar) {
    asm volatile("{\n.reg .pred p;\nelect.sync _|p, 0xffffffff;\n"
                 "@p cp.async.bulk.shared::cluster.global.mbarrier::complete_tx::bytes [%0], [%1], 1024, [%2];\n}\n"
                 ::"r"(dst), "l"(src), "r"(bar) : "memory");
}
__device__ __forceinline__ void ll_read(u64 (&c)[4], uint32_t a) {
    asm volatile("ld.volatile.shared.b64 %0, [%4];\nld.volatile.shared.b64 %1, [%4 + 256];\n"
                 "ld.volatile.shared.b64 %2, [%4 + 512];\nld.volatile.shared.b64 %3, [%4 + 768];"
                 : "=l"(c[0]), "=l"(c[1]), "=l"(c[2]), "=l"(c[3]) : "r"(a) : "memory");
}
template <int NS>
__device__ __forceinline__ void ll_check(u64 (&c)[4], uint32_t a, uint32_t dst, const char* src, uint32_t bar, uint32_t tag) {
    asm volatile(
        "{\n.reg .pred p, q;\n.reg .b32 l, h0, h1, x, i;\n"
        "mov.u32 i, 0;\n"
        "L_%=:\n"
        "mov.b64 {l, h0}, %0;\nmov.b64 {l, h1}, %1;\n"
        "lop3.b32 x, %8, h0, h1, 0x7e;\n"
        "mov.b64 {l, h0}, %2;\nmov.b64 {l, h1}, %3;\n"
        "lop3.b32 x, x, %8, h0, 0xf6;\n"
        "lop3.b32 x, x, %8, h1, 0xf6;\n"
        "setp.ne.u32 p, x, 0;\n"
        "vote.sync.any.pred p, p, 0xffffffff;\n"
        "@!p bra D_%=;\n"
        "add.u32 i, i, 1;\n"
        "and.b32 x, i, %10;\n"
        "setp.ne.u32 q, x, 0;\n"
        "@q bra R_%=;\n"
        "elect.sync _|q, 0xffffffff;\n"
        "@q mbarrier.expect_tx.relaxed.cta.shared::cta.b64 [%7], 1024;\n"
        "@q cp.async.bulk.shared::cluster.global.mbarrier::complete_tx::bytes [%5], [%6], 1024, [%7];\n"
        "R_%=:\n"
        "ld.volatile.shared.b64 %0, [%4];\nld.volatile.shared.b64 %1, [%4 + 256];\n"
        "ld.volatile.shared.b64 %2, [%4 + 512];\nld.volatile.shared.b64 %3, [%4 + 768];\n"
        "setp.lt.u32 p, i, %9;\n"
        "@p bra L_%=;\n"
        "D_%=:\n}\n"
        : "+l"(c[0]), "+l"(c[1]), "+l"(c[2]), "+l"(c[3])
        : "r"(a), "r"(dst), "l"(src), "r"(bar), "r"(tag), "n"(SPIN_LIMIT), "n"(NS - 1) : "memory");
}
__device__ __forceinline__ void ll_poll(u64 (&c)[4], const char* p, uint32_t tag) {
    unsigned it = 0;
    do {
        ll_fetch(c, p);
    } while (__any_sync(0xffffffffu, (((uint32_t)(c[0] >> 32) ^ tag) | ((uint32_t)(c[1] >> 32) ^ tag) |
                                      ((uint32_t)(c[2] >> 32) ^ tag) | ((uint32_t)(c[3] >> 32) ^ tag)) != 0) &&
             ++it < (SPIN_LIMIT >> 4));
}
__device__ __forceinline__ void decode_alu(uint32_t& r0, uint32_t& r1, uint32_t& r2, uint32_t& r3, uint32_t w,
                                           const uint32_t (&lt)[8]) {
    const uint32_t s0 = w & 0x77777777u, s1 = s0 >> 16, w4 = w * 16;
    const uint32_t m0 = prmt(w4, w, 0xd9c8), m1 = prmt(w4, w, 0xfbea);
    const uint32_t l0 = (prmt(lt[0], lt[1], s0) & ~m0) | (prmt(lt[2], lt[3], s0) & m0);
    const uint32_t h0 = (prmt(lt[4], lt[5], s0) & ~m0) | (prmt(lt[6], lt[7], s0) & m0);
    const uint32_t l1 = (prmt(lt[0], lt[1], s1) & ~m1) | (prmt(lt[2], lt[3], s1) & m1);
    const uint32_t h1 = (prmt(lt[4], lt[5], s1) & ~m1) | (prmt(lt[6], lt[7], s1) & m1);
    r0 = prmt(l0, h0, 0x5140); r1 = prmt(l0, h0, 0x7362);
    r2 = prmt(l1, h1, 0x5140); r3 = prmt(l1, h1, 0x7362);
}
__device__ __forceinline__ void decode(uint32_t (&a)[16], const u64 (&c)[4], uint32_t tblv, const uint32_t (&lt)[8]) {
#pragma unroll
    for (int i = 0; i < 4; i++) {
        const int b = (i >> 1) * 8 + (i & 1);
        if (i < 4 - NALU) {
#pragma unroll
            for (int j = 0; j < 4; j++) a[b + 2 * j] = lds32(dp4a_u((uint32_t)c[i], 0x80u << (8 * j), tblv));
        } else {
            decode_alu(a[b], a[b + 2], a[b + 4], a[b + 6], (uint32_t)c[i], lt);
        }
    }
}

__host__ __device__ constexpr int slot_of(int j) {
    return j < 16 ? j % 6 : j < 18 ? j - 16 : (0x410532 >> (4 * ((j - 18) % 6))) & 7;
}
__host__ __device__ constexpr int loads_before(int j) {
    int n = 0;
    for (int i = 0; i < j; i++) n += slot_of(i) == slot_of(j);
    return n;
}
__host__ __device__ constexpr int uses_before(int j) {
    return loads_before(j) + (j >= 16 && slot_of(j) >= 4);
}
__host__ __device__ constexpr uint64_t prod_tbl(int j0) {
    uint64_t t = 0;
    for (int j = j0; j < j0 + 16; j++) t |= (uint64_t)(slot_of(j) | (((uses_before(j) + 1) & 1) << 3)) << (4 * (j - j0));
    return t;
}
__host__ __device__ constexpr int dec_upto(int j) { return j + 1 + (j >= RAMP1) + (j >= RAMP2); }
__host__ __device__ constexpr bool read_early(int d) {
    return d > FPAIR + 1 && d < NSL && d != RAMP1 + 3 && d != RAMP1 + 4 && d != 18 && d != 20 && d != 21 && d != RAMP2 + 4 &&
           d != RAMP2 + 5;
}
__host__ __device__ constexpr bool get_early(int d) { return d == RAMP1 + 1 || d == RAMP2 + 2; }

__device__ __forceinline__ void fence_a(uint32_t (&a)[16]) {
#pragma unroll
    for (int i = 0; i < 16; i++) asm volatile("" : "+r"(a[i])::"memory");
}
template <int J, int N, int COL>
__device__ __forceinline__ void mma_slice(float (&acc)[N0 / 2], uint32_t (&a)[4][16]) {
    constexpr int off = (slot_of(J) * SLOT_BYTES + COL * 128) / 16, b = J % 4;
    constexpr uint64_t d0 = make_desc(SMEM_BASE);
    WG<N, COL / 2, (J % KSTEPS) != 0, N0 / 2>::mma(acc, a[b][0], a[b][1], a[b][2], a[b][3], d0 + off);
    WG<N, COL / 2, true, N0 / 2>::mma(acc, a[b][4], a[b][5], a[b][6], a[b][7], d0 + (off + 2));
    WG<N, COL / 2, true, N0 / 2>::mma(acc, a[b][8], a[b][9], a[b][10], a[b][11], d0 + (off + 4));
    WG<N, COL / 2, true, N0 / 2>::mma(acc, a[b][12], a[b][13], a[b][14], a[b][15], d0 + (off + 6));
}
template <int N> __device__ __forceinline__ void rename_acc(float (&acc)[N0 / 2]) {
#pragma unroll
    for (int i = 0; i < N / 2; i++) asm volatile("mov.b32 %0, %1;" : "=f"(acc[i]) : "f"(acc[i]) : "memory");
}
template <int N, int COL, bool FENCE>
__device__ __forceinline__ void stage_out(float (&acc)[N0 / 2], uint32_t sa, float s0, float s1) {
#pragma unroll
    for (int i = COL / 2; i < (COL + N) / 2; i++) asm volatile("" : "+f"(acc[i])::"memory");
#pragma unroll
    for (int j = COL / 8; j + 1 < (COL + N) / 8; j += 2) {
        const uint32_t r0 = pack_bf16x2(acc[4 * j + 0] * s0, acc[4 * j + 1] * s0);
        const uint32_t r1 = pack_bf16x2(acc[4 * j + 2] * s1, acc[4 * j + 3] * s1);
        const uint32_t r2 = pack_bf16x2(acc[4 * j + 4] * s0, acc[4 * j + 5] * s0);
        const uint32_t r3 = pack_bf16x2(acc[4 * j + 6] * s1, acc[4 * j + 7] * s1);
        asm volatile("stmatrix.sync.aligned.m8n8.x4.trans.shared.b16 [%0], {%1, %2, %3, %4};"
                     ::"r"(sa + j * 1024), "r"(r0), "r"(r1), "r"(r2), "r"(r3) : "memory");
    }
    if constexpr ((N / 8) & 1) {
        constexpr int j = (COL + N) / 8 - 1;
        const uint32_t r0 = pack_bf16x2(acc[4 * j + 0] * s0, acc[4 * j + 1] * s0);
        const uint32_t r1 = pack_bf16x2(acc[4 * j + 2] * s1, acc[4 * j + 3] * s1);
        asm volatile("stmatrix.sync.aligned.m8n8.x2.trans.shared.b16 [%0], {%1, %2};"
                     ::"r"(sa + j * 1024), "r"(r0), "r"(r1) : "memory");
    }
    if constexpr (FENCE) asm volatile("fence.proxy.async.shared::cta;" ::: "memory");
}

struct Maps { CUtensorMap m[8]; };

__global__ void __cluster_dims__(2, 1, 1) __launch_bounds__(NUM_THREADS, 1)
nf4_gemm_kernel(const int* __restrict__ qw, u64* __restrict__ ll, unsigned* __restrict__ epoch,
                const __nv_bfloat16* __restrict__ lut, const __nv_bfloat16* __restrict__ scales,
                const __grid_constant__ Maps tm) {
    extern __shared__ __align__(1024) uint8_t smem_raw[];
    const uint32_t t_start = clock32();
    const int lane = threadIdx.x & 31;
    const int warp = __shfl_sync(0xffffffffu, threadIdx.x >> 5, 0);
    const uint32_t sb = smem_u32(smem_raw);
    const uint32_t bar_full = sb + BAR_OFF;
    const uint32_t bar_empty = bar_full + NSLOTS * 8;
    const uint32_t bar_tbl = bar_empty + NSLOTS * 8;
    const uint32_t bar_code = bar_tbl + 8;
    const int crank = blockIdx.x & 1, cluster = blockIdx.x >> 1;

    if (warp != 8) cluster_arrive_relaxed();
    if (warp < 8) {
        const int wg = warp >> 2;
        const uint32_t u0 = (1 + warp) * NUM_CTAS + blockIdx.x, q0 = u0 / W1_FG, fg0 = u0 % W1_FG;
        uint4 v[8];
        TSW(640 + warp);
        const uint32_t tag = ld_ca_u32(epoch + lane);
        const uint32_t lv = ldg_u16(reinterpret_cast<const unsigned short*>(lut) + (lane & 15));
        int fp0, fp1, mm;
        tile0_of(cluster, fp0, mm);
        tile1_of(cluster, fp1, mm);
        const int ft0 = fp0 * 2 + crank, ft1 = fp1 * 2 + crank;
        const unsigned short* sc16 = reinterpret_cast<const unsigned short*>(scales) + warp * 16 + (lane >> 2);
        uint32_t sc0 = ldg_u16(sc16 + ft0 * FT), sc0h = ldg_u16(sc16 + ft0 * FT + 8);
        uint32_t sc1 = ldg_u16(sc16 + ft1 * FT), sc1h = ldg_u16(sc16 + ft1 * FT + 8);
        if (NBOR > 0 && warp < NBOR) {
            delay_until(t_start, round_time(1 + warp));
            load_unit(v, add_off(qw, unit_src(q0, fg0) + lane_src(lane)));
            uint32_t e[4], o[4];
            pk_gather(e, o, v);
            pk_write(add_off(ll, unit_dst(q0, fg0) + lane_dst(lane)), e, o, tag + (q0 >> 1));
            TSW(701 + warp);
        } else if (wg == 1) {
            uint32_t lo[4];
#pragma unroll
            for (int i = 0; i < 4; i++) lo[i] = __shfl_sync(0xffffffffu, lv, 4 * i + (lane >> 3));
#pragma unroll 1
            for (int h = (warp & 3) * 4; h < (warp & 3) * 4 + 4; h++) {
                const uint32_t hi = __shfl_sync(0xffffffffu, lv, h) << 16;
#pragma unroll
                for (int i = 0; i < 4; i++)
                    asm volatile("st.shared.v4.u32 [%0], {%1, %1, %1, %1};"
                                 ::"r"(sb + TBL_OFF + h * 2048 + i * 512 + lane * 16), "r"(lo[i] | hi) : "memory");
            }
        }
        asm volatile("setmaxnreg.inc.sync.aligned.u32 %0;" ::"n"(CREGS));
        cluster_wait();
        if (wg == 1) mbar_arrive(bar_tbl);
        TS(132);
        sc0 |= sc0h << 16;
        sc1 |= sc1h << 16;
        const char* ll0 = keep(reinterpret_cast<const char*>(ll) + (ft0 * (KSTEPS * 8192) + warp * 1024 + lane), 0);
        const char* ll1 = keep(reinterpret_cast<const char*>(ll) + (ft1 * (KSTEPS * 8192) + warp * 1024 + lane), 0);
        const uint32_t cbuf = sb + RAW_OFF + warp * 1024;
        const uint32_t tblv = keep(sb + TBL_OFF + lane * 4, lane);
        const uint32_t cempty = keep(lane < 2 ? mapa(bar_empty, lane) : 0, lane);
        const uint32_t sa0 = keep(sb + (((lane >> 4) * 8 + (lane & 7)) * 128) +
                                  ((((warp & 3) * 2 + ((lane >> 3) & 1)) ^ (lane & 7)) << 4), lane);
        uint32_t lt[8];
        {
            const uint32_t p01 = __shfl_sync(0xffffffffu, lv, 4 * lane) | (__shfl_sync(0xffffffffu, lv, 4 * lane + 1) << 16);
            const uint32_t p23 = __shfl_sync(0xffffffffu, lv, 4 * lane + 2) | (__shfl_sync(0xffffffffu, lv, 4 * lane + 3) << 16);
            const uint32_t pl = prmt(p01, p23, lane & 4 ? 0x7531 : 0x6420);
#pragma unroll
            for (int i = 0; i < 8; i++) lt[i] = __shfl_sync(0xffffffffu, pl, i & 1 ? i : i + (lane & 24));
        }
        uint32_t a[4][16];
        float acc[N0 / 2];

        auto src = [&](auto dc) {
            constexpr int D = decltype(dc)::value;
            return (D < KSTEPS ? ll0 : ll1) + (D % KSTEPS) * 8192;
        };
        u64 c[4];
        const uint32_t aw = keep(cbuf + lane * 8, lane);
        auto fetch = [&](auto dc) {
            constexpr int D = decltype(dc)::value;
            if constexpr (D < NGATE) delay_until(t_start, DLY_POLL + D * DLY_PS);
            if constexpr (D < NSL) ll_copy(cbuf + (D & 1) * 8192, src(dc), bar_code);
        };
        auto read = [&](auto dc) {
            constexpr int D = decltype(dc)::value;
            ll_read(c, aw + (D & 1) * 8192);
        };
        auto get = [&](auto dc) {
            constexpr int D = decltype(dc)::value;
            if constexpr (D <= ND0) {
                delay_until(t_start, DLY_POLL + D * DLY_PS);
                ll_poll(c, src(dc) + lane * 8, tag + D);
            } else {
                if constexpr (!read_early(D)) read(dc);
                ll_check<(D < NGATE ? NSPIN0 : NSPIN1)>(c, aw + (D & 1) * 8192, cbuf + (D & 1) * 8192, src(dc), bar_code,
                                                        tag + D % KSTEPS);
            }
            if constexpr (D >= FPAIR && D + 2 >= NGATE) fetch(IC<D + 2>{});
        };
        auto dec = [&](auto dc) {
            constexpr int D = decltype(dc)::value;
            decode(a[D % 4], c, tblv, lt);
            if constexpr (D >= ND0 && D <= FPAIR) fetch(IC<D + 1>{});
            if constexpr (D >= FPAIR && D + 2 < NGATE) fetch(IC<D + 2>{});
            if constexpr (read_early(D + 1)) read(IC<D + 1>{});
            if constexpr (get_early(D + 1)) get(IC<D + 1>{});
        };
        auto wait_full = [&](auto jc) {
            constexpr int J = decltype(jc)::value;
            mbar_wait(bar_full + slot_of(J) * 8, loads_before(J) & 1);
        };
        auto release = [&](auto jc) {
            constexpr int J = decltype(jc)::value;
            if constexpr (J < NSL - 4) mbar_arrive_pair(cempty + slot_of(J) * 8, cempty);
        };
        auto step = [&](auto jc) {
            constexpr int J = decltype(jc)::value, D = dec_upto(J - 1) + 1;
            fence_a(a[J % 4]);
            wgmma_fence();
            mma_slice<J, (J < KSTEPS ? N0 : N1), 0>(acc, a);
            wgmma_commit();
            TS(J);
            if constexpr (!get_early(D)) get(IC<D>{});
            if constexpr (J >= NEARLY) wait_full(IC<J + 1>{});
            wgmma_wait<1>();
            if constexpr (J != 0 && J != 18) release(IC<J - 1>{});
            dec(IC<D>{});
            if constexpr (dec_upto(J) > D) { get(IC<D + 1>{}); dec(IC<D + 1>{}); }
            if constexpr (J < NEARLY) wait_full(IC<J + 1>{});
        };
        static_assert(FPAIR <= 9 && ND0 <= FPAIR && (SMEM_BASE + TBL_OFF) % 128 == 0, "code schedule");
        static_assert(slot_of(10) == 4 && slot_of(11) == 5 && uses_before(10) == 1 && uses_before(11) == 1 &&
                      2 * E0 * 128 <= SLOT_BYTES + 1024 && 2 * E1 * 128 <= SLOT_BYTES, "staging slots");

        mbar_wait(bar_tbl, 0);
        TS(133);
        get(IC<0>{});
        dec(IC<0>{});
        TS(134);
        wait_full(IC<0>{});
        TS(137);
        static_for<0, 14>(step);
        {
            const float s0 = __uint_as_float(sc0 << 16), s1 = __uint_as_float(sc0 & 0xffff0000u);
            wait_full(IC<15>{});
            fence_a(a[2]); fence_a(a[3]);
            TS(140);
            wgmma_wait<0>();
            rename_acc<N0>(acc);
            wgmma_fence();
            mma_slice<14, E0, 0>(acc, a);
            mma_slice<15, E0, 0>(acc, a);
            wgmma_commit();
            TS(14);
            release(IC<13>{});
            get(IC<16>{}); dec(IC<16>{});
            TS(141);
            wgmma_fence();
            mma_slice<14, E1, E0>(acc, a);
            mma_slice<15, E1, E0>(acc, a);
            wgmma_commit();
            TS(15);
            get(IC<17>{}); dec(IC<17>{});
            TS(142);
            mbar_wait(bar_empty + 5 * 8, 1);
            wgmma_wait<1>();
            TS(143);
            stage_out<EH, 0, false>(acc, sa0 + 5 * SLOT_BYTES + wg * (E0 * 128), s0, s1);
            wgmma_wait<0>();
            release(IC<14>{}); release(IC<15>{});
            stage_out<E0 - EH, EH, true>(acc, sa0 + 5 * SLOT_BYTES + wg * (E0 * 128), s0, s1);
            named_bar_arrive<14, 288>();
            TS(144);
            wait_full(IC<16>{}); wait_full(IC<17>{});
            fence_a(a[0]); fence_a(a[1]);
            wgmma_fence();
            mma_slice<16, S0, 0>(acc, a);
            mma_slice<17, S0, 0>(acc, a);
            wgmma_commit();
            TS(16);
            TS(128);
            stage_out<E1, E0, true>(acc, sa0 + 4 * SLOT_BYTES - E0 * 128 + wg * (E1 * 128), s0, s1);
            named_bar_arrive<15, 288>();
            TS(129);
            wgmma_fence();
            mma_slice<16, S1, S0>(acc, a);
            mma_slice<17, S1, S0>(acc, a);
            wgmma_commit();
            TS(17);
            get(IC<18>{}); dec(IC<18>{});
            get(IC<19>{}); dec(IC<19>{});
            wait_full(IC<18>{});
            TS(145);
            wgmma_wait<0>();
            rename_acc<N1>(acc);
            release(IC<16>{}); release(IC<17>{});
            TS(146);
        }
        static_for<18, NSL - 4>(step);
        {
            constexpr int J0 = NSL - 4;
            const float s0 = __uint_as_float(sc1 << 16), s1 = __uint_as_float(sc1 & 0xffff0000u);
            const uint32_t sa = sa0 + (wg ? slot_of(27) : slot_of(26)) * SLOT_BYTES;
            wait_full(IC<J0 + 1>{}); wait_full(IC<J0 + 2>{});
            fence_a(a[0]); fence_a(a[1]); fence_a(a[2]);
            TS(160);
            wgmma_wait<0>();
            rename_acc<N1>(acc);
            wgmma_fence();
            mma_slice<J0, CA, 0>(acc, a);
            TS(J0);
            release(IC<J0 - 1>{});
            get(IC<NSL - 1>{}); dec(IC<NSL - 1>{});
            asm volatile("{\n.reg .pred p;\nelect.sync _|p, 0xffffffff;\n"
                         "@p mbarrier.arrive.expect_tx.shared::cta.b64 _, [%0], %1;\n}\n" ::"r"(bar_code), "n"((NSL - 1 - ND0) * 1024) : "memory");
            wgmma_fence();
            mma_slice<J0 + 1, CA, 0>(acc, a);
            mma_slice<J0 + 2, CA, 0>(acc, a);
            wait_full(IC<NSL - 1>{});
            fence_a(a[3]);
            wgmma_fence();
            mma_slice<J0 + 3, CA, 0>(acc, a);
            wgmma_commit();
            static_for<1, 5>([&](auto cc) {
                constexpr int C = decltype(cc)::value;
                constexpr int N = C == 1 ? CA : C == 2 ? CB : CC, COL = C == 3 ? 2 * CA + CB : C * CA;
                constexpr int NP = C <= 2 ? CA : C == 3 ? CB : CC, COLP = C == 4 ? 2 * CA + CB : (C - 1) * CA;
                if constexpr (C < 4) {
                    wgmma_fence();
                    mma_slice<J0, N, COL>(acc, a);
                    wgmma_commit();
                    if constexpr (C == 1) mbar_wait(bar_empty + (wg ? slot_of(27) : slot_of(26)) * 8, (wg ? uses_before(27) : uses_before(26)) & 1);
                    wgmma_wait<1>();
                } else {
                    wgmma_wait<0>();
                    TS(130);
                }
                TS(160 + C * 4);
                stage_out<NP, COLP, true>(acc, sa, s0, s1);
                bar_arrive_id(5 + C + wg * 4, 160);
                TS(160 + C * 4 + 1);
                if constexpr (C < 4) {
                    wgmma_fence();
                    static_for<J0 + 1, NSL>([&](auto jc) { mma_slice<decltype(jc)::value, N, COL>(acc, a); });
                    wgmma_commit();
                    TS(J0 + C);
                }
            });
            TS(131);
        }
    } else {
      asm volatile("setmaxnreg.dec.sync.aligned.u32 %0;" ::"n"(504 - 2 * CREGS));
      if (warp >= 9) {
        {
            const int pw = warp - 9;
            int u = (pw ? NBOR + 1 + pw : 0) * NUM_CTAS + blockIdx.x;
            uint32_t q = u / W1_FG, fg = u % W1_FG;
            uint4 v[8];
            if (pw > 0) delay_until(t_start, round_time(NBOR + 1 + pw));
            load_unit(v, add_off(qw, unit_src(q, fg) + lane_src(lane)));
            TSW(648 + pw);
            const uint32_t tag = ld_ca_u32(epoch + lane);
            const int* qwk = keep(add_off(qw, lane_src(lane)), lane);
            u64* llk = keep(add_off(ll, lane_dst(lane)), lane);
            constexpr int nun = NUM_UNITS;
            int rr = pw ? NBOR + 1 + pw : 0;
            if (pw == 0) u += (NBOR + 1 - NUM_AUX) * NUM_CTAS;
#pragma unroll 1
            for (;;) {
                u64* dst = add_off(llk, unit_dst(q, fg));
                const uint32_t tg = tag + (q >> 1);
                u += u < (RSTOP - NUM_AUX) * NUM_CTAS ? NUM_AUX * NUM_CTAS : pw == 2 ? NUM_UNITS : u < RSTOP * NUM_CTAS ? NUM_AUX * NUM_CTAS : 2 * NUM_CTAS;
                unit_pos(min(u, NUM_UNITS - 1), q, fg);
                const int* p = add_off(qwk, unit_src(q, fg));
                uint32_t e[4], o[4];
                pk_gather(e, o, v);
                TSW(700 + rr); rr += rr == 0 ? NBOR + 1 : rr < RSTOP ? NUM_AUX : 2;
                if (u >= nun) { pk_write(dst, e, o, tg); break; }
                load_unit(v, p);
                pk_write(dst, e, o, tg);
            }
        }
        const CUtensorMap* maps = keep(&tm.m[3] + lane, 0);
        named_bar_arrive<4, 128>();
        cluster_wait();
        int fp, m0;
        if (warp == 11) {
            tile0_of(cluster, fp, m0);
            const int f0 = (fp * 2 + crank) * FT;
#pragma unroll 1
            for (int ch = 0; ch < 2; ch++) {
                const uint32_t src = sb + (5 - ch) * SLOT_BYTES;
                bar_sync_id(14 + ch, 288);
                if (lane == 0) {
                    const int rows = ch ? E1 : E0, step = ch ? BX1 : BX0;
#pragma unroll 1
                    for (int r = 0; r < 2 * rows; r += step) {
                        const int h = r >= rows;
                        tma_store_2d(maps + 3 + ch, src + r * 128, f0 + h * 64, m0 + ch * E0 + r - h * rows);
                        asm volatile("cp.async.bulk.commit_group;" ::: "memory");
                        asm volatile("cp.async.bulk.wait_group.read %0;" ::"n"(STQ) : "memory");
                    }
                    asm volatile("cp.async.bulk.wait_group.read 0;" ::: "memory");
                }
                __syncwarp();
                if (lane < 2) mbar_arrive_cluster_n(mapa(bar_empty + (5 - ch) * 8, lane), 8);
                TSG(604 + ch * 2);
            }
        } else {
            const int wg = warp - 9;
            tile1_of(cluster, fp, m0);
            const int f0 = (fp * 2 + crank) * FT + wg * 64;
            const uint32_t src = sb + (wg ? slot_of(27) : slot_of(26)) * SLOT_BYTES;
#pragma unroll 1
            for (int ch = 0; ch < 4; ch++) {
                const int r0 = ch < 3 ? ch * CA : 2 * CA + CB;
                const CUtensorMap* map = maps + max(ch - 1, 0);
                bar_sync_id(6 + wg * 4 + ch, 160);
                if (lane == 0) {
                    tma_store_2d(map, src + r0 * 128, f0, m0 + r0);
                    asm volatile("cp.async.bulk.commit_group;" ::: "memory");
                }
            }
            if (lane == 0) asm volatile("cp.async.bulk.wait_group.read 0;" ::: "memory");
            __syncwarp();
            TSG(600 + wg * 2);
        }
      } else {
        if ((sb & 0xFFFFFF) != SMEM_BASE) __trap();
        if (lane == 0) {
            for (int s = 0; s < NSLOTS; s++) {
                mbar_init(bar_full + s * 8, 1);
                mbar_init(bar_empty + s * 8, 16);
            }
            mbar_init(bar_tbl, 128);
            mbar_init(bar_code, 8);
            asm volatile("fence.mbarrier_init.release.cluster;" ::: "memory");
        }
        __syncwarp();
        cluster_arrive_relaxed();
        const CUtensorMap* maps = keep(&tm.m[0] + lane, 0);
        unsigned* epk = keep(epoch + lane, 0);
        if (lane == 0) prefetch_map(maps + crank);
        TSG(512);
        int fp, m0;
        tile0_of(cluster, fp, m0);
        cluster_wait();
#pragma unroll 1
        for (int t = 0; t < 2; t++) {
            const int lo = t == 0 ? 120 : 104, row = m0 + crank * lo;
            const CUtensorMap* map = maps + (t ? 2 : crank);
            const uint32_t bytes = (t ? N1 : N0) * 128, dst = sb + crank * lo * 128;
            uint64_t tbl = t ? prod_tbl(16) : prod_tbl(0);
#pragma unroll 1
            for (int ks = 0; ks < KSTEPS; ks++, tbl >>= 4) {
                const uint32_t slot = (uint32_t)tbl & 7;
                if (t == 0 && ks > 0 && ks < NSLOTS) delay_until(t_start, DLY_X0 + ks * DLY_XS);
                mbar_wait(bar_empty + slot * 8, ((uint32_t)tbl >> 3) & 1);
                asm volatile(
                    "{\n.reg .pred p;\nelect.sync _|p, 0xffffffff;\n"
                    "@p mbarrier.arrive.expect_tx.shared::cta.b64 _, [%2], %5;\n"
                    "@p cp.async.bulk.tensor.2d.shared::cluster.global.mbarrier::complete_tx::bytes.multicast::cluster"
                    " [%0], [%1, {%3, %4}], [%2], %6;\n}\n"
                    ::"r"(dst + slot * SLOT_BYTES), "l"(map), "r"(bar_full + slot * 8), "r"(ks * BK), "r"(row), "r"(bytes),
                    "h"((uint16_t)3) : "memory");
                TSG(514 + (t * 18 + ks) * 2);
            }
            tile1_of(cluster, fp, m0);
            if (t == 0 && lane >= 2 && lane < 8) prefetch_map(maps + lane);
        }
        named_bar_sync<4, 128>();
        const uint32_t tag = ld_ca_u32(epk + lane);
        unsigned old = 0;
        if (lane == 0) old = atomicAdd(epk + 32, tag != 0 ? 1u : 0u);
        if (__shfl_sync(0xffffffffu, old, 0) == NUM_CTAS - 1) {
            if (lane == 0) epk[32] = 0;
            epk[lane] = tag == 0xfffffff0u ? 16 : tag + 16;
        }
        mbar_wait(bar_code, 0);
      }
    }
}

__global__ void generic_kernel(const __nv_bfloat16* __restrict__ x, const int* __restrict__ qw,
                               const __nv_bfloat16* __restrict__ lut, const __nv_bfloat16* __restrict__ scales,
                               __nv_bfloat16* __restrict__ out, int M, int N, int K, int G) {
    const int n = blockIdx.x * blockDim.x + threadIdx.x;
    const int m = blockIdx.y;
    if (n >= N) return;
    float acc = 0.f;
    for (int k = 0; k < K; k++) {
        const float l = __bfloat162float(lut[qw[(size_t)k * N + n] & 15]);
        const float s = __bfloat162float(scales[(size_t)(k / G) * N + n]);
        const float w = __bfloat162float(__float2bfloat16_rn(l * s));
        acc += __bfloat162float(x[(size_t)m * K + k]) * w;
    }
    out[(size_t)m * N + n] = __float2bfloat16_rn(acc);
}

typedef CUresult (*PFN_encodeTiled)(CUtensorMap*, CUtensorMapDataType, cuuint32_t, void*, const cuuint64_t*,
                                    const cuuint64_t*, const cuuint32_t*, const cuuint32_t*, CUtensorMapInterleave,
                                    CUtensorMapSwizzle, CUtensorMapL2promotion, CUtensorMapFloatOOBfill);

bool make_map_2d(PFN_encodeTiled fn, CUtensorMap* map, void* base, uint64_t inner, uint64_t outer, uint32_t box_inner,
                 uint32_t box_outer) {
    cuuint64_t dims[2] = {inner, outer};
    cuuint64_t strides[1] = {inner * 2};
    cuuint32_t box[2] = {box_inner, box_outer};
    cuuint32_t estr[2] = {1, 1};
    return fn(map, CU_TENSOR_MAP_DATA_TYPE_BFLOAT16, 2, base, dims, strides, box, estr, CU_TENSOR_MAP_INTERLEAVE_NONE,
              CU_TENSOR_MAP_SWIZZLE_128B, XPROMO,
              CU_TENSOR_MAP_FLOAT_OOB_FILL_NONE) == CUDA_SUCCESS;
}

}

extern "C" void kernel_launch(void* const* d_in, const int* in_sizes, int n_in, void* d_out, int out_size) {
    const __nv_bfloat16* x = (const __nv_bfloat16*)d_in[0];
    const int* qw = (const int*)d_in[1];
    const __nv_bfloat16* lut = (const __nv_bfloat16*)d_in[2];
    const __nv_bfloat16* scales = (const __nv_bfloat16*)d_in[3];
    __nv_bfloat16* out = (__nv_bfloat16*)d_out;

    const double Kd = sqrt((double)in_sizes[0] * (double)in_sizes[1] / (double)out_size);
    const int K = (int)(Kd + 0.5);
    const int M = in_sizes[0] / K, N = in_sizes[1] / K;
    const int ng = in_sizes[3] / N;
    const int G = K / ng;

    bool fast = (M == kM && N == kN && K == kK && ng == 1 && in_sizes[2] >= 16);
    PFN_encodeTiled enc = nullptr;
    Maps tm;
    void *ll = nullptr, *epoch = nullptr;
    if (fast) {
        cudaDriverEntryPointQueryResult qres;
        void* fp = nullptr;
        if (cudaGetDriverEntryPoint("cuTensorMapEncodeTiled", &fp, cudaEnableDefault, &qres) != cudaSuccess || !fp) fast = false;
        enc = (PFN_encodeTiled)fp;
    }
    static_assert(2 * CA + CB + CC == N1 && S0 <= E0, "chunks");
    if (fast) {
        fast = make_map_2d(enc, &tm.m[0], (void*)x, kK, kM, BK, 120) &&
               make_map_2d(enc, &tm.m[1], (void*)x, kK, kM, BK, 112) &&
               make_map_2d(enc, &tm.m[2], (void*)x, kK, kM, BK, 104) &&
               make_map_2d(enc, &tm.m[3], (void*)out, kN, kM, 64, CA) &&
               make_map_2d(enc, &tm.m[4], (void*)out, kN, kM, 64, CB) &&
               make_map_2d(enc, &tm.m[5], (void*)out, kN, kM, 64, CC) &&
               make_map_2d(enc, &tm.m[6], (void*)out, kN, kM, 64, BX0) &&
               make_map_2d(enc, &tm.m[7], (void*)out, kN, kM, 64, BX1) &&
               cudaGetSymbolAddress(&ll, g_ll) == cudaSuccess && cudaGetSymbolAddress(&epoch, g_epoch) == cudaSuccess;
    }
    cudaLaunchConfig_t cfg = {};
    cfg.gridDim = dim3(NUM_CTAS);
    cfg.blockDim = dim3(NUM_THREADS);
    cfg.dynamicSmemBytes = SMEM_TOTAL;
    cfg.stream = cudaStreamPerThread;
    if (fast) {
        int nclusters = 0;
        fast = cudaFuncSetAttribute(nf4_gemm_kernel, cudaFuncAttributeMaxDynamicSharedMemorySize, SMEM_TOTAL) == cudaSuccess &&
               cudaOccupancyMaxActiveClusters(&nclusters, nf4_gemm_kernel, &cfg) == cudaSuccess &&
               nclusters >= NUM_CTAS / 2;
    }
    if (!fast) {
        generic_kernel<<<dim3((N + 127) / 128, M), 128>>>(x, qw, lut, scales, out, M, N, K, G);
        return;
    }
    cudaLaunchKernelEx(&cfg, nf4_gemm_kernel, qw, (u64*)ll, (unsigned*)epoch, lut, scales, tm);
}
```

```cpp
#include <cuda_runtime.h>
#include <cuda_bf16.h>
#include <cuda.h>
#include <stdint.h>
#include <stdio.h>
#include <math.h>

namespace {

constexpr int kM = 2048, kN = 3584, kK = 1024;
constexpr int FT = 128;
constexpr int N0 = 232, N1 = 208;
constexpr int BK = 64, KSTEPS = kK / BK;
constexpr int NSLOTS = 6;
constexpr int SLOT_BYTES = N0 * 128;
constexpr int TBL_OFF = NSLOTS * SLOT_BYTES + 1024;
constexpr int RAW_OFF = TBL_OFF + 32768;
constexpr int BAR_OFF = RAW_OFF + 4 * 4096;
constexpr int TS_OFF = BAR_OFF + 256;
constexpr int SMEM_TOTAL = BAR_OFF + 256;
constexpr int NUM_THREADS = 384;
constexpr int NUM_CTAS = 132;
constexpr int NUM_AUX = 3;
constexpr int NQ = kK / 32, NUM_UNITS = NQ * (kN / 32);
constexpr int W1_FG = 64, W2_FG = kN / 32 - W1_FG;
constexpr int NSL = 2 * KSTEPS;
#define NBOR 0
#define CREGS 224
#define DLY_R0 200
#define DLY_R 400
#define R_KNEE 4
#define DLY_R2 450
#define PF_KIND 0
#define PF_DIST 2
#define PF_LEAD 700
#define DLY_X0 1000
#define DLY_XS 900
#define DLY_POLL 2600
#define DLY_PS 700
#define DLY_P1 3200
#define FLATE 3
#define RLATE 4
#define RAMP1 8
#define RAMP1B 12
#define RAMP2A 0
#define RAMP2 24
#define NSPIN0 24
#define NSPIN1 8
#define NALU 2
#define RSTOP (15 + NAUX0 + NBOR)
#define EH 48
#define BX0 24
#define BX1 16
#define STQ 1
#define NCHK0 8
#define NAUX0 3
#define WL1 18
#define EI 64
#define TOPLD 2
#define PFN 0
#define PFR 3
#define PF0 1200
#define PFD 400
#define TOPN 32
#define DLY_2 0
#define DLY_2S 400
#define NEARLY 4
#define NGATE 8
#define DLY_ST0 800
#define DLY_ST 800
#define XPROMO CU_TENSOR_MAP_L2_PROMOTION_L2_128B
constexpr int E0 = 120, E1 = N0 - E0, S0 = 112, S1 = N1 - S0, CA = 64, CB = 48, CC = 32;
constexpr unsigned SPIN_LIMIT = 1u << 20;

__device__ __align__(1024) unsigned long long g_ll[(size_t)(kN / FT) * NQ * FT * 4];
__device__ __align__(256) unsigned int g_epoch[64] = {16, 16, 16, 16, 16, 16, 16, 16, 16, 16, 16, 16, 16, 16, 16, 16,
                                                      16, 16, 16, 16, 16, 16, 16, 16, 16, 16, 16, 16, 16, 16, 16, 16};

#define TS(idx) do {} while (0)
#define TSW(idx) do {} while (0)
#define TSG(idx) do {} while (0)
#define TSA(idx) do {} while (0)

template <int I> struct IC { static constexpr int value = I; };
template <int B, int E, class F> __device__ __forceinline__ void static_for(F&& f) {
    if constexpr (B < E) { f(IC<B>{}); static_for<B + 1, E>(f); }
}

__device__ __forceinline__ uint32_t smem_u32(const void* p) { return (uint32_t)__cvta_generic_to_shared(p); }
__device__ __forceinline__ uint32_t keep(uint32_t v, int lane) {
    asm volatile("shfl.sync.idx.b32 %0, %0, %1, 0x1f, 0xffffffff;" : "+r"(v) : "r"(lane));
    return v;
}
template <class T> __device__ __forceinline__ T* keep(T* p, int lane) {
    const uint64_t v = (uint64_t)p;
    return (T*)(((uint64_t)keep((uint32_t)(v >> 32), lane) << 32) | keep((uint32_t)v, lane));
}
__device__ __forceinline__ void mbar_init(uint32_t bar, uint32_t count) {
    asm volatile("mbarrier.init.shared::cta.b64 [%0], %1;" ::"r"(bar), "r"(count) : "memory");
}
__device__ __forceinline__ void mbar_arrive_expect_tx(uint32_t bar, uint32_t bytes) {
    asm volatile("mbarrier.arrive.expect_tx.shared::cta.b64 _, [%0], %1;" ::"r"(bar), "r"(bytes) : "memory");
}
__device__ __forceinline__ uint32_t clock32() { uint64_t c; asm volatile("mov.u64 %0, %%clock64;" : "=l"(c)); return (uint32_t)c; }
__device__ __forceinline__ void mbar_arrive(uint32_t bar) {
    asm volatile("mbarrier.arrive.shared::cta.b64 _, [%0];" ::"r"(bar) : "memory");
}
__device__ __forceinline__ uint32_t mapa(uint32_t a, uint32_t rank) {
    uint32_t r;
    asm("mapa.shared::cluster.u32 %0, %1, %2;" : "=r"(r) : "r"(a), "r"(rank));
    return r;
}
__device__ __forceinline__ void mbar_arrive_pair(uint32_t cbar, uint32_t base) {
    asm volatile("{\n.reg .pred p;\nsetp.ne.u32 p, %1, 0;\n@p mbarrier.arrive.shared::cluster.b64 _, [%0];\n}\n"
                 ::"r"(cbar), "r"(base) : "memory");
}
__device__ __forceinline__ void mbar_arrive_cluster_n(uint32_t cbar, uint32_t n) {
    asm volatile("mbarrier.arrive.shared::cluster.b64 _, [%0], %1;" ::"r"(cbar), "r"(n) : "memory");
}
__device__ __forceinline__ void delay_until(uint32_t t0, int clks) {
    while (__any_sync(0xffffffffu, (int)(clock32() - t0) < clks)) {}
}
__device__ __forceinline__ bool mbar_test(uint32_t bar, uint32_t parity) {
    uint32_t ok;
    asm volatile("{\n.reg .pred p;\nmbarrier.test_wait.parity.shared::cta.b64 p, [%1], %2;\nvote.sync.all.pred p, p, 0xffffffff;\nselp.u32 %0, 1, 0, p;\n}\n"
                 : "=r"(ok) : "r"(bar), "r"(parity) : "memory");
    return ok != 0;
}
__device__ __forceinline__ void mbar_wait(uint32_t bar, uint32_t parity) {
    asm volatile(
        "{\n.reg .pred p;\n.reg .u32 i;\n"
        "mbarrier.try_wait.parity.shared::cta.b64 p, [%0], %1;\n"
        "@p bra D_%=;\n"
        "mov.u32 i, 0;\n"
        "L_%=:\n"
        "mbarrier.try_wait.parity.shared::cta.b64 p, [%0], %1;\n"
        "@p bra D_%=;\n"
        "add.u32 i, i, 1;\n"
        "setp.lt.u32 p, i, %2;\n"
        "@p bra L_%=;\n"
        "D_%=:\n}\n"
        ::"r"(bar), "r"(parity), "n"(SPIN_LIMIT) : "memory");
}
__device__ __forceinline__ void tma_load_2d_mc(uint32_t dst, const CUtensorMap* map, uint32_t bar, int c0, int c1,
                                               uint16_t mask) {
    asm volatile(
        "cp.async.bulk.tensor.2d.shared::cluster.global.mbarrier::complete_tx::bytes.multicast::cluster"
        " [%0], [%1, {%3, %4}], [%2], %5;"
        ::"r"(dst), "l"(map), "r"(bar), "r"(c0), "r"(c1), "h"(mask) : "memory");
}
__device__ __forceinline__ void tma_store_2d(const CUtensorMap* map, uint32_t src, int c0, int c1) {
    asm volatile("cp.async.bulk.tensor.2d.global.shared::cta.bulk_group [%0, {%2, %3}], [%1];"
                 ::"l"(map), "r"(src), "r"(c0), "r"(c1) : "memory");
}
__device__ __forceinline__ void prefetch_map(const CUtensorMap* map) {
    asm volatile("prefetch.tensormap [%0];" ::"l"(map) : "memory");
}
constexpr uint32_t SMEM_BASE = 1024;
__host__ __device__ constexpr uint64_t make_desc(uint32_t saddr) {
    return (uint64_t)((saddr & 0x3FFFF) >> 4) | ((uint64_t)1 << 16) | ((uint64_t)(1024 >> 4) << 32) | ((uint64_t)1 << 62);
}
__device__ __forceinline__ void wgmma_fence() { asm volatile("wgmma.fence.sync.aligned;" ::: "memory"); }
__device__ __forceinline__ void wgmma_commit() { asm volatile("wgmma.commit_group.sync.aligned;" ::: "memory"); }
template <int N> __device__ __forceinline__ void wgmma_wait() {
    asm volatile("wgmma.wait_group.sync.aligned %0;" ::"n"(N) : "memory");
}
__device__ __forceinline__ uint32_t pack_bf16x2(float lo, float hi) {
    uint32_t r;
    asm("cvt.rn.bf16x2.f32 %0, %1, %2;" : "=r"(r) : "f"(hi), "f"(lo));
    return r;
}
__device__ __forceinline__ uint32_t lds32(uint32_t addr) {
    uint32_t v;
    asm("ld.shared.u32 %0, [%1];" : "=r"(v) : "r"(addr));
    return v;
}
__device__ __forceinline__ uint32_t dp4a_u(uint32_t a, uint32_t b, uint32_t c) {
    uint32_t d;
    asm("dp4a.u32.u32 %0, %1, %2, %3;" : "=r"(d) : "r"(a), "r"(b), "r"(c));
    return d;
}
__device__ __forceinline__ uint32_t prmt(uint32_t a, uint32_t b, uint32_t s) {
    uint32_t d;
    asm("prmt.b32 %0, %1, %2, %3;" : "=r"(d) : "r"(a), "r"(b), "r"(s));
    return d;
}
template <int ID, int NT> __device__ __forceinline__ void named_bar_sync() {
    asm volatile("bar.sync %0, %1;" ::"n"(ID), "n"(NT) : "memory");
}
template <int ID, int NT> __device__ __forceinline__ void named_bar_arrive() {
    asm volatile("bar.arrive %0, %1;" ::"n"(ID), "n"(NT) : "memory");
}
__device__ __forceinline__ void bar_sync_id(int id, int nt) { asm volatile("bar.sync %0, %1;" ::"r"(id), "r"(nt) : "memory"); }
__device__ __forceinline__ void bar_arrive_id(int id, int nt) { asm volatile("bar.arrive %0, %1;" ::"r"(id), "r"(nt) : "memory"); }
__device__ __forceinline__ void cluster_arrive_relaxed() { asm volatile("barrier.cluster.arrive.relaxed.aligned;" ::: "memory"); }
__device__ __forceinline__ void cluster_wait() { asm volatile("barrier.cluster.wait.acquire.aligned;" ::: "memory"); }
__device__ __forceinline__ uint4 ldg_stream(const int* p) {
    uint4 v;
    asm volatile("ld.global.L1::no_allocate.L2::128B.v4.u32 {%0, %1, %2, %3}, [%4];"
                 : "=r"(v.x), "=r"(v.y), "=r"(v.z), "=r"(v.w) : "l"(p));
    return v;
}
__device__ __forceinline__ uint32_t ldg_u16(const unsigned short* p) {
    uint32_t v;
    asm volatile("ld.global.nc.u16 %0, [%1];" : "=r"(v) : "l"(p));
    return v;
}
__device__ __forceinline__ unsigned ld_ca_u32(const unsigned* p) {
    unsigned v;
    asm volatile("ld.global.ca.u32 %0, [%1];" : "=r"(v) : "l"(p) : "memory");
    return v;
}
typedef unsigned long long u64;
__device__ __forceinline__ void ll_store2(u64* p, uint32_t w0, uint32_t w1, uint32_t tag) {
    asm volatile("{\n.reg .b64 a, b;\nmov.b64 a, {%1, %3};\nmov.b64 b, {%2, %3};\n"
                 "st.relaxed.gpu.global.v2.b64 [%0], {a, b};\n}\n" ::"l"(p), "r"(w0), "r"(w1), "r"(tag) : "memory");
}

template <int N, int OFF, bool ACC, int NA> struct WG;
template <int OFF, int NA> struct WG<232, OFF, false, NA> {
    static __device__ __forceinline__ void mma(float (&d)[NA], uint32_t a0, uint32_t a1, uint32_t a2, uint32_t a3, uint64_t descB) {
        asm volatile(
            "{\n"
            ".reg .pred p;\n"
            "setp.ne.b32 p, %121, 0;\n"
            "wgmma.mma_async.sync.aligned.m64n232k16.f32.bf16.bf16 "
            "{%0, %1, %2, %3, %4, %5, %6, %7, %8, %9, %10, %11, %12, %13, %14, %15, %16, %17, %18, %19, %20, %21, %22, %23, %24, %25, %26, %27, %28, %29, %30, %31, %32, %33, %34, %35, %36, %37, %38, %39, %40, %41, %42, %43, %44, %45, %46, %47, %48, %49, %50, %51, %52, %53, %54, %55, %56, %57, %58, %59, %60, %61, %62, %63, %64, %65, %66, %67, %68, %69, %70, %71, %72, %73, %74, %75, %76, %77, %78, %79, %80, %81, %82, %83, %84, %85, %86, %87, %88, %89, %90, %91, %92, %93, %94, %95, %96, %97, %98, %99, %100, %101, %102, %103, %104, %105, %106, %107, %108, %109, %110, %111, %112, %113, %114, %115}, "
            "{%116, %117, %118, %119}, %120, p, 1, 1, 0;\n"
            "}\n"
            : "=f"(d[OFF + 0]), "=f"(d[OFF + 1]), "=f"(d[OFF + 2]), "=f"(d[OFF + 3]), "=f"(d[OFF + 4]), "=f"(d[OFF + 5]), "=f"(d[OFF + 6]), "=f"(d[OFF + 7]), "=f"(d[OFF + 8]), "=f"(d[OFF + 9]), "=f"(d[OFF + 10]), "=f"(d[OFF + 11]), "=f"(d[OFF + 12]), "=f"(d[OFF + 13]), "=f"(d[OFF + 14]), "=f"(d[OFF + 15]), "=f"(d[OFF + 16]), "=f"(d[OFF + 17]), "=f"(d[OFF + 18]), "=f"(d[OFF + 19]), "=f"(d[OFF + 20]), "=f"(d[OFF + 21]), "=f"(d[OFF + 22]), "=f"(d[OFF + 23]), "=f"(d[OFF + 24]), "=f"(d[OFF + 25]), "=f"(d[OFF + 26]), "=f"(d[OFF + 27]), "=f"(d[OFF + 28]), "=f"(d[OFF + 29]), "=f"(d[OFF + 30]), "=f"(d[OFF + 31]), "=f"(d[OFF + 32]), "=f"(d[OFF + 33]), "=f"(d[OFF + 34]), "=f"(d[OFF + 35]), "=f"(d[OFF + 36]), "=f"(d[OFF + 37]), "=f"(d[OFF + 38]), "=f"(d[OFF + 39]), "=f"(d[OFF + 40]), "=f"(d[OFF + 41]), "=f"(d[OFF + 42]), "=f"(d[OFF + 43]), "=f"(d[OFF + 44]), "=f"(d[OFF + 45]), "=f"(d[OFF + 46]), "=f"(d[OFF + 47]), "=f"(d[OFF + 48]), "=f"(d[OFF + 49]), "=f"(d[OFF + 50]), "=f"(d[OFF + 51]), "=f"(d[OFF + 52]), "=f"(d[OFF + 53]), "=f"(d[OFF + 54]), "=f"(d[OFF + 55]), "=f"(d[OFF + 56]), "=f"(d[OFF + 57]), "=f"(d[OFF + 58]), "=f"(d[OFF + 59]), "=f"(d[OFF + 60]), "=f"(d[OFF + 61]), "=f"(d[OFF + 62]), "=f"(d[OFF + 63]), "=f"(d[OFF + 64]), "=f"(d[OFF + 65]), "=f"(d[OFF + 66]), "=f"(d[OFF + 67]), "=f"(d[OFF + 68]), "=f"(d[OFF + 69]), "=f"(d[OFF + 70]), "=f"(d[OFF + 71]), "=f"(d[OFF + 72]), "=f"(d[OFF + 73]), "=f"(d[OFF + 74]), "=f"(d[OFF + 75]), "=f"(d[OFF + 76]), "=f"(d[OFF + 77]), "=f"(d[OFF + 78]), "=f"(d[OFF + 79]), "=f"(d[OFF + 80]), "=f"(d[OFF + 81]), "=f"(d[OFF + 82]), "=f"(d[OFF + 83]), "=f"(d[OFF + 84]), "=f"(d[OFF + 85]), "=f"(d[OFF + 86]), "=f"(d[OFF + 87]), "=f"(d[OFF + 88]), "=f"(d[OFF + 89]), "=f"(d[OFF + 90]), "=f"(d[OFF + 91]), "=f"(d[OFF + 92]), "=f"(d[OFF + 93]), "=f"(d[OFF + 94]), "=f"(d[OFF + 95]), "=f"(d[OFF + 96]), "=f"(d[OFF + 97]), "=f"(d[OFF + 98]), "=f"(d[OFF + 99]), "=f"(d[OFF + 100]), "=f"(d[OFF + 101]), "=f"(d[OFF + 102]), "=f"(d[OFF + 103]), "=f"(d[OFF + 104]), "=f"(d[OFF + 105]), "=f"(d[OFF + 106]), "=f"(d[OFF + 107]), "=f"(d[OFF + 108]), "=f"(d[OFF + 109]), "=f"(d[OFF + 110]), "=f"(d[OFF + 111]), "=f"(d[OFF + 112]), "=f"(d[OFF + 113]), "=f"(d[OFF + 114]), "=f"(d[OFF + 115])
            : "r"(a0), "r"(a1), "r"(a2), "r"(a3), "l"(descB), "n"(0));
    }
};
template <int OFF, int NA> struct WG<232, OFF, true, NA> {
    static __device__ __forceinline__ void mma(float (&d)[NA], uint32_t a0, uint32_t a1, uint32_t a2, uint32_t a3, uint64_t descB) {
        asm volatile(
            "{\n"
            ".reg .pred p;\n"
            "setp.ne.b32 p, %121, 0;\n"
            "wgmma.mma_async.sync.aligned.m64n232k16.f32.bf16.bf16 "
            "{%0, %1, %2, %3, %4, %5, %6, %7, %8, %9, %10, %11, %12, %13, %14, %15, %16, %17, %18, %19, %20, %21, %22, %23, %24, %25, %26, %27, %28, %29, %30, %31, %32, %33, %34, %35, %36, %37, %38, %39, %40, %41, %42, %43, %44, %45, %46, %47, %48, %49, %50, %51, %52, %53, %54, %55, %56, %57, %58, %59, %60, %61, %62, %63, %64, %65, %66, %67, %68, %69, %70, %71, %72, %73, %74, %75, %76, %77, %78, %79, %80, %81, %82, %83, %84, %85, %86, %87, %88, %89, %90, %91, %92, %93, %94, %95, %96, %97, %98, %99, %100, %101, %102, %103, %104, %105, %106, %107, %108, %109, %110, %111, %112, %113, %114, %115}, "
            "{%116, %117, %118, %119}, %120, p, 1, 1, 0;\n"
            "}\n"
            : "+f"(d[OFF + 0]), "+f"(d[OFF + 1]), "+f"(d[OFF + 2]), "+f"(d[OFF + 3]), "+f"(d[OFF + 4]), "+f"(d[OFF + 5]), "+f"(d[OFF + 6]), "+f"(d[OFF + 7]), "+f"(d[OFF + 8]), "+f"(d[OFF + 9]), "+f"(d[OFF + 10]), "+f"(d[OFF + 11]), "+f"(d[OFF + 12]), "+f"(d[OFF + 13]), "+f"(d[OFF + 14]), "+f"(d[OFF + 15]), "+f"(d[OFF + 16]), "+f"(d[OFF + 17]), "+f"(d[OFF + 18]), "+f"(d[OFF + 19]), "+f"(d[OFF + 20]), "+f"(d[OFF + 21]), "+f"(d[OFF + 22]), "+f"(d[OFF + 23]), "+f"(d[OFF + 24]), "+f"(d[OFF + 25]), "+f"(d[OFF + 26]), "+f"(d[OFF + 27]), "+f"(d[OFF + 28]), "+f"(d[OFF + 29]), "+f"(d[OFF + 30]), "+f"(d[OFF + 31]), "+f"(d[OFF + 32]), "+f"(d[OFF + 33]), "+f"(d[OFF + 34]), "+f"(d[OFF + 35]), "+f"(d[OFF + 36]), "+f"(d[OFF + 37]), "+f"(d[OFF + 38]), "+f"(d[OFF + 39]), "+f"(d[OFF + 40]), "+f"(d[OFF + 41]), "+f"(d[OFF + 42]), "+f"(d[OFF + 43]), "+f"(d[OFF + 44]), "+f"(d[OFF + 45]), "+f"(d[OFF + 46]), "+f"(d[OFF + 47]), "+f"(d[OFF + 48]), "+f"(d[OFF + 49]), "+f"(d[OFF + 50]), "+f"(d[OFF + 51]), "+f"(d[OFF + 52]), "+f"(d[OFF + 53]), "+f"(d[OFF + 54]), "+f"(d[OFF + 55]), "+f"(d[OFF + 56]), "+f"(d[OFF + 57]), "+f"(d[OFF + 58]), "+f"(d[OFF + 59]), "+f"(d[OFF + 60]), "+f"(d[OFF + 61]), "+f"(d[OFF + 62]), "+f"(d[OFF + 63]), "+f"(d[OFF + 64]), "+f"(d[OFF + 65]), "+f"(d[OFF + 66]), "+f"(d[OFF + 67]), "+f"(d[OFF + 68]), "+f"(d[OFF + 69]), "+f"(d[OFF + 70]), "+f"(d[OFF + 71]), "+f"(d[OFF + 72]), "+f"(d[OFF + 73]), "+f"(d[OFF + 74]), "+f"(d[OFF + 75]), "+f"(d[OFF + 76]), "+f"(d[OFF + 77]), "+f"(d[OFF + 78]), "+f"(d[OFF + 79]), "+f"(d[OFF + 80]), "+f"(d[OFF + 81]), "+f"(d[OFF + 82]), "+f"(d[OFF + 83]), "+f"(d[OFF + 84]), "+f"(d[OFF + 85]), "+f"(d[OFF + 86]), "+f"(d[OFF + 87]), "+f"(d[OFF + 88]), "+f"(d[OFF + 89]), "+f"(d[OFF + 90]), "+f"(d[OFF + 91]), "+f"(d[OFF + 92]), "+f"(d[OFF + 93]), "+f"(d[OFF + 94]), "+f"(d[OFF + 95]), "+f"(d[OFF + 96]), "+f"(d[OFF + 97]), "+f"(d[OFF + 98]), "+f"(d[OFF + 99]), "+f"(d[OFF + 100]), "+f"(d[OFF + 101]), "+f"(d[OFF + 102]), "+f"(d[OFF + 103]), "+f"(d[OFF + 104]), "+f"(d[OFF + 105]), "+f"(d[OFF + 106]), "+f"(d[OFF + 107]), "+f"(d[OFF + 108]), "+f"(d[OFF + 109]), "+f"(d[OFF + 110]), "+f"(d[OFF + 111]), "+f"(d[OFF + 112]), "+f"(d[OFF + 113]), "+f"(d[OFF + 114]), "+f"(d[OFF + 115])
            : "r"(a0), "r"(a1), "r"(a2), "r"(a3), "l"(descB), "n"(1));
    }
};
template <int OFF, int NA> struct WG<208, OFF, false, NA> {
    static __device__ __forceinline__ void mma(float (&d)[NA], uint32_t a0, uint32_t a1, uint32_t a2, uint32_t a3, uint64_t descB) {
        asm volatile(
            "{\n"
            ".reg .pred p;\n"
            "setp.ne.b32 p, %109, 0;\n"
            "wgmma.mma_async.sync.aligned.m64n208k16.f32.bf16.bf16 "
            "{%0, %1, %2, %3, %4, %5, %6, %7, %8, %9, %10, %11, %12, %13, %14, %15, %16, %17, %18, %19, %20, %21, %22, %23, %24, %25, %26, %27, %28, %29, %30, %31, %32, %33, %34, %35, %36, %37, %38, %39, %40, %41, %42, %43, %44, %45, %46, %47, %48, %49, %50, %51, %52, %53, %54, %55, %56, %57, %58, %59, %60, %61, %62, %63, %64, %65, %66, %67, %68, %69, %70, %71, %72, %73, %74, %75, %76, %77, %78, %79, %80, %81, %82, %83, %84, %85, %86, %87, %88, %89, %90, %91, %92, %93, %94, %95, %96, %97, %98, %99, %100, %101, %102, %103}, "
            "{%104, %105, %106, %107}, %108, p, 1, 1, 0;\n"
            "}\n"
            : "=f"(d[OFF + 0]), "=f"(d[OFF + 1]), "=f"(d[OFF + 2]), "=f"(d[OFF + 3]), "=f"(d[OFF + 4]), "=f"(d[OFF + 5]), "=f"(d[OFF + 6]), "=f"(d[OFF + 7]), "=f"(d[OFF + 8]), "=f"(d[OFF + 9]), "=f"(d[OFF + 10]), "=f"(d[OFF + 11]), "=f"(d[OFF + 12]), "=f"(d[OFF + 13]), "=f"(d[OFF + 14]), "=f"(d[OFF + 15]), "=f"(d[OFF + 16]), "=f"(d[OFF + 17]), "=f"(d[OFF + 18]), "=f"(d[OFF + 19]), "=f"(d[OFF + 20]), "=f"(d[OFF + 21]), "=f"(d[OFF + 22]), "=f"(d[OFF + 23]), "=f"(d[OFF + 24]), "=f"(d[OFF + 25]), "=f"(d[OFF + 26]), "=f"(d[OFF + 27]), "=f"(d[OFF + 28]), "=f"(d[OFF + 29]), "=f"(d[OFF + 30]), "=f"(d[OFF + 31]), "=f"(d[OFF + 32]), "=f"(d[OFF + 33]), "=f"(d[OFF + 34]), "=f"(d[OFF + 35]), "=f"(d[OFF + 36]), "=f"(d[OFF + 37]), "=f"(d[OFF + 38]), "=f"(d[OFF + 39]), "=f"(d[OFF + 40]), "=f"(d[OFF + 41]), "=f"(d[OFF + 42]), "=f"(d[OFF + 43]), "=f"(d[OFF + 44]), "=f"(d[OFF + 45]), "=f"(d[OFF + 46]), "=f"(d[OFF + 47]), "=f"(d[OFF + 48]), "=f"(d[OFF + 49]), "=f"(d[OFF + 50]), "=f"(d[OFF + 51]), "=f"(d[OFF + 52]), "=f"(d[OFF + 53]), "=f"(d[OFF + 54]), "=f"(d[OFF + 55]), "=f"(d[OFF + 56]), "=f"(d[OFF + 57]), "=f"(d[OFF + 58]), "=f"(d[OFF + 59]), "=f"(d[OFF + 60]), "=f"(d[OFF + 61]), "=f"(d[OFF + 62]), "=f"(d[OFF + 63]), "=f"(d[OFF + 64]), "=f"(d[OFF + 65]), "=f"(d[OFF + 66]), "=f"(d[OFF + 67]), "=f"(d[OFF + 68]), "=f"(d[OFF + 69]), "=f"(d[OFF + 70]), "=f"(d[OFF + 71]), "=f"(d[OFF + 72]), "=f"(d[OFF + 73]), "=f"(d[OFF + 74]), "=f"(d[OFF + 75]), "=f"(d[OFF + 76]), "=f"(d[OFF + 77]), "=f"(d[OFF + 78]), "=f"(d[OFF + 79]), "=f"(d[OFF + 80]), "=f"(d[OFF + 81]), "=f"(d[OFF + 82]), "=f"(d[OFF + 83]), "=f"(d[OFF + 84]), "=f"(d[OFF + 85]), "=f"(d[OFF + 86]), "=f"(d[OFF + 87]), "=f"(d[OFF + 88]), "=f"(d[OFF + 89]), "=f"(d[OFF + 90]), "=f"(d[OFF + 91]), "=f"(d[OFF + 92]), "=f"(d[OFF + 93]), "=f"(d[OFF + 94]), "=f"(d[OFF + 95]), "=f"(d[OFF + 96]), "=f"(d[OFF + 97]), "=f"(d[OFF + 98]), "=f"(d[OFF + 99]), "=f"(d[OFF + 100]), "=f"(d[OFF + 101]), "=f"(d[OFF + 102]), "=f"(d[OFF + 103])
            : "r"(a0), "r"(a1), "r"(a2), "r"(a3), "l"(descB), "n"(0));
    }
};
template <int OFF, int NA> struct WG<208, OFF, true, NA> {
    static __device__ __forceinline__ void mma(float (&d)[NA], uint32_t a0, uint32_t a1, uint32_t a2, uint32_t a3, uint64_t descB) {
        asm volatile(
            "{\n"
            ".reg .pred p;\n"
            "setp.ne.b32 p, %109, 0;\n"
            "wgmma.mma_async.sync.aligned.m64n208k16.f32.bf16.bf16 "
            "{%0, %1, %2, %3, %4, %5, %6, %7, %8, %9, %10, %11, %12, %13, %14, %15, %16, %17, %18, %19, %20, %21, %22, %23, %24, %25, %26, %27, %28, %29, %30, %31, %32, %33, %34, %35, %36, %37, %38, %39, %40, %41, %42, %43, %44, %45, %46, %47, %48, %49, %50, %51, %52, %53, %54, %55, %56, %57, %58, %59, %60, %61, %62, %63, %64, %65, %66, %67, %68, %69, %70, %71, %72, %73, %74, %75, %76, %77, %78, %79, %80, %81, %82, %83, %84, %85, %86, %87, %88, %89, %90, %91, %92, %93, %94, %95, %96, %97, %98, %99, %100, %101, %102, %103}, "
            "{%104, %105, %106, %107}, %108, p, 1, 1, 0;\n"
            "}\n"
            : "+f"(d[OFF + 0]), "+f"(d[OFF + 1]), "+f"(d[OFF + 2]), "+f"(d[OFF + 3]), "+f"(d[OFF + 4]), "+f"(d[OFF + 5]), "+f"(d[OFF + 6]), "+f"(d[OFF + 7]), "+f"(d[OFF + 8]), "+f"(d[OFF + 9]), "+f"(d[OFF + 10]), "+f"(d[OFF + 11]), "+f"(d[OFF + 12]), "+f"(d[OFF + 13]), "+f"(d[OFF + 14]), "+f"(d[OFF + 15]), "+f"(d[OFF + 16]), "+f"(d[OFF + 17]), "+f"(d[OFF + 18]), "+f"(d[OFF + 19]), "+f"(d[OFF + 20]), "+f"(d[OFF + 21]), "+f"(d[OFF + 22]), "+f"(d[OFF + 23]), "+f"(d[OFF + 24]), "+f"(d[OFF + 25]), "+f"(d[OFF + 26]), "+f"(d[OFF + 27]), "+f"(d[OFF + 28]), "+f"(d[OFF + 29]), "+f"(d[OFF + 30]), "+f"(d[OFF + 31]), "+f"(d[OFF + 32]), "+f"(d[OFF + 33]), "+f"(d[OFF + 34]), "+f"(d[OFF + 35]), "+f"(d[OFF + 36]), "+f"(d[OFF + 37]), "+f"(d[OFF + 38]), "+f"(d[OFF + 39]), "+f"(d[OFF + 40]), "+f"(d[OFF + 41]), "+f"(d[OFF + 42]), "+f"(d[OFF + 43]), "+f"(d[OFF + 44]), "+f"(d[OFF + 45]), "+f"(d[OFF + 46]), "+f"(d[OFF + 47]), "+f"(d[OFF + 48]), "+f"(d[OFF + 49]), "+f"(d[OFF + 50]), "+f"(d[OFF + 51]), "+f"(d[OFF + 52]), "+f"(d[OFF + 53]), "+f"(d[OFF + 54]), "+f"(d[OFF + 55]), "+f"(d[OFF + 56]), "+f"(d[OFF + 57]), "+f"(d[OFF + 58]), "+f"(d[OFF + 59]), "+f"(d[OFF + 60]), "+f"(d[OFF + 61]), "+f"(d[OFF + 62]), "+f"(d[OFF + 63]), "+f"(d[OFF + 64]), "+f"(d[OFF + 65]), "+f"(d[OFF + 66]), "+f"(d[OFF + 67]), "+f"(d[OFF + 68]), "+f"(d[OFF + 69]), "+f"(d[OFF + 70]), "+f"(d[OFF + 71]), "+f"(d[OFF + 72]), "+f"(d[OFF + 73]), "+f"(d[OFF + 74]), "+f"(d[OFF + 75]), "+f"(d[OFF + 76]), "+f"(d[OFF + 77]), "+f"(d[OFF + 78]), "+f"(d[OFF + 79]), "+f"(d[OFF + 80]), "+f"(d[OFF + 81]), "+f"(d[OFF + 82]), "+f"(d[OFF + 83]), "+f"(d[OFF + 84]), "+f"(d[OFF + 85]), "+f"(d[OFF + 86]), "+f"(d[OFF + 87]), "+f"(d[OFF + 88]), "+f"(d[OFF + 89]), "+f"(d[OFF + 90]), "+f"(d[OFF + 91]), "+f"(d[OFF + 92]), "+f"(d[OFF + 93]), "+f"(d[OFF + 94]), "+f"(d[OFF + 95]), "+f"(d[OFF + 96]), "+f"(d[OFF + 97]), "+f"(d[OFF + 98]), "+f"(d[OFF + 99]), "+f"(d[OFF + 100]), "+f"(d[OFF + 101]), "+f"(d[OFF + 102]), "+f"(d[OFF + 103])
            : "r"(a0), "r"(a1), "r"(a2), "r"(a3), "l"(descB), "n"(1));
    }
};
template <int OFF, int NA> struct WG<120, OFF, false, NA> {
    static __device__ __forceinline__ void mma(float (&d)[NA], uint32_t a0, uint32_t a1, uint32_t a2, uint32_t a3, uint64_t descB) {
        asm volatile(
            "{\n"
            ".reg .pred p;\n"
            "setp.ne.b32 p, %65, 0;\n"
            "wgmma.mma_async.sync.aligned.m64n120k16.f32.bf16.bf16 "
            "{%0, %1, %2, %3, %4, %5, %6, %7, %8, %9, %10, %11, %12, %13, %14, %15, %16, %17, %18, %19, %20, %21, %22, %23, %24, %25, %26, %27, %28, %29, %30, %31, %32, %33, %34, %35, %36, %37, %38, %39, %40, %41, %42, %43, %44, %45, %46, %47, %48, %49, %50, %51, %52, %53, %54, %55, %56, %57, %58, %59}, "
            "{%60, %61, %62, %63}, %64, p, 1, 1, 0;\n"
            "}\n"
            : "=f"(d[OFF + 0]), "=f"(d[OFF + 1]), "=f"(d[OFF + 2]), "=f"(d[OFF + 3]), "=f"(d[OFF + 4]), "=f"(d[OFF + 5]), "=f"(d[OFF + 6]), "=f"(d[OFF + 7]), "=f"(d[OFF + 8]), "=f"(d[OFF + 9]), "=f"(d[OFF + 10]), "=f"(d[OFF + 11]), "=f"(d[OFF + 12]), "=f"(d[OFF + 13]), "=f"(d[OFF + 14]), "=f"(d[OFF + 15]), "=f"(d[OFF + 16]), "=f"(d[OFF + 17]), "=f"(d[OFF + 18]), "=f"(d[OFF + 19]), "=f"(d[OFF + 20]), "=f"(d[OFF + 21]), "=f"(d[OFF + 22]), "=f"(d[OFF + 23]), "=f"(d[OFF + 24]), "=f"(d[OFF + 25]), "=f"(d[OFF + 26]), "=f"(d[OFF + 27]), "=f"(d[OFF + 28]), "=f"(d[OFF + 29]), "=f"(d[OFF + 30]), "=f"(d[OFF + 31]), "=f"(d[OFF + 32]), "=f"(d[OFF + 33]), "=f"(d[OFF + 34]), "=f"(d[OFF + 35]), "=f"(d[OFF + 36]), "=f"(d[OFF + 37]), "=f"(d[OFF + 38]), "=f"(d[OFF + 39]), "=f"(d[OFF + 40]), "=f"(d[OFF + 41]), "=f"(d[OFF + 42]), "=f"(d[OFF + 43]), "=f"(d[OFF + 44]), "=f"(d[OFF + 45]), "=f"(d[OFF + 46]), "=f"(d[OFF + 47]), "=f"(d[OFF + 48]), "=f"(d[OFF + 49]), "=f"(d[OFF + 50]), "=f"(d[OFF + 51]), "=f"(d[OFF + 52]), "=f"(d[OFF + 53]), "=f"(d[OFF + 54]), "=f"(d[OFF + 55]), "=f"(d[OFF + 56]), "=f"(d[OFF + 57]), "=f"(d[OFF + 58]), "=f"(d[OFF + 59])
            : "r"(a0), "r"(a1), "r"(a2), "r"(a3), "l"(descB), "n"(0));
    }
};
template <int OFF, int NA> struct WG<120, OFF, true, NA> {
    static __device__ __forceinline__ void mma(float (&d)[NA], uint32_t a0, uint32_t a1, uint32_t a2, uint32_t a3, uint64_t descB) {
        asm volatile(
            "{\n"
            ".reg .pred p;\n"
            "setp.ne.b32 p, %65, 0;\n"
            "wgmma.mma_async.sync.aligned.m64n120k16.f32.bf16.bf16 "
            "{%0, %1, %2, %3, %4, %5, %6, %7, %8, %9, %10, %11, %12, %13, %14, %15, %16, %17, %18, %19, %20, %21, %22, %23, %24, %25, %26, %27, %28, %29, %30, %31, %32, %33, %34, %35, %36, %37, %38, %39, %40, %41, %42, %43, %44, %45, %46, %47, %48, %49, %50, %51, %52, %53, %54, %55, %56, %57, %58, %59}, "
            "{%60, %61, %62, %63}, %64, p, 1, 1, 0;\n"
            "}\n"
            : "+f"(d[OFF + 0]), "+f"(d[OFF + 1]), "+f"(d[OFF + 2]), "+f"(d[OFF + 3]), "+f"(d[OFF + 4]), "+f"(d[OFF + 5]), "+f"(d[OFF + 6]), "+f"(d[OFF + 7]), "+f"(d[OFF + 8]), "+f"(d[OFF + 9]), "+f"(d[OFF + 10]), "+f"(d[OFF + 11]), "+f"(d[OFF + 12]), "+f"(d[OFF + 13]), "+f"(d[OFF + 14]), "+f"(d[OFF + 15]), "+f"(d[OFF + 16]), "+f"(d[OFF + 17]), "+f"(d[OFF + 18]), "+f"(d[OFF + 19]), "+f"(d[OFF + 20]), "+f"(d[OFF + 21]), "+f"(d[OFF + 22]), "+f"(d[OFF + 23]), "+f"(d[OFF + 24]), "+f"(d[OFF + 25]), "+f"(d[OFF + 26]), "+f"(d[OFF + 27]), "+f"(d[OFF + 28]), "+f"(d[OFF + 29]), "+f"(d[OFF + 30]), "+f"(d[OFF + 31]), "+f"(d[OFF + 32]), "+f"(d[OFF + 33]), "+f"(d[OFF + 34]), "+f"(d[OFF + 35]), "+f"(d[OFF + 36]), "+f"(d[OFF + 37]), "+f"(d[OFF + 38]), "+f"(d[OFF + 39]), "+f"(d[OFF + 40]), "+f"(d[OFF + 41]), "+f"(d[OFF + 42]), "+f"(d[OFF + 43]), "+f"(d[OFF + 44]), "+f"(d[OFF + 45]), "+f"(d[OFF + 46]), "+f"(d[OFF + 47]), "+f"(d[OFF + 48]), "+f"(d[OFF + 49]), "+f"(d[OFF + 50]), "+f"(d[OFF + 51]), "+f"(d[OFF + 52]), "+f"(d[OFF + 53]), "+f"(d[OFF + 54]), "+f"(d[OFF + 55]), "+f"(d[OFF + 56]), "+f"(d[OFF + 57]), "+f"(d[OFF + 58]), "+f"(d[OFF + 59])
            : "r"(a0), "r"(a1), "r"(a2), "r"(a3), "l"(descB), "n"(1));
    }
};
template <int OFF, int NA> struct WG<112, OFF, false, NA> {
    static __device__ __forceinline__ void mma(float (&d)[NA], uint32_t a0, uint32_t a1, uint32_t a2, uint32_t a3, uint64_t descB) {
        asm volatile(
            "{\n"
            ".reg .pred p;\n"
            "setp.ne.b32 p, %61, 0;\n"
            "wgmma.mma_async.sync.aligned.m64n112k16.f32.bf16.bf16 "
            "{%0, %1, %2, %3, %4, %5, %6, %7, %8, %9, %10, %11, %12, %13, %14, %15, %16, %17, %18, %19, %20, %21, %22, %23, %24, %25, %26, %27, %28, %29, %30, %31, %32, %33, %34, %35, %36, %37, %38, %39, %40, %41, %42, %43, %44, %45, %46, %47, %48, %49, %50, %51, %52, %53, %54, %55}, "
            "{%56, %57, %58, %59}, %60, p, 1, 1, 0;\n"
            "}\n"
            : "=f"(d[OFF + 0]), "=f"(d[OFF + 1]), "=f"(d[OFF + 2]), "=f"(d[OFF + 3]), "=f"(d[OFF + 4]), "=f"(d[OFF + 5]), "=f"(d[OFF + 6]), "=f"(d[OFF + 7]), "=f"(d[OFF + 8]), "=f"(d[OFF + 9]), "=f"(d[OFF + 10]), "=f"(d[OFF + 11]), "=f"(d[OFF + 12]), "=f"(d[OFF + 13]), "=f"(d[OFF + 14]), "=f"(d[OFF + 15]), "=f"(d[OFF + 16]), "=f"(d[OFF + 17]), "=f"(d[OFF + 18]), "=f"(d[OFF + 19]), "=f"(d[OFF + 20]), "=f"(d[OFF + 21]), "=f"(d[OFF + 22]), "=f"(d[OFF + 23]), "=f"(d[OFF + 24]), "=f"(d[OFF + 25]), "=f"(d[OFF + 26]), "=f"(d[OFF + 27]), "=f"(d[OFF + 28]), "=f"(d[OFF + 29]), "=f"(d[OFF + 30]), "=f"(d[OFF + 31]), "=f"(d[OFF + 32]), "=f"(d[OFF + 33]), "=f"(d[OFF + 34]), "=f"(d[OFF + 35]), "=f"(d[OFF + 36]), "=f"(d[OFF + 37]), "=f"(d[OFF + 38]), "=f"(d[OFF + 39]), "=f"(d[OFF + 40]), "=f"(d[OFF + 41]), "=f"(d[OFF + 42]), "=f"(d[OFF + 43]), "=f"(d[OFF + 44]), "=f"(d[OFF + 45]), "=f"(d[OFF + 46]), "=f"(d[OFF + 47]), "=f"(d[OFF + 48]), "=f"(d[OFF + 49]), "=f"(d[OFF + 50]), "=f"(d[OFF + 51]), "=f"(d[OFF + 52]), "=f"(d[OFF + 53]), "=f"(d[OFF + 54]), "=f"(d[OFF + 55])
            : "r"(a0), "r"(a1), "r"(a2), "r"(a3), "l"(descB), "n"(0));
    }
};
template <int OFF, int NA> struct WG<112, OFF, true, NA> {
    static __device__ __forceinline__ void mma(float (&d)[NA], uint32_t a0, uint32_t a1, uint32_t a2, uint32_t a3, uint64_t descB) {
        asm volatile(
            "{\n"
            ".reg .pred p;\n"
            "setp.ne.b32 p, %61, 0;\n"
            "wgmma.mma_async.sync.aligned.m64n112k16.f32.bf16.bf16 "
            "{%0, %1, %2, %3, %4, %5, %6, %7, %8, %9, %10, %11, %12, %13, %14, %15, %16, %17, %18, %19, %20, %21, %22, %23, %24, %25, %26, %27, %28, %29, %30, %31, %32, %33, %34, %35, %36, %37, %38, %39, %40, %41, %42, %43, %44, %45, %46, %47, %48, %49, %50, %51, %52, %53, %54, %55}, "
            "{%56, %57, %58, %59}, %60, p, 1, 1, 0;\n"
            "}\n"
            : "+f"(d[OFF + 0]), "+f"(d[OFF + 1]), "+f"(d[OFF + 2]), "+f"(d[OFF + 3]), "+f"(d[OFF + 4]), "+f"(d[OFF + 5]), "+f"(d[OFF + 6]), "+f"(d[OFF + 7]), "+f"(d[OFF + 8]), "+f"(d[OFF + 9]), "+f"(d[OFF + 10]), "+f"(d[OFF + 11]), "+f"(d[OFF + 12]), "+f"(d[OFF + 13]), "+f"(d[OFF + 14]), "+f"(d[OFF + 15]), "+f"(d[OFF + 16]), "+f"(d[OFF + 17]), "+f"(d[OFF + 18]), "+f"(d[OFF + 19]), "+f"(d[OFF + 20]), "+f"(d[OFF + 21]), "+f"(d[OFF + 22]), "+f"(d[OFF + 23]), "+f"(d[OFF + 24]), "+f"(d[OFF + 25]), "+f"(d[OFF + 26]), "+f"(d[OFF + 27]), "+f"(d[OFF + 28]), "+f"(d[OFF + 29]), "+f"(d[OFF + 30]), "+f"(d[OFF + 31]), "+f"(d[OFF + 32]), "+f"(d[OFF + 33]), "+f"(d[OFF + 34]), "+f"(d[OFF + 35]), "+f"(d[OFF + 36]), "+f"(d[OFF + 37]), "+f"(d[OFF + 38]), "+f"(d[OFF + 39]), "+f"(d[OFF + 40]), "+f"(d[OFF + 41]), "+f"(d[OFF + 42]), "+f"(d[OFF + 43]), "+f"(d[OFF + 44]), "+f"(d[OFF + 45]), "+f"(d[OFF + 46]), "+f"(d[OFF + 47]), "+f"(d[OFF + 48]), "+f"(d[OFF + 49]), "+f"(d[OFF + 50]), "+f"(d[OFF + 51]), "+f"(d[OFF + 52]), "+f"(d[OFF + 53]), "+f"(d[OFF + 54]), "+f"(d[OFF + 55])
            : "r"(a0), "r"(a1), "r"(a2), "r"(a3), "l"(descB), "n"(1));
    }
};
template <int OFF, int NA> struct WG<96, OFF, false, NA> {
    static __device__ __forceinline__ void mma(float (&d)[NA], uint32_t a0, uint32_t a1, uint32_t a2, uint32_t a3, uint64_t descB) {
        asm volatile(
            "{\n"
            ".reg .pred p;\n"
            "setp.ne.b32 p, %53, 0;\n"
            "wgmma.mma_async.sync.aligned.m64n96k16.f32.bf16.bf16 "
            "{%0, %1, %2, %3, %4, %5, %6, %7, %8, %9, %10, %11, %12, %13, %14, %15, %16, %17, %18, %19, %20, %21, %22, %23, %24, %25, %26, %27, %28, %29, %30, %31, %32, %33, %34, %35, %36, %37, %38, %39, %40, %41, %42, %43, %44, %45, %46, %47}, "
            "{%48, %49, %50, %51}, %52, p, 1, 1, 0;\n"
            "}\n"
            : "=f"(d[OFF + 0]), "=f"(d[OFF + 1]), "=f"(d[OFF + 2]), "=f"(d[OFF + 3]), "=f"(d[OFF + 4]), "=f"(d[OFF + 5]), "=f"(d[OFF + 6]), "=f"(d[OFF + 7]), "=f"(d[OFF + 8]), "=f"(d[OFF + 9]), "=f"(d[OFF + 10]), "=f"(d[OFF + 11]), "=f"(d[OFF + 12]), "=f"(d[OFF + 13]), "=f"(d[OFF + 14]), "=f"(d[OFF + 15]), "=f"(d[OFF + 16]), "=f"(d[OFF + 17]), "=f"(d[OFF + 18]), "=f"(d[OFF + 19]), "=f"(d[OFF + 20]), "=f"(d[OFF + 21]), "=f"(d[OFF + 22]), "=f"(d[OFF + 23]), "=f"(d[OFF + 24]), "=f"(d[OFF + 25]), "=f"(d[OFF + 26]), "=f"(d[OFF + 27]), "=f"(d[OFF + 28]), "=f"(d[OFF + 29]), "=f"(d[OFF + 30]), "=f"(d[OFF + 31]), "=f"(d[OFF + 32]), "=f"(d[OFF + 33]), "=f"(d[OFF + 34]), "=f"(d[OFF + 35]), "=f"(d[OFF + 36]), "=f"(d[OFF + 37]), "=f"(d[OFF + 38]), "=f"(d[OFF + 39]), "=f"(d[OFF + 40]), "=f"(d[OFF + 41]), "=f"(d[OFF + 42]), "=f"(d[OFF + 43]), "=f"(d[OFF + 44]), "=f"(d[OFF + 45]), "=f"(d[OFF + 46]), "=f"(d[OFF + 47])
            : "r"(a0), "r"(a1), "r"(a2), "r"(a3), "l"(descB), "n"(0));
    }
};
template <int OFF, int NA> struct WG<96, OFF, true, NA> {
    static __device__ __forceinline__ void mma(float (&d)[NA], uint32_t a0, uint32_t a1, uint32_t a2, uint32_t a3, uint64_t descB) {
        asm volatile(
            "{\n"
            ".reg .pred p;\n"
            "setp.ne.b32 p, %53, 0;\n"
            "wgmma.mma_async.sync.aligned.m64n96k16.f32.bf16.bf16 "
            "{%0, %1, %2, %3, %4, %5, %6, %7, %8, %9, %10, %11, %12, %13, %14, %15, %16, %17, %18, %19, %20, %21, %22, %23, %24, %25, %26, %27, %28, %29, %30, %31, %32, %33, %34, %35, %36, %37, %38, %39, %40, %41, %42, %43, %44, %45, %46, %47}, "
            "{%48, %49, %50, %51}, %52, p, 1, 1, 0;\n"
            "}\n"
            : "+f"(d[OFF + 0]), "+f"(d[OFF + 1]), "+f"(d[OFF + 2]), "+f"(d[OFF + 3]), "+f"(d[OFF + 4]), "+f"(d[OFF + 5]), "+f"(d[OFF + 6]), "+f"(d[OFF + 7]), "+f"(d[OFF + 8]), "+f"(d[OFF + 9]), "+f"(d[OFF + 10]), "+f"(d[OFF + 11]), "+f"(d[OFF + 12]), "+f"(d[OFF + 13]), "+f"(d[OFF + 14]), "+f"(d[OFF + 15]), "+f"(d[OFF + 16]), "+f"(d[OFF + 17]), "+f"(d[OFF + 18]), "+f"(d[OFF + 19]), "+f"(d[OFF + 20]), "+f"(d[OFF + 21]), "+f"(d[OFF + 22]), "+f"(d[OFF + 23]), "+f"(d[OFF + 24]), "+f"(d[OFF + 25]), "+f"(d[OFF + 26]), "+f"(d[OFF + 27]), "+f"(d[OFF + 28]), "+f"(d[OFF + 29]), "+f"(d[OFF + 30]), "+f"(d[OFF + 31]), "+f"(d[OFF + 32]), "+f"(d[OFF + 33]), "+f"(d[OFF + 34]), "+f"(d[OFF + 35]), "+f"(d[OFF + 36]), "+f"(d[OFF + 37]), "+f"(d[OFF + 38]), "+f"(d[OFF + 39]), "+f"(d[OFF + 40]), "+f"(d[OFF + 41]), "+f"(d[OFF + 42]), "+f"(d[OFF + 43]), "+f"(d[OFF + 44]), "+f"(d[OFF + 45]), "+f"(d[OFF + 46]), "+f"(d[OFF + 47])
            : "r"(a0), "r"(a1), "r"(a2), "r"(a3), "l"(descB), "n"(1));
    }
};
template <int OFF, int NA> struct WG<64, OFF, true, NA> {
    static __device__ __forceinline__ void mma(float (&d)[NA], uint32_t a0, uint32_t a1, uint32_t a2, uint32_t a3, uint64_t descB) {
        asm volatile(
            "{\n"
            ".reg .pred p;\n"
            "setp.ne.b32 p, %37, 0;\n"
            "wgmma.mma_async.sync.aligned.m64n64k16.f32.bf16.bf16 "
            "{%0, %1, %2, %3, %4, %5, %6, %7, %8, %9, %10, %11, %12, %13, %14, %15, %16, %17, %18, %19, %20, %21, %22, %23, %24, %25, %26, %27, %28, %29, %30, %31}, "
            "{%32, %33, %34, %35}, %36, p, 1, 1, 0;\n"
            "}\n"
            : "+f"(d[OFF + 0]), "+f"(d[OFF + 1]), "+f"(d[OFF + 2]), "+f"(d[OFF + 3]), "+f"(d[OFF + 4]), "+f"(d[OFF + 5]), "+f"(d[OFF + 6]), "+f"(d[OFF + 7]), "+f"(d[OFF + 8]), "+f"(d[OFF + 9]), "+f"(d[OFF + 10]), "+f"(d[OFF + 11]), "+f"(d[OFF + 12]), "+f"(d[OFF + 13]), "+f"(d[OFF + 14]), "+f"(d[OFF + 15]), "+f"(d[OFF + 16]), "+f"(d[OFF + 17]), "+f"(d[OFF + 18]), "+f"(d[OFF + 19]), "+f"(d[OFF + 20]), "+f"(d[OFF + 21]), "+f"(d[OFF + 22]), "+f"(d[OFF + 23]), "+f"(d[OFF + 24]), "+f"(d[OFF + 25]), "+f"(d[OFF + 26]), "+f"(d[OFF + 27]), "+f"(d[OFF + 28]), "+f"(d[OFF + 29]), "+f"(d[OFF + 30]), "+f"(d[OFF + 31])
            : "r"(a0), "r"(a1), "r"(a2), "r"(a3), "l"(descB), "n"(1));
    }
};
template <int OFF, int NA> struct WG<48, OFF, true, NA> {
    static __device__ __forceinline__ void mma(float (&d)[NA], uint32_t a0, uint32_t a1, uint32_t a2, uint32_t a3, uint64_t descB) {
        asm volatile(
            "{\n"
            ".reg .pred p;\n"
            "setp.ne.b32 p, %29, 0;\n"
            "wgmma.mma_async.sync.aligned.m64n48k16.f32.bf16.bf16 "
            "{%0, %1, %2, %3, %4, %5, %6, %7, %8, %9, %10, %11, %12, %13, %14, %15, %16, %17, %18, %19, %20, %21, %22, %23}, "
            "{%24, %25, %26, %27}, %28, p, 1, 1, 0;\n"
            "}\n"
            : "+f"(d[OFF + 0]), "+f"(d[OFF + 1]), "+f"(d[OFF + 2]), "+f"(d[OFF + 3]), "+f"(d[OFF + 4]), "+f"(d[OFF + 5]), "+f"(d[OFF + 6]), "+f"(d[OFF + 7]), "+f"(d[OFF + 8]), "+f"(d[OFF + 9]), "+f"(d[OFF + 10]), "+f"(d[OFF + 11]), "+f"(d[OFF + 12]), "+f"(d[OFF + 13]), "+f"(d[OFF + 14]), "+f"(d[OFF + 15]), "+f"(d[OFF + 16]), "+f"(d[OFF + 17]), "+f"(d[OFF + 18]), "+f"(d[OFF + 19]), "+f"(d[OFF + 20]), "+f"(d[OFF + 21]), "+f"(d[OFF + 22]), "+f"(d[OFF + 23])
            : "r"(a0), "r"(a1), "r"(a2), "r"(a3), "l"(descB), "n"(1));
    }
};
template <int OFF, int NA> struct WG<32, OFF, true, NA> {
    static __device__ __forceinline__ void mma(float (&d)[NA], uint32_t a0, uint32_t a1, uint32_t a2, uint32_t a3, uint64_t descB) {
        asm volatile(
            "{\n"
            ".reg .pred p;\n"
            "setp.ne.b32 p, %21, 0;\n"
            "wgmma.mma_async.sync.aligned.m64n32k16.f32.bf16.bf16 "
            "{%0, %1, %2, %3, %4, %5, %6, %7, %8, %9, %10, %11, %12, %13, %14, %15}, "
            "{%16, %17, %18, %19}, %20, p, 1, 1, 0;\n"
            "}\n"
            : "+f"(d[OFF + 0]), "+f"(d[OFF + 1]), "+f"(d[OFF + 2]), "+f"(d[OFF + 3]), "+f"(d[OFF + 4]), "+f"(d[OFF + 5]), "+f"(d[OFF + 6]), "+f"(d[OFF + 7]), "+f"(d[OFF + 8]), "+f"(d[OFF + 9]), "+f"(d[OFF + 10]), "+f"(d[OFF + 11]), "+f"(d[OFF + 12]), "+f"(d[OFF + 13]), "+f"(d[OFF + 14]), "+f"(d[OFF + 15])
            : "r"(a0), "r"(a1), "r"(a2), "r"(a3), "l"(descB), "n"(1));
    }
};

__device__ __forceinline__ int round_time(int r) { return DLY_R0 + r * DLY_R; }
__host__ __device__ constexpr int gate_time(int d) { return d == 0 ? DLY_POLL : DLY_P1 + (d - 1) * DLY_PS; }
__device__ __forceinline__ void unit_pos(uint32_t u, uint32_t& q, uint32_t& fg) {
    static_assert(W1_FG == 64 && W2_FG == 48, "unit order");
    const uint32_t r = u - NQ * W1_FG, q2 = (r * 1366) >> 16;
    q = u < NQ * W1_FG ? u >> 6 : q2;
    fg = u < NQ * W1_FG ? u & 63 : W1_FG + r - q2 * 48;
}
template <class T> __device__ __forceinline__ T* add_off(T* p, uint32_t bytes) {
    uint64_t r;
    asm("{\n.reg .b64 o;\ncvt.u64.u32 o, %2;\nadd.u64 %0, %1, o;\n}\n" : "=l"(r) : "l"(p), "r"(bytes));
    return (T*)r;
}
__device__ __forceinline__ uint32_t unit_src(uint32_t q, uint32_t fg) { return q * (32 * kN * 4) + fg * 128; }
__device__ __forceinline__ uint32_t lane_src(int lane) { return (lane >> 3) * (2 * kN * 4) + (lane & 7) * 16; }
__device__ __forceinline__ uint32_t unit_dst(uint32_t q, uint32_t fg) {
    return ((fg >> 2) * KSTEPS + (q >> 1)) * 8192 + (fg & 3) * 2048 + (q & 1) * 512;
}
__device__ __forceinline__ uint32_t lane_dst(int lane) { return ((lane >> 2) & 1) * 1024 + (lane & 3) * 64 + (lane >> 3) * 16; }
__device__ __forceinline__ uint32_t lane_unit(int lane) {
    return ((lane >> 3) & 1) * 256 + (((lane >> 4) ^ (lane >> 3)) & 1) * 64 + (lane & 3) * 16 + ((lane >> 2) & 1) * 8;
}
__device__ __forceinline__ constexpr int unit_row(int i) { return 16 * (i >> 2) + 8 * ((i >> 1) & 1) + (i & 1); }
__device__ __forceinline__ void load_unit(uint4 (&v)[8], const int* p) {
#pragma unroll
    for (int i = 0; i < 8; i++) v[i] = ldg_stream(p + (size_t)unit_row(i) * kN);
}
__device__ __forceinline__ uint32_t bytes4(uint32_t v0, uint32_t v1, uint32_t v2, uint32_t v3) {
    return prmt(prmt(v0, v1, 0x0040), prmt(v2, v3, 0x0040), 0x5410);
}
__device__ __forceinline__ void pk_gather(uint32_t (&e)[4], uint32_t (&o)[4], const uint4 (&v)[8]) {
    e[0] = bytes4(v[0].x, v[2].x, v[4].x, v[6].x); o[0] = bytes4(v[1].x, v[3].x, v[5].x, v[7].x);
    e[1] = bytes4(v[0].y, v[2].y, v[4].y, v[6].y); o[1] = bytes4(v[1].y, v[3].y, v[5].y, v[7].y);
    e[2] = bytes4(v[0].z, v[2].z, v[4].z, v[6].z); o[2] = bytes4(v[1].z, v[3].z, v[5].z, v[7].z);
    e[3] = bytes4(v[0].w, v[2].w, v[4].w, v[6].w); o[3] = bytes4(v[1].w, v[3].w, v[5].w, v[7].w);
}
__device__ __forceinline__ void pk_write(u64* p, const uint32_t (&e)[4], const uint32_t (&o)[4], uint32_t tag) {
    uint32_t w[4];
#pragma unroll
    for (int c = 0; c < 4; c++)
        asm("lop3.b32 %0, %1, %2, 0x0f0f0f0f, 0xe4;" : "=r"(w[c]) : "r"(e[c]), "r"(o[c] << 4));
    ll_store2(p, w[0], w[1], tag);
    ll_store2((u64*)((uint64_t)p ^ 320), w[2], w[3], tag);
}

__device__ __forceinline__ void tile0_of(int c, int& fp, int& m0) {
    if (c < 18) { fp = c >= 9; m0 = min((c - 9 * fp) * N0, kM - N0); }
    else { fp = 2 + ((c - 18) >> 3); m0 = ((c - 18) & 7) * N0; }
}
__device__ __forceinline__ void tile1_of(int c, int& fp, int& m0) {
    if (c < 6) { fp = 2 + c; m0 = kM - N1; }
    else { fp = 8 + (c - 6) / 10; m0 = min(((c - 6) % 10) * N1, kM - N1); }
}

__device__ __forceinline__ void ll_fetch(u64 (&c)[4], const char* p) {
    asm volatile("ld.relaxed.gpu.global.b64 %0, [%4];\nld.relaxed.gpu.global.b64 %1, [%4 + 128];\n"
                 "ld.relaxed.gpu.global.b64 %2, [%4 + 512];\nld.relaxed.gpu.global.b64 %3, [%4 + 640];"
                 : "=l"(c[0]), "=l"(c[1]), "=l"(c[2]), "=l"(c[3]) : "l"(p) : "memory");
}
__device__ __forceinline__ void ll_copy(uint32_t dst, const char* src, uint32_t bar) {
    asm volatile("{\n.reg .pred p;\nelect.sync _|p, 0xffffffff;\n"
                 "@p cp.async.bulk.shared::cluster.global.mbarrier::complete_tx::bytes [%0], [%1], 1024, [%2];\n}\n"
                 ::"r"(dst), "l"(src), "r"(bar) : "memory");
}
__device__ __forceinline__ void ll_read(u64 (&c)[4], uint32_t a) {
    asm volatile("ld.volatile.shared.b64 %0, [%4];\nld.volatile.shared.b64 %1, [%4 + 128];\n"
                 "ld.volatile.shared.b64 %2, [%4 + 512];\nld.volatile.shared.b64 %3, [%4 + 640];"
                 : "=l"(c[0]), "=l"(c[1]), "=l"(c[2]), "=l"(c[3]) : "r"(a) : "memory");
}
template <int NS>
__device__ __forceinline__ void ll_check(u64 (&c)[4], uint32_t a, const char* p, uint32_t tag) {
    asm volatile(
        "{\n.reg .pred p, q;\n.reg .b32 l, h0, h1, h2, h3, x, i, o;\n.reg .b64 g;\n"
        "mov.u32 i, 0;\n"
        "L_%=:\n"
        "mov.b64 {l, h0}, %0;\nmov.b64 {l, h1}, %1;\nmov.b64 {l, h2}, %2;\nmov.b64 {l, h3}, %3;\n"
        "lop3.b32 x, %6, h0, h1, 0x7e;\n"
        "lop3.b32 x, x, %6, h2, 0xf6;\n"
        "lop3.b32 x, x, %6, h3, 0xf6;\n"
        "setp.ne.u32 p, x, 0;\n"
        "vote.sync.any.pred p, p, 0xffffffff;\n"
        "@!p bra D_%=;\n"
        "and.b32 o, %4, 1023;\ncvt.u64.u32 g, o;\nadd.u64 g, g, %5;\n"
        "sub.u32 o, %6, 16;\n"
        "setp.eq.u32 q, h0, o;\nsetp.eq.or.u32 q, h1, o, q;\nsetp.eq.or.u32 q, h2, o, q;\nsetp.eq.or.u32 q, h3, o, q;\n"
        "setp.ge.or.u32 q, i, %8, q;\n"
        "vote.sync.any.pred q, q, 0xffffffff;\n"
        "@!q ld.volatile.shared.b64 %0, [%4];\n@!q ld.volatile.shared.b64 %1, [%4 + 128];\n"
        "@!q ld.volatile.shared.b64 %2, [%4 + 512];\n@!q ld.volatile.shared.b64 %3, [%4 + 640];\n"
        "@q ld.relaxed.gpu.global.b64 %0, [g];\n@q ld.relaxed.gpu.global.b64 %1, [g + 128];\n"
        "@q ld.relaxed.gpu.global.b64 %2, [g + 512];\n@q ld.relaxed.gpu.global.b64 %3, [g + 640];\n"
        "add.u32 i, i, 1;\n"
        "setp.lt.u32 p, i, %7;\n"
        "@p bra L_%=;\n"
        "D_%=:\n}\n"
        : "+l"(c[0]), "+l"(c[1]), "+l"(c[2]), "+l"(c[3])
        : "r"(a), "l"(p), "r"(tag), "n"(SPIN_LIMIT >> 4), "n"(NS) : "memory");
}
__device__ __forceinline__ void ll_poll(u64 (&c)[4], const char* p, uint32_t tag) {
    unsigned it = 0;
    while (__any_sync(0xffffffffu, (((uint32_t)(c[0] >> 32) ^ tag) | ((uint32_t)(c[1] >> 32) ^ tag) |
                                    ((uint32_t)(c[2] >> 32) ^ tag) | ((uint32_t)(c[3] >> 32) ^ tag)) != 0) &&
           ++it < (SPIN_LIMIT >> 4))
        ll_fetch(c, p);
}
__device__ __forceinline__ void decode_alu(uint32_t& r0, uint32_t& r1, uint32_t& r2, uint32_t& r3, uint32_t w,
                                           const uint32_t (&lt)[8]) {
    const uint32_t s0 = w & 0x77777777u, s1 = s0 >> 16, w4 = w * 16;
    const uint32_t m0 = prmt(w4, w, 0xd9c8), m1 = prmt(w4, w, 0xfbea);
    const uint32_t l0 = (prmt(lt[0], lt[1], s0) & ~m0) | (prmt(lt[2], lt[3], s0) & m0);
    const uint32_t h0 = (prmt(lt[4], lt[5], s0) & ~m0) | (prmt(lt[6], lt[7], s0) & m0);
    const uint32_t l1 = (prmt(lt[0], lt[1], s1) & ~m1) | (prmt(lt[2], lt[3], s1) & m1);
    const uint32_t h1 = (prmt(lt[4], lt[5], s1) & ~m1) | (prmt(lt[6], lt[7], s1) & m1);
    r0 = prmt(l0, h0, 0x5140); r1 = prmt(l0, h0, 0x7362);
    r2 = prmt(l1, h1, 0x5140); r3 = prmt(l1, h1, 0x7362);
}
__device__ __forceinline__ void decode(uint32_t (&a)[16], const u64 (&c)[4], uint32_t tblv, const uint32_t (&lt)[8]) {
#pragma unroll
    for (int i = 0; i < 4; i++) {
        const int b = (i >> 1) * 8 + (i & 1);
        if (i < 4 - NALU) {
#pragma unroll
            for (int j = 0; j < 4; j++) a[b + 2 * j] = lds32(dp4a_u((uint32_t)c[i], 0x80u << (8 * j), tblv));
        } else {
            decode_alu(a[b], a[b + 2], a[b + 4], a[b + 6], (uint32_t)c[i], lt);
        }
    }
}

__host__ __device__ constexpr int slot_of(int j) {
    return j < 16 ? j % 6 : j < 18 ? j - 16 : (0x410532 >> (4 * ((j - 18) % 6))) & 7;
}
__host__ __device__ constexpr int loads_before(int j) {
    int n = 0;
    for (int i = 0; i < j; i++) n += slot_of(i) == slot_of(j);
    return n;
}
__host__ __device__ constexpr int uses_before(int j) {
    return loads_before(j) + (j >= 16 && slot_of(j) >= 4);
}
__host__ __device__ constexpr uint64_t prod_tbl(int j0) {
    uint64_t t = 0;
    for (int j = j0; j < j0 + 16; j++) t |= (uint64_t)(slot_of(j) | (((uses_before(j) + 1) & 1) << 3)) << (4 * (j - j0));
    return t;
}
__host__ __device__ constexpr int dec_upto(int j) {
    return j < 14 ? j + 1 + (j >= RAMP1) + (j >= RAMP1B) : j + 1 + (j >= RAMP2A) + (j >= RAMP2);
}
__host__ __device__ constexpr bool ramp_first(int d) {
    for (int j = 1; j < NSL - 4; j++)
        if ((j < 14 || j >= 18) && dec_upto(j) == dec_upto(j - 1) + 2 && d == dec_upto(j) - 1) return true;
    return false;
}
__host__ __device__ constexpr bool read_early(int d) {
    return d > RLATE && d < NSL && !ramp_first(d - 2) && !ramp_first(d - 3) && d != 18 && (RAMP2A >= 18 || (d != 20 && d != 21));
}
__host__ __device__ constexpr bool get_early(int d) { return ramp_first(d); }

__device__ __forceinline__ void fence_a(uint32_t (&a)[16]) {
#pragma unroll
    for (int i = 0; i < 16; i++) asm volatile("" : "+r"(a[i])::"memory");
}
template <int J, int N, int COL>
__device__ __forceinline__ void mma_slice(float (&acc)[N0 / 2], uint32_t (&a)[4][16]) {
    constexpr int off = (slot_of(J) * SLOT_BYTES + COL * 128) / 16, b = J % 4;
    constexpr uint64_t d0 = make_desc(SMEM_BASE);
    WG<N, COL / 2, (J % KSTEPS) != 0, N0 / 2>::mma(acc, a[b][0], a[b][1], a[b][2], a[b][3], d0 + off);
    WG<N, COL / 2, true, N0 / 2>::mma(acc, a[b][4], a[b][5], a[b][6], a[b][7], d0 + (off + 2));
    WG<N, COL / 2, true, N0 / 2>::mma(acc, a[b][8], a[b][9], a[b][10], a[b][11], d0 + (off + 4));
    WG<N, COL / 2, true, N0 / 2>::mma(acc, a[b][12], a[b][13], a[b][14], a[b][15], d0 + (off + 6));
}
template <int N> __device__ __forceinline__ void rename_acc(float (&acc)[N0 / 2]) {
#pragma unroll
    for (int i = 0; i < N / 2; i++) asm volatile("mov.b32 %0, %1;" : "=f"(acc[i]) : "f"(acc[i]) : "memory");
}
template <int N, int COL, bool FENCE>
__device__ __forceinline__ void stage_out(float (&acc)[N0 / 2], uint32_t sa, float s0, float s1) {
#pragma unroll
    for (int i = COL / 2; i < (COL + N) / 2; i++) asm volatile("" : "+f"(acc[i])::"memory");
#pragma unroll
    for (int j = COL / 8; j + 1 < (COL + N) / 8; j += 2) {
        const uint32_t r0 = pack_bf16x2(acc[4 * j + 0] * s0, acc[4 * j + 1] * s0);
        const uint32_t r1 = pack_bf16x2(acc[4 * j + 2] * s1, acc[4 * j + 3] * s1);
        const uint32_t r2 = pack_bf16x2(acc[4 * j + 4] * s0, acc[4 * j + 5] * s0);
        const uint32_t r3 = pack_bf16x2(acc[4 * j + 6] * s1, acc[4 * j + 7] * s1);
        asm volatile("stmatrix.sync.aligned.m8n8.x4.trans.shared.b16 [%0], {%1, %2, %3, %4};"
                     ::"r"(sa + j * 1024), "r"(r0), "r"(r1), "r"(r2), "r"(r3) : "memory");
    }
    if constexpr ((N / 8) & 1) {
        constexpr int j = (COL + N) / 8 - 1;
        const uint32_t r0 = pack_bf16x2(acc[4 * j + 0] * s0, acc[4 * j + 1] * s0);
        const uint32_t r1 = pack_bf16x2(acc[4 * j + 2] * s1, acc[4 * j + 3] * s1);
        asm volatile("stmatrix.sync.aligned.m8n8.x2.trans.shared.b16 [%0], {%1, %2};"
                     ::"r"(sa + j * 1024), "r"(r0), "r"(r1) : "memory");
    }
    if constexpr (FENCE) asm volatile("fence.proxy.async.shared::cta;" ::: "memory");
}

struct Maps { CUtensorMap m[8]; };

__global__ void __cluster_dims__(2, 1, 1) __launch_bounds__(NUM_THREADS, 1)
nf4_gemm_kernel(const int* __restrict__ qw, u64* __restrict__ ll, unsigned* __restrict__ epoch,
                const __nv_bfloat16* __restrict__ lut, const __nv_bfloat16* __restrict__ scales,
                const __grid_constant__ Maps tm) {
    extern __shared__ __align__(1024) uint8_t smem_raw[];
    const uint32_t t_start = clock32();
    const int lane = threadIdx.x & 31;
    uint4 v[8];
    if (threadIdx.x < TOPN) {
        const uint32_t up = (threadIdx.x >> 7) * NUM_CTAS + blockIdx.x;
        asm volatile("prefetch.global.L2 [%0];" ::"l"(add_off(qw, unit_src(up / W1_FG, up % W1_FG) + lane * (kN * 4) + ((threadIdx.x >> 5) & 3) * 32)) : "memory");
    }
    const int warp = __shfl_sync(0xffffffffu, threadIdx.x >> 5, 0);
    const uint32_t sb = smem_u32(smem_raw);
    const uint32_t bar_full = sb + BAR_OFF;
    const uint32_t bar_empty = bar_full + NSLOTS * 8;
    const uint32_t bar_tbl = bar_empty + NSLOTS * 8;
    const uint32_t bar_code = bar_tbl + 8;
    const uint32_t bar_stg = bar_code + 8;
    const int crank = blockIdx.x & 1, cluster = blockIdx.x >> 1;

    if (warp != 8) cluster_arrive_relaxed();
    if (warp < 8) {
        const int wg = warp >> 2;
        const uint32_t u0 = (NAUX0 + warp) * NUM_CTAS + blockIdx.x, q0 = u0 / W1_FG, fg0 = u0 % W1_FG;
        TSW(640 + warp);
        const uint32_t tag = ld_ca_u32(epoch + lane);
        const uint32_t lv = ldg_u16(reinterpret_cast<const unsigned short*>(lut) + (lane & 15));
        int fp0, fp1, mm;
        tile0_of(cluster, fp0, mm);
        tile1_of(cluster, fp1, mm);
        const int ft0 = fp0 * 2 + crank, ft1 = fp1 * 2 + crank;
        const unsigned short* sc16 = reinterpret_cast<const unsigned short*>(scales) + warp * 16 + (lane >> 2);
        uint32_t sc0 = ldg_u16(sc16 + ft0 * FT), sc0h = ldg_u16(sc16 + ft0 * FT + 8);
        uint32_t sc1 = ldg_u16(sc16 + ft1 * FT), sc1h = ldg_u16(sc16 + ft1 * FT + 8);
        if (PFN > 0 && warp < PFN) {
            const uint32_t up = (PFR + warp) * NUM_CTAS + blockIdx.x;
            const int* pp = add_off(qw, unit_src(up / W1_FG, up % W1_FG) + lane * (kN * 4));
            delay_until(t_start, PF0 + warp * PFD);
            asm volatile("prefetch.global.L2 [%0];\nprefetch.global.L2 [%0 + 32];\nprefetch.global.L2 [%0 + 64];\nprefetch.global.L2 [%0 + 96];" ::"l"(pp) : "memory");
        }
        if (NBOR > 0 && warp < NBOR) {
            delay_until(t_start, round_time(NAUX0 + warp));
            load_unit(v, add_off(qw, unit_src(q0, fg0) + lane_src(lane)));
            uint32_t e[4], o[4];
            pk_gather(e, o, v);
            pk_write(add_off(ll, unit_dst(q0, fg0) + lane_dst(lane)), e, o, tag + (q0 >> 1));
            TSW(700 + NAUX0 + warp);
        } else if (wg == 1) {
            uint32_t lo[4];
#pragma unroll
            for (int i = 0; i < 4; i++) lo[i] = __shfl_sync(0xffffffffu, lv, 4 * i + (lane >> 3));
#pragma unroll 1
            for (int h = (warp & 3) * 4; h < (warp & 3) * 4 + 4; h++) {
                const uint32_t hi = __shfl_sync(0xffffffffu, lv, h) << 16;
#pragma unroll
                for (int i = 0; i < 4; i++)
                    asm volatile("st.shared.v4.u32 [%0], {%1, %1, %1, %1};"
                                 ::"r"(sb + TBL_OFF + h * 2048 + i * 512 + lane * 16), "r"(lo[i] | hi) : "memory");
            }
        }
        asm volatile("setmaxnreg.inc.sync.aligned.u32 %0;" ::"n"(CREGS));
        cluster_wait();
        if (wg == 1) mbar_arrive(bar_tbl);
        TS(132);
        sc0 |= sc0h << 16;
        sc1 |= sc1h << 16;
        const char* ll0 = keep(reinterpret_cast<const char*>(ll) + (ft0 * (KSTEPS * 8192) + warp * 1024 + lane), 0);
        const char* ll1 = keep(reinterpret_cast<const char*>(ll) + (ft1 * (KSTEPS * 8192) + warp * 1024 + lane), 0);
        const uint32_t cbuf = sb + RAW_OFF + warp * 1024;
        const uint32_t tblv = keep(sb + TBL_OFF + lane * 4, lane);
        const uint32_t cempty = keep(lane < 2 ? mapa(bar_empty, lane) : 0, lane);
        const uint32_t sa0 = keep(sb + (((lane >> 4) * 8 + (lane & 7)) * 128) +
                                  ((((warp & 3) * 2 + ((lane >> 3) & 1)) ^ (lane & 7)) << 4), lane);
        uint32_t lt[8];
        {
            const uint32_t p01 = __shfl_sync(0xffffffffu, lv, 4 * lane) | (__shfl_sync(0xffffffffu, lv, 4 * lane + 1) << 16);
            const uint32_t p23 = __shfl_sync(0xffffffffu, lv, 4 * lane + 2) | (__shfl_sync(0xffffffffu, lv, 4 * lane + 3) << 16);
            const uint32_t pl = prmt(p01, p23, lane & 4 ? 0x7531 : 0x6420);
#pragma unroll
            for (int i = 0; i < 8; i++) lt[i] = __shfl_sync(0xffffffffu, pl, i & 1 ? i : i + (lane & 24));
        }
        uint32_t a[4][16];
        float acc[N0 / 2];

        auto src = [&](auto dc) {
            constexpr int D = decltype(dc)::value;
            return (D < KSTEPS ? ll0 : ll1) + (D % KSTEPS) * 8192;
        };
        u64 c[4];
        const uint32_t aw = keep(cbuf + lane_unit(lane), lane);
        auto fetch = [&](auto dc) {
            constexpr int D = decltype(dc)::value;
            if constexpr (D < NGATE) delay_until(t_start, gate_time(D));
            if constexpr (D < NSL) ll_copy(cbuf + (D & 1) * 8192, src(dc), bar_code);
        };
        auto read = [&](auto dc) {
            constexpr int D = decltype(dc)::value;
            ll_read(c, aw + (D & 1) * 8192);
        };
        auto get = [&](auto dc) {
            constexpr int D = decltype(dc)::value;
            if constexpr (D + 1 <= FLATE) fetch(IC<D + 1>{});
            if constexpr (!read_early(D)) read(dc);
            ll_check<NSPIN0>(c, aw + (D & 1) * 8192, src(dc), tag + D % KSTEPS);
            if constexpr (D + 2 >= NGATE) fetch(IC<D + 2>{});
        };
        auto dec = [&](auto dc) {
            constexpr int D = decltype(dc)::value;
            decode(a[D % 4], c, tblv, lt);
            if constexpr (D + 2 > FLATE && D + 2 < NGATE) fetch(IC<D + 2>{});
            if constexpr (read_early(D + 1)) read(IC<D + 1>{});
            if constexpr (get_early(D + 1)) get(IC<D + 1>{});
        };
        auto wait_full = [&](auto jc) {
            constexpr int J = decltype(jc)::value;
            mbar_wait(bar_full + slot_of(J) * 8, loads_before(J) & 1);
        };
        auto release = [&](auto jc) {
            constexpr int J = decltype(jc)::value;
            if constexpr (J < NSL - 4) mbar_arrive_pair(cempty + slot_of(J) * 8, cempty);
        };
        auto step = [&](auto jc) {
            constexpr int J = decltype(jc)::value, D = dec_upto(J - 1) + 1;
            fence_a(a[J % 4]);
            wgmma_fence();
            mma_slice<J, (J < KSTEPS ? N0 : N1), 0>(acc, a);
            wgmma_commit();
            TS(J);
            if constexpr (!get_early(D)) get(IC<D>{});
            constexpr bool WLATE = J < NEARLY || (J >= 18 && J < WL1);
            if constexpr (!WLATE) wait_full(IC<J + 1>{});
            wgmma_wait<1>();
            if constexpr (J != 0 && J != 18) release(IC<J - 1>{});
            dec(IC<D>{});
            if constexpr (dec_upto(J) > D) { get(IC<D + 1>{}); dec(IC<D + 1>{}); }
            if constexpr (WLATE) wait_full(IC<J + 1>{});
        };
        static_assert(FLATE >= 1 && FLATE < NGATE && RLATE >= FLATE && RLATE < RAMP1, "code schedule");
        static_assert(slot_of(10) == 4 && slot_of(11) == 5 && uses_before(10) == 1 && uses_before(11) == 1 &&
                      2 * E0 * 128 <= SLOT_BYTES + 1024 && 2 * E1 * 128 <= SLOT_BYTES, "staging slots");

        mbar_wait(bar_tbl, 0);
        TS(133);
        delay_until(t_start, gate_time(0));
        ll_fetch(c, src(IC<0>{}) + (aw & 1023));
        fetch(IC<1>{});
        ll_poll(c, src(IC<0>{}) + (aw & 1023), tag);
        TSW(850 + warp);
        dec(IC<0>{});
        TS(134);
        wait_full(IC<0>{});
        TS(137);
        static_for<0, 14>(step);
        {
            const float s0 = __uint_as_float(sc0 << 16), s1 = __uint_as_float(sc0 & 0xffff0000u);
            const uint32_t sa = sa0 + 5 * SLOT_BYTES + wg * (E0 * 128), sc = sa0 + 4 * SLOT_BYTES - E0 * 128 + wg * (E1 * 128);
            auto group = [&](auto jc, auto nc, auto cc) {
                fence_a(a[decltype(jc)::value % 4]);
                wgmma_fence();
                mma_slice<decltype(jc)::value, decltype(nc)::value, decltype(cc)::value>(acc, a);
                wgmma_commit();
            };
            static_assert(dec_upto(13) == 16 && dec_upto(17) == 19, "ILV");
            wait_full(IC<15>{});
            TS(140);
            wgmma_wait<0>();
            rename_acc<N0>(acc);
            group(IC<14>{}, IC<E0>{}, IC<0>{});
            release(IC<13>{});
            get(IC<17>{});
            mbar_wait(bar_empty + 5 * 8, 1);
            group(IC<15>{}, IC<E0>{}, IC<0>{});
            TS(14);
            dec(IC<17>{});
            TS(141);
            group(IC<14>{}, IC<E1>{}, IC<E0>{});
            TS(15);
            wgmma_wait<1>();
            stage_out<EI, 0, false>(acc, sa, s0, s1);
            group(IC<15>{}, IC<E1>{}, IC<E0>{});
            TS(142);
            wait_full(IC<16>{});
            wgmma_wait<1>();
            release(IC<14>{});
            TS(143);
            stage_out<E0 - EI, EI, true>(acc, sa, s0, s1);
            mbar_arrive(bar_stg + wg * 8);
            TS(144);
            group(IC<16>{}, IC<S0>{}, IC<0>{});
            wait_full(IC<17>{});
            wgmma_wait<1>();
            release(IC<15>{});
            TS(16);
            stage_out<EI, E0, false>(acc, sc, s0, s1);
            group(IC<17>{}, IC<S0>{}, IC<0>{});
            TS(128);
            stage_out<E1 - EI, E0 + EI, true>(acc, sc, s0, s1);
            mbar_arrive(bar_stg + 16 + wg * 8);
            TS(129);
            group(IC<16>{}, IC<S1>{}, IC<S0>{});
            get(IC<18>{}); dec(IC<18>{});
            group(IC<17>{}, IC<S1>{}, IC<S0>{});
            TS(17);
            get(IC<19>{});
            wait_full(IC<18>{});
            wgmma_wait<1>();
            release(IC<16>{});
            dec(IC<19>{});
            TS(145);
            wgmma_wait<0>();
            rename_acc<N1>(acc);
            release(IC<17>{});
            TS(146);
        }
        static_for<18, NSL - 4>(step);
        {
            constexpr int J0 = NSL - 4;
            const float s0 = __uint_as_float(sc1 << 16), s1 = __uint_as_float(sc1 & 0xffff0000u);
            const uint32_t sa = sa0 + (wg ? slot_of(27) : slot_of(26)) * SLOT_BYTES;
            wait_full(IC<J0 + 1>{}); wait_full(IC<J0 + 2>{});
            fence_a(a[0]); fence_a(a[1]); fence_a(a[2]);
            TS(160);
            wgmma_wait<0>();
            rename_acc<N1>(acc);
            wgmma_fence();
            mma_slice<J0, CA, 0>(acc, a);
            TS(J0);
            release(IC<J0 - 1>{});
            get(IC<NSL - 1>{}); dec(IC<NSL - 1>{});
            asm volatile("{\n.reg .pred p;\nelect.sync _|p, 0xffffffff;\n"
                         "@p mbarrier.arrive.expect_tx.shared::cta.b64 _, [%0], %1;\n}\n" ::"r"(bar_code), "n"((NSL - 1) * 1024) : "memory");
            wgmma_fence();
            mma_slice<J0 + 1, CA, 0>(acc, a);
            mma_slice<J0 + 2, CA, 0>(acc, a);
            wait_full(IC<NSL - 1>{});
            fence_a(a[3]);
            wgmma_fence();
            mma_slice<J0 + 3, CA, 0>(acc, a);
            wgmma_commit();
            static_for<1, 5>([&](auto cc) {
                constexpr int C = decltype(cc)::value;
                constexpr int N = C == 1 ? CA : C == 2 ? CB : CC, COL = C == 3 ? 2 * CA + CB : C * CA;
                constexpr int NP = C <= 2 ? CA : C == 3 ? CB : CC, COLP = C == 4 ? 2 * CA + CB : (C - 1) * CA;
                if constexpr (C < 4) {
                    wgmma_fence();
                    mma_slice<J0, N, COL>(acc, a);
                    wgmma_commit();
                    if constexpr (C == 1) mbar_wait(bar_empty + (wg ? slot_of(27) : slot_of(26)) * 8, (wg ? uses_before(27) : uses_before(26)) & 1);
                    wgmma_wait<1>();
                } else {
                    wgmma_wait<0>();
                    TS(130);
                }
                TS(160 + C * 4);
                stage_out<NP, COLP, true>(acc, sa, s0, s1);
                bar_arrive_id(5 + C + wg * 4, 160);
                TS(160 + C * 4 + 1);
                if constexpr (C < 4) {
                    wgmma_fence();
                    static_for<J0 + 1, NSL>([&](auto jc) { mma_slice<decltype(jc)::value, N, COL>(acc, a); });
                    wgmma_commit();
                    TS(J0 + C);
                }
            });
            TS(131);
        }
    } else {
      if (warp >= 9) {
        {
            const int pw = warp - 9;
            int rr = pw < NAUX0 ? pw : NAUX0 + NBOR + pw;
            int u = rr * NUM_CTAS + blockIdx.x;
            uint32_t q = u / W1_FG, fg = u % W1_FG;
            const int* qwk = keep(add_off(qw, lane_src(lane)), lane);
            u64* llk = keep(add_off(ll, lane_dst(lane)), lane);
            const unsigned* ep = epoch + lane;
            asm volatile("setmaxnreg.dec.sync.aligned.u32 %0;" ::"n"(504 - 2 * CREGS));
            const uint32_t tag = ld_ca_u32(ep);
            if (pw > 0) delay_until(t_start, round_time(rr));
            load_unit(v, add_off(qwk, unit_src(q, fg)));
            TSA(648 + pw);
            constexpr int nun = NUM_UNITS;
            if (pw < NAUX0) u += (NAUX0 + NBOR - NUM_AUX) * NUM_CTAS;
#pragma unroll 1
            for (;;) {
                u64* dst = add_off(llk, unit_dst(q, fg));
                u64* dst2 = (u64*)((uint64_t)dst ^ 320);
                const uint32_t sl = q >> 1;
                u += u < (RSTOP - NUM_AUX) * NUM_CTAS ? NUM_AUX * NUM_CTAS : pw == 2 ? NUM_UNITS : u < RSTOP * NUM_CTAS ? NUM_AUX * NUM_CTAS : 2 * NUM_CTAS;
                unit_pos(min(u, NUM_UNITS - 1), q, fg);
                const int* p = add_off(qwk, unit_src(q, fg));
                asm volatile("{\n.reg .pred p;\nL_%=:\nsetp.eq.u64 p, %0, 0;\nsetp.eq.or.u64 p, %1, 0, p;\nsetp.eq.or.u64 p, %2, 0, p;\n@p bra L_%=;\n}\n"
                             ::"l"(p), "l"(dst), "l"(dst2) : "memory");
                uint32_t e[4], o[4], w[4];
                pk_gather(e, o, v);
                TSA(700 + rr); rr += rr < NAUX0 ? NAUX0 + NBOR : rr < RSTOP ? NUM_AUX : 2;
#pragma unroll
                for (int k = 0; k < 4; k++) asm("lop3.b32 %0, %1, %2, 0x0f0f0f0f, 0xe4;" : "=r"(w[k]) : "r"(e[k]), "r"(o[k] << 4));
                ll_store2(dst, w[0], w[1], tag + sl);
                ll_store2(dst2, w[2], w[3], tag + sl);
                if (u >= nun) break;
                if (DLY_2 > 0 && u < 6 * NUM_CTAS) delay_until(t_start, DLY_2 + pw * DLY_2S);
                load_unit(v, p);
            }
        }
        const CUtensorMap* maps = keep(&tm.m[3] + lane, 0);
        named_bar_arrive<4, 128>();
        cluster_wait();
        int fp, m0;
        if (warp == 11) {
            tile0_of(cluster, fp, m0);
            const int f0 = (fp * 2 + crank) * FT;
#pragma unroll 1
            for (int ch = 0; ch < 2; ch++) {
                const uint32_t src = sb + (5 - ch) * SLOT_BYTES;
                const int rows = ch ? E1 : E0, step = ch ? BX1 : BX0;
                int h = 0;
#pragma unroll 1
                for (unsigned it = 0; it < 16 * SPIN_LIMIT && !mbar_test(bar_stg + ch * 16 + h * 8, 0); it++) { h ^= 1; __nanosleep(20); }
#pragma unroll 1
                for (int k = 0; k < 2; k++, h ^= 1) {
                    mbar_wait(bar_stg + ch * 16 + h * 8, 0);
#pragma unroll 1
                    for (int r = 0; r < rows; r += step) {
                        asm volatile("{\n.reg .pred p;\nelect.sync _|p, 0xffffffff;\n"
                                     "@p cp.async.bulk.tensor.2d.global.shared::cta.bulk_group [%0, {%2, %3}], [%1];\n"
                                     "cp.async.bulk.commit_group;\ncp.async.bulk.wait_group.read %4;\n}\n"
                                     ::"l"(maps + 3 + ch), "r"(src + (h * rows + r) * 128), "r"(f0 + h * 64), "r"(m0 + ch * E0 + r),
                                     "n"(STQ) : "memory");
                    }
                }
                asm volatile("cp.async.bulk.wait_group.read 0;" ::: "memory");
                __syncwarp();
                if (lane < 2) mbar_arrive_cluster_n(mapa(bar_empty + (5 - ch) * 8, lane), 8);
                TSG(604 + ch * 2);
            }
        } else {
            const int wg = warp - 9;
            tile1_of(cluster, fp, m0);
            const int f0 = (fp * 2 + crank) * FT + wg * 64;
            const uint32_t src = sb + (wg ? slot_of(27) : slot_of(26)) * SLOT_BYTES;
#pragma unroll 1
            for (int ch = 0; ch < 4; ch++) {
                const int r0 = ch < 3 ? ch * CA : 2 * CA + CB;
                const CUtensorMap* map = maps + max(ch - 1, 0);
                bar_sync_id(6 + wg * 4 + ch, 160);
                if (lane == 0) {
                    tma_store_2d(map, src + r0 * 128, f0, m0 + r0);
                    asm volatile("cp.async.bulk.commit_group;" ::: "memory");
                }
            }
            if (lane == 0) asm volatile("cp.async.bulk.wait_group.read 0;" ::: "memory");
            __syncwarp();
            TSG(600 + wg * 2);
        }
      } else {
        asm volatile("setmaxnreg.dec.sync.aligned.u32 %0;" ::"n"(504 - 2 * CREGS));
        if ((sb & 0xFFFFFF) != SMEM_BASE) __trap();
        if (lane == 0) {
            for (int s = 0; s < NSLOTS; s++) {
                mbar_init(bar_full + s * 8, 1);
                mbar_init(bar_empty + s * 8, 16);
            }
            mbar_init(bar_tbl, 128);
            mbar_init(bar_code, 8);
            for (int i = 0; i < 4; i++) mbar_init(bar_stg + i * 8, 128);
            asm volatile("fence.mbarrier_init.release.cluster;" ::: "memory");
        }
        __syncwarp();
        cluster_arrive_relaxed();
        const CUtensorMap* maps = keep(&tm.m[0] + lane, 0);
        unsigned* epk = keep(epoch + lane, 0);
        if (lane == 0) prefetch_map(maps + crank);
        TSG(512);
        int fp, m0;
        tile0_of(cluster, fp, m0);
        cluster_wait();
#pragma unroll 1
        for (int t = 0; t < 2; t++) {
            const int lo = t == 0 ? 120 : 104, row = m0 + crank * lo;
            const CUtensorMap* map = maps + (t ? 2 : crank);
            const uint32_t bytes = (t ? N1 : N0) * 128, dst = sb + crank * lo * 128;
            uint64_t tbl = t ? prod_tbl(16) : prod_tbl(0);
#pragma unroll 1
            for (int ks = 0; ks < KSTEPS; ks++, tbl >>= 4) {
                const uint32_t slot = (uint32_t)tbl & 7;
                if (t == 0 && ks > 0 && ks < NSLOTS) delay_until(t_start, DLY_X0 + ks * DLY_XS);
                mbar_wait(bar_empty + slot * 8, ((uint32_t)tbl >> 3) & 1);
                asm volatile(
                    "{\n.reg .pred p;\nelect.sync _|p, 0xffffffff;\n"
                    "@p mbarrier.arrive.expect_tx.shared::cta.b64 _, [%2], %5;\n"
                    "@p cp.async.bulk.tensor.2d.shared::cluster.global.mbarrier::complete_tx::bytes.multicast::cluster"
                    " [%0], [%1, {%3, %4}], [%2], %6;\n}\n"
                    ::"r"(dst + slot * SLOT_BYTES), "l"(map), "r"(bar_full + slot * 8), "r"(ks * BK), "r"(row), "r"(bytes),
                    "h"((uint16_t)3) : "memory");
                TSG(514 + (t * 18 + ks) * 2);
            }
            tile1_of(cluster, fp, m0);
            if (t == 0 && lane >= 2 && lane < 8) prefetch_map(maps + lane);
        }
        named_bar_sync<4, 128>();
        const uint32_t tag = ld_ca_u32(epk + lane);
        unsigned old = 0;
        if (lane == 0) old = atomicAdd(epk + 32, tag != 0 ? 1u : 0u);
        if (__shfl_sync(0xffffffffu, old, 0) == NUM_CTAS - 1) {
            if (lane == 0) epk[32] = 0;
            epk[lane] = tag == 0xfffffff0u ? 16 : tag + 16;
        }
        mbar_wait(bar_code, 0);
      }
    }
}

__global__ void generic_kernel(const __nv_bfloat16* __restrict__ x, const int* __restrict__ qw,
                               const __nv_bfloat16* __restrict__ lut, const __nv_bfloat16* __restrict__ scales,
                               __nv_bfloat16* __restrict__ out, int M, int N, int K, int G) {
    const int n = blockIdx.x * blockDim.x + threadIdx.x;
    const int m = blockIdx.y;
    if (n >= N) return;
    float acc = 0.f;
    for (int k = 0; k < K; k++) {
        const float l = __bfloat162float(lut[qw[(size_t)k * N + n] & 15]);
        const float s = __bfloat162float(scales[(size_t)(k / G) * N + n]);
        const float w = __bfloat162float(__float2bfloat16_rn(l * s));
        acc += __bfloat162float(x[(size_t)m * K + k]) * w;
    }
    out[(size_t)m * N + n] = __float2bfloat16_rn(acc);
}

typedef CUresult (*PFN_encodeTiled)(CUtensorMap*, CUtensorMapDataType, cuuint32_t, void*, const cuuint64_t*,
                                    const cuuint64_t*, const cuuint32_t*, const cuuint32_t*, CUtensorMapInterleave,
                                    CUtensorMapSwizzle, CUtensorMapL2promotion, CUtensorMapFloatOOBfill);

bool make_map_2d(PFN_encodeTiled fn, CUtensorMap* map, void* base, uint64_t inner, uint64_t outer, uint32_t box_inner,
                 uint32_t box_outer) {
    cuuint64_t dims[2] = {inner, outer};
    cuuint64_t strides[1] = {inner * 2};
    cuuint32_t box[2] = {box_inner, box_outer};
    cuuint32_t estr[2] = {1, 1};
    return fn(map, CU_TENSOR_MAP_DATA_TYPE_BFLOAT16, 2, base, dims, strides, box, estr, CU_TENSOR_MAP_INTERLEAVE_NONE,
              CU_TENSOR_MAP_SWIZZLE_128B, XPROMO,
              CU_TENSOR_MAP_FLOAT_OOB_FILL_NONE) == CUDA_SUCCESS;
}

}

extern "C" void kernel_launch(void* const* d_in, const int* in_sizes, int n_in, void* d_out, int out_size) {
    const __nv_bfloat16* x = (const __nv_bfloat16*)d_in[0];
    const int* qw = (const int*)d_in[1];
    const __nv_bfloat16* lut = (const __nv_bfloat16*)d_in[2];
    const __nv_bfloat16* scales = (const __nv_bfloat16*)d_in[3];
    __nv_bfloat16* out = (__nv_bfloat16*)d_out;

    const double Kd = sqrt((double)in_sizes[0] * (double)in_sizes[1] / (double)out_size);
    const int K = (int)(Kd + 0.5);
    const int M = in_sizes[0] / K, N = in_sizes[1] / K;
    const int ng = in_sizes[3] / N;
    const int G = K / ng;

    bool fast = (M == kM && N == kN && K == kK && ng == 1 && in_sizes[2] >= 16);
    PFN_encodeTiled enc = nullptr;
    Maps tm;
    void *ll = nullptr, *epoch = nullptr;
    if (fast) {
        cudaDriverEntryPointQueryResult qres;
        void* fp = nullptr;
        if (cudaGetDriverEntryPoint("cuTensorMapEncodeTiled", &fp, cudaEnableDefault, &qres) != cudaSuccess || !fp) fast = false;
        enc = (PFN_encodeTiled)fp;
    }
    static_assert(2 * CA + CB + CC == N1 && S0 <= E0, "chunks");
    if (fast) {
        fast = make_map_2d(enc, &tm.m[0], (void*)x, kK, kM, BK, 120) &&
               make_map_2d(enc, &tm.m[1], (void*)x, kK, kM, BK, 112) &&
               make_map_2d(enc, &tm.m[2], (void*)x, kK, kM, BK, 104) &&
               make_map_2d(enc, &tm.m[3], (void*)out, kN, kM, 64, CA) &&
               make_map_2d(enc, &tm.m[4], (void*)out, kN, kM, 64, CB) &&
               make_map_2d(enc, &tm.m[5], (void*)out, kN, kM, 64, CC) &&
               make_map_2d(enc, &tm.m[6], (void*)out, kN, kM, 64, BX0) &&
               make_map_2d(enc, &tm.m[7], (void*)out, kN, kM, 64, BX1) &&
               cudaGetSymbolAddress(&ll, g_ll) == cudaSuccess && cudaGetSymbolAddress(&epoch, g_epoch) == cudaSuccess;
    }
    cudaLaunchConfig_t cfg = {};
    cfg.gridDim = dim3(NUM_CTAS);
    cfg.blockDim = dim3(NUM_THREADS);
    cfg.dynamicSmemBytes = SMEM_TOTAL;
    cfg.stream = cudaStreamPerThread;
    if (fast) {
        int nclusters = 0;
        fast = cudaFuncSetAttribute(nf4_gemm_kernel, cudaFuncAttributeMaxDynamicSharedMemorySize, SMEM_TOTAL) == cudaSuccess &&
               cudaOccupancyMaxActiveClusters(&nclusters, nf4_gemm_kernel, &cfg) == cudaSuccess &&
               nclusters >= NUM_CTAS / 2;
    }
    if (!fast) {
        generic_kernel<<<dim3((N + 127) / 128, M), 128>>>(x, qw, lut, scales, out, M, N, K, G);
        return;
    }
    cudaLaunchKernelEx(&cfg, nf4_gemm_kernel, qw, (u64*)ll, (unsigned*)epoch, lut, scales, tm);
}
```

```cpp
#include <cuda_runtime.h>
#include <cuda_bf16.h>
#include <cuda.h>
#include <stdint.h>
#include <stdio.h>
#include <math.h>

namespace {

constexpr int kM = 2048, kN = 3584, kK = 1024;
constexpr int FT = 128;
constexpr int N0 = 232, N1 = 208;
constexpr int BK = 64, KSTEPS = kK / BK;
constexpr int NSL = 2 * KSTEPS;
constexpr int NSLOTS = 7;
constexpr int SLOT_BYTES = N0 * 128;
constexpr int SLOT_OFF = 3 * N1 * 128 - 2 * SLOT_BYTES;
#define TBLC 16
constexpr int TBL_OFF = SLOT_OFF + 6 * SLOT_BYTES;
constexpr int COD_OFF = TBL_OFF + TBLC * 1024;
constexpr int BAR_OFF = COD_OFF + 2 * 8192;
constexpr int SMEM_TOTAL = BAR_OFF + 256;
constexpr int NUM_THREADS = 384;
constexpr int NUM_CTAS = 132;
constexpr int NUM_AUX = 3;
constexpr int CREGS = 224;
constexpr int NQ = kK / 32, NUM_UNITS = NQ * (kN / 32);
constexpr int W1_FG = 64, W2_FG = kN / 32 - W1_FG;
#define DLY_R0 200
#define DLY_R 400
#define DLY_X0 1000
#define DLY_XS 900
#define DLY_POLL 2600
#define DLY_P1 3200
#define DLY_PS 700
#define NGATE 8
#define FLATE 3
#define RLATE 4
#define NEARLY 4
#define RAMP1 8
#define RAMP2 12
#define RAMP3 24
#define NSPIN 24
#define NALU 2
#define RSTOP 18
#define BX0 24
#define BX1 16
#define EI 64
constexpr int E0 = 120, E1 = N0 - E0, S0 = 112, S1 = N1 - S0, CA = 64, CB = 48, CC = 32;
constexpr unsigned SPIN_LIMIT = 1u << 20;

__device__ __align__(1024) unsigned long long g_ll[(size_t)(kN / FT) * NQ * FT * 4];
__device__ __align__(256) unsigned int g_epoch[64] = {16, 16, 16, 16, 16, 16, 16, 16, 16, 16, 16, 16, 16, 16, 16, 16,
                                                      16, 16, 16, 16, 16, 16, 16, 16, 16, 16, 16, 16, 16, 16, 16, 16};

#define TS(idx) do {} while (0)
#define TSW(idx) do {} while (0)
#define TSG(idx) do {} while (0)

template <int I> struct IC { static constexpr int value = I; };
template <int B, int E, class F> __device__ __forceinline__ void static_for(F&& f) {
    if constexpr (B < E) { f(IC<B>{}); static_for<B + 1, E>(f); }
}

__device__ __forceinline__ uint32_t smem_u32(const void* p) { return (uint32_t)__cvta_generic_to_shared(p); }
__device__ __forceinline__ uint32_t keep(uint32_t v, int lane) {
    asm volatile("shfl.sync.idx.b32 %0, %0, %1, 0x1f, 0xffffffff;" : "+r"(v) : "r"(lane));
    return v;
}
template <class T> __device__ __forceinline__ T* keep(T* p, int lane) {
    const uint64_t v = (uint64_t)p;
    return (T*)(((uint64_t)keep((uint32_t)(v >> 32), lane) << 32) | keep((uint32_t)v, lane));
}
__device__ __forceinline__ void mbar_init(uint32_t bar, uint32_t count) {
    asm volatile("mbarrier.init.shared::cta.b64 [%0], %1;" ::"r"(bar), "r"(count) : "memory");
}
__device__ __forceinline__ uint32_t clock32() { uint64_t c; asm volatile("mov.u64 %0, %%clock64;" : "=l"(c)); return (uint32_t)c; }
__device__ __forceinline__ void mbar_arrive(uint32_t bar) {
    asm volatile("mbarrier.arrive.shared::cta.b64 _, [%0];" ::"r"(bar) : "memory");
}
__device__ __forceinline__ uint32_t mapa(uint32_t a, uint32_t rank) {
    uint32_t r;
    asm("mapa.shared::cluster.u32 %0, %1, %2;" : "=r"(r) : "r"(a), "r"(rank));
    return r;
}
__device__ __forceinline__ void mbar_arrive_pair(uint32_t cbar, uint32_t base) {
    asm volatile("{\n.reg .pred p;\nsetp.ne.u32 p, %1, 0;\n@p mbarrier.arrive.shared::cluster.b64 _, [%0];\n}\n"
                 ::"r"(cbar), "r"(base) : "memory");
}
__device__ __forceinline__ void mbar_arrive_cluster_n(uint32_t cbar, uint32_t n) {
    asm volatile("mbarrier.arrive.shared::cluster.b64 _, [%0], %1;" ::"r"(cbar), "r"(n) : "memory");
}
__device__ __forceinline__ void delay_until(uint32_t t0, int clks) {
    while (__any_sync(0xffffffffu, (int)(clock32() - t0) < clks)) {}
}
__device__ __forceinline__ bool mbar_test(uint32_t bar, uint32_t parity) {
    uint32_t ok;
    asm volatile("{\n.reg .pred p;\nmbarrier.test_wait.parity.shared::cta.b64 p, [%1], %2;\nvote.sync.all.pred p, p, 0xffffffff;\nselp.u32 %0, 1, 0, p;\n}\n"
                 : "=r"(ok) : "r"(bar), "r"(parity) : "memory");
    return ok != 0;
}
__device__ __forceinline__ void mbar_wait(uint32_t bar, uint32_t parity) {
    asm volatile(
        "{\n.reg .pred p;\n.reg .u32 i;\n"
        "mbarrier.try_wait.parity.shared::cta.b64 p, [%0], %1;\n"
        "@p bra D_%=;\n"
        "mov.u32 i, 0;\n"
        "L_%=:\n"
        "mbarrier.try_wait.parity.shared::cta.b64 p, [%0], %1;\n"
        "@p bra D_%=;\n"
        "add.u32 i, i, 1;\n"
        "setp.lt.u32 p, i, %2;\n"
        "@p bra L_%=;\n"
        "D_%=:\n}\n"
        ::"r"(bar), "r"(parity), "n"(SPIN_LIMIT) : "memory");
}
__device__ __forceinline__ void tma_store_2d(const CUtensorMap* map, uint32_t src, int c0, int c1) {
    asm volatile("cp.async.bulk.tensor.2d.global.shared::cta.bulk_group [%0, {%2, %3}], [%1];"
                 ::"l"(map), "r"(src), "r"(c0), "r"(c1) : "memory");
}
__device__ __forceinline__ void prefetch_map(const CUtensorMap* map) {
    asm volatile("prefetch.tensormap [%0];" ::"l"(map) : "memory");
}
constexpr uint32_t SMEM_BASE = 1024;
__host__ __device__ constexpr uint64_t make_desc(uint32_t saddr) {
    return (uint64_t)((saddr & 0x3FFFF) >> 4) | ((uint64_t)1 << 16) | ((uint64_t)(1024 >> 4) << 32) | ((uint64_t)1 << 62);
}
__device__ __forceinline__ void wgmma_fence() { asm volatile("wgmma.fence.sync.aligned;" ::: "memory"); }
__device__ __forceinline__ void wgmma_commit() { asm volatile("wgmma.commit_group.sync.aligned;" ::: "memory"); }
template <int N> __device__ __forceinline__ void wgmma_wait() {
    asm volatile("wgmma.wait_group.sync.aligned %0;" ::"n"(N) : "memory");
}
__device__ __forceinline__ uint32_t pack_bf16x2(float lo, float hi) {
    uint32_t r;
    asm("cvt.rn.bf16x2.f32 %0, %1, %2;" : "=r"(r) : "f"(hi), "f"(lo));
    return r;
}
__device__ __forceinline__ uint32_t lds32(uint32_t addr) {
    uint32_t v;
    asm("ld.shared.u32 %0, [%1];" : "=r"(v) : "r"(addr));
    return v;
}
__device__ __forceinline__ uint32_t dp4a_u(uint32_t a, uint32_t b, uint32_t c) {
    uint32_t d;
    asm("dp4a.u32.u32 %0, %1, %2, %3;" : "=r"(d) : "r"(a), "r"(b), "r"(c));
    return d;
}
__device__ __forceinline__ uint32_t prmt(uint32_t a, uint32_t b, uint32_t s) {
    uint32_t d;
    asm("prmt.b32 %0, %1, %2, %3;" : "=r"(d) : "r"(a), "r"(b), "r"(s));
    return d;
}
template <int ID, int NT> __device__ __forceinline__ void named_bar_sync() {
    asm volatile("bar.sync %0, %1;" ::"n"(ID), "n"(NT) : "memory");
}
template <int ID, int NT> __device__ __forceinline__ void named_bar_arrive() {
    asm volatile("bar.arrive %0, %1;" ::"n"(ID), "n"(NT) : "memory");
}
__device__ __forceinline__ void bar_sync_id(int id, int nt) { asm volatile("bar.sync %0, %1;" ::"r"(id), "r"(nt) : "memory"); }
__device__ __forceinline__ void bar_arrive_id(int id, int nt) { asm volatile("bar.arrive %0, %1;" ::"r"(id), "r"(nt) : "memory"); }
__device__ __forceinline__ void cluster_arrive_relaxed() { asm volatile("barrier.cluster.arrive.relaxed.aligned;" ::: "memory"); }
__device__ __forceinline__ void cluster_wait() { asm volatile("barrier.cluster.wait.acquire.aligned;" ::: "memory"); }
__device__ __forceinline__ uint4 ldg_stream(const int* p) {
    uint4 v;
    asm volatile("ld.global.L1::no_allocate.L2::128B.v4.u32 {%0, %1, %2, %3}, [%4];"
                 : "=r"(v.x), "=r"(v.y), "=r"(v.z), "=r"(v.w) : "l"(p));
    return v;
}
__device__ __forceinline__ uint32_t ldg_u16(const unsigned short* p) {
    uint32_t v;
    asm volatile("ld.global.nc.u16 %0, [%1];" : "=r"(v) : "l"(p));
    return v;
}
__device__ __forceinline__ unsigned ld_ca_u32(const unsigned* p) {
    unsigned v;
    asm volatile("ld.global.ca.u32 %0, [%1];" : "=r"(v) : "l"(p) : "memory");
    return v;
}
typedef unsigned long long u64;
__device__ __forceinline__ void ll_store2(u64* p, uint32_t w0, uint32_t w1, uint32_t tag) {
    asm volatile("{\n.reg .b64 a, b;\nmov.b64 a, {%1, %3};\nmov.b64 b, {%2, %3};\n"
                 "st.relaxed.gpu.global.v2.b64 [%0], {a, b};\n}\n" ::"l"(p), "r"(w0), "r"(w1), "r"(tag) : "memory");
}

template <int N, int OFF, bool ACC, int NA> struct WG;
template <int OFF, int NA> struct WG<232, OFF, false, NA> {
    static __device__ __forceinline__ void mma(float (&d)[NA], uint32_t a0, uint32_t a1, uint32_t a2, uint32_t a3, uint64_t descB) {
        asm volatile(
            "{\n"
            ".reg .pred p;\n"
            "setp.ne.b32 p, %121, 0;\n"
            "wgmma.mma_async.sync.aligned.m64n232k16.f32.bf16.bf16 "
            "{%0, %1, %2, %3, %4, %5, %6, %7, %8, %9, %10, %11, %12, %13, %14, %15, %16, %17, %18, %19, %20, %21, %22, %23, %24, %25, %26, %27, %28, %29, %30, %31, %32, %33, %34, %35, %36, %37, %38, %39, %40, %41, %42, %43, %44, %45, %46, %47, %48, %49, %50, %51, %52, %53, %54, %55, %56, %57, %58, %59, %60, %61, %62, %63, %64, %65, %66, %67, %68, %69, %70, %71, %72, %73, %74, %75, %76, %77, %78, %79, %80, %81, %82, %83, %84, %85, %86, %87, %88, %89, %90, %91, %92, %93, %94, %95, %96, %97, %98, %99, %100, %101, %102, %103, %104, %105, %106, %107, %108, %109, %110, %111, %112, %113, %114, %115}, "
            "{%116, %117, %118, %119}, %120, p, 1, 1, 0;\n"
            "}\n"
            : "=f"(d[OFF + 0]), "=f"(d[OFF + 1]), "=f"(d[OFF + 2]), "=f"(d[OFF + 3]), "=f"(d[OFF + 4]), "=f"(d[OFF + 5]), "=f"(d[OFF + 6]), "=f"(d[OFF + 7]), "=f"(d[OFF + 8]), "=f"(d[OFF + 9]), "=f"(d[OFF + 10]), "=f"(d[OFF + 11]), "=f"(d[OFF + 12]), "=f"(d[OFF + 13]), "=f"(d[OFF + 14]), "=f"(d[OFF + 15]), "=f"(d[OFF + 16]), "=f"(d[OFF + 17]), "=f"(d[OFF + 18]), "=f"(d[OFF + 19]), "=f"(d[OFF + 20]), "=f"(d[OFF + 21]), "=f"(d[OFF + 22]), "=f"(d[OFF + 23]), "=f"(d[OFF + 24]), "=f"(d[OFF + 25]), "=f"(d[OFF + 26]), "=f"(d[OFF + 27]), "=f"(d[OFF + 28]), "=f"(d[OFF + 29]), "=f"(d[OFF + 30]), "=f"(d[OFF + 31]), "=f"(d[OFF + 32]), "=f"(d[OFF + 33]), "=f"(d[OFF + 34]), "=f"(d[OFF + 35]), "=f"(d[OFF + 36]), "=f"(d[OFF + 37]), "=f"(d[OFF + 38]), "=f"(d[OFF + 39]), "=f"(d[OFF + 40]), "=f"(d[OFF + 41]), "=f"(d[OFF + 42]), "=f"(d[OFF + 43]), "=f"(d[OFF + 44]), "=f"(d[OFF + 45]), "=f"(d[OFF + 46]), "=f"(d[OFF + 47]), "=f"(d[OFF + 48]), "=f"(d[OFF + 49]), "=f"(d[OFF + 50]), "=f"(d[OFF + 51]), "=f"(d[OFF + 52]), "=f"(d[OFF + 53]), "=f"(d[OFF + 54]), "=f"(d[OFF + 55]), "=f"(d[OFF + 56]), "=f"(d[OFF + 57]), "=f"(d[OFF + 58]), "=f"(d[OFF + 59]), "=f"(d[OFF + 60]), "=f"(d[OFF + 61]), "=f"(d[OFF + 62]), "=f"(d[OFF + 63]), "=f"(d[OFF + 64]), "=f"(d[OFF + 65]), "=f"(d[OFF + 66]), "=f"(d[OFF + 67]), "=f"(d[OFF + 68]), "=f"(d[OFF + 69]), "=f"(d[OFF + 70]), "=f"(d[OFF + 71]), "=f"(d[OFF + 72]), "=f"(d[OFF + 73]), "=f"(d[OFF + 74]), "=f"(d[OFF + 75]), "=f"(d[OFF + 76]), "=f"(d[OFF + 77]), "=f"(d[OFF + 78]), "=f"(d[OFF + 79]), "=f"(d[OFF + 80]), "=f"(d[OFF + 81]), "=f"(d[OFF + 82]), "=f"(d[OFF + 83]), "=f"(d[OFF + 84]), "=f"(d[OFF + 85]), "=f"(d[OFF + 86]), "=f"(d[OFF + 87]), "=f"(d[OFF + 88]), "=f"(d[OFF + 89]), "=f"(d[OFF + 90]), "=f"(d[OFF + 91]), "=f"(d[OFF + 92]), "=f"(d[OFF + 93]), "=f"(d[OFF + 94]), "=f"(d[OFF + 95]), "=f"(d[OFF + 96]), "=f"(d[OFF + 97]), "=f"(d[OFF + 98]), "=f"(d[OFF + 99]), "=f"(d[OFF + 100]), "=f"(d[OFF + 101]), "=f"(d[OFF + 102]), "=f"(d[OFF + 103]), "=f"(d[OFF + 104]), "=f"(d[OFF + 105]), "=f"(d[OFF + 106]), "=f"(d[OFF + 107]), "=f"(d[OFF + 108]), "=f"(d[OFF + 109]), "=f"(d[OFF + 110]), "=f"(d[OFF + 111]), "=f"(d[OFF + 112]), "=f"(d[OFF + 113]), "=f"(d[OFF + 114]), "=f"(d[OFF + 115])
            : "r"(a0), "r"(a1), "r"(a2), "r"(a3), "l"(descB), "n"(0));
    }
};
template <int OFF, int NA> struct WG<232, OFF, true, NA> {
    static __device__ __forceinline__ void mma(float (&d)[NA], uint32_t a0, uint32_t a1, uint32_t a2, uint32_t a3, uint64_t descB) {
        asm volatile(
            "{\n"
            ".reg .pred p;\n"
            "setp.ne.b32 p, %121, 0;\n"
            "wgmma.mma_async.sync.aligned.m64n232k16.f32.bf16.bf16 "
            "{%0, %1, %2, %3, %4, %5, %6, %7, %8, %9, %10, %11, %12, %13, %14, %15, %16, %17, %18, %19, %20, %21, %22, %23, %24, %25, %26, %27, %28, %29, %30, %31, %32, %33, %34, %35, %36, %37, %38, %39, %40, %41, %42, %43, %44, %45, %46, %47, %48, %49, %50, %51, %52, %53, %54, %55, %56, %57, %58, %59, %60, %61, %62, %63, %64, %65, %66, %67, %68, %69, %70, %71, %72, %73, %74, %75, %76, %77, %78, %79, %80, %81, %82, %83, %84, %85, %86, %87, %88, %89, %90, %91, %92, %93, %94, %95, %96, %97, %98, %99, %100, %101, %102, %103, %104, %105, %106, %107, %108, %109, %110, %111, %112, %113, %114, %115}, "
            "{%116, %117, %118, %119}, %120, p, 1, 1, 0;\n"
            "}\n"
            : "+f"(d[OFF + 0]), "+f"(d[OFF + 1]), "+f"(d[OFF + 2]), "+f"(d[OFF + 3]), "+f"(d[OFF + 4]), "+f"(d[OFF + 5]), "+f"(d[OFF + 6]), "+f"(d[OFF + 7]), "+f"(d[OFF + 8]), "+f"(d[OFF + 9]), "+f"(d[OFF + 10]), "+f"(d[OFF + 11]), "+f"(d[OFF + 12]), "+f"(d[OFF + 13]), "+f"(d[OFF + 14]), "+f"(d[OFF + 15]), "+f"(d[OFF + 16]), "+f"(d[OFF + 17]), "+f"(d[OFF + 18]), "+f"(d[OFF + 19]), "+f"(d[OFF + 20]), "+f"(d[OFF + 21]), "+f"(d[OFF + 22]), "+f"(d[OFF + 23]), "+f"(d[OFF + 24]), "+f"(d[OFF + 25]), "+f"(d[OFF + 26]), "+f"(d[OFF + 27]), "+f"(d[OFF + 28]), "+f"(d[OFF + 29]), "+f"(d[OFF + 30]), "+f"(d[OFF + 31]), "+f"(d[OFF + 32]), "+f"(d[OFF + 33]), "+f"(d[OFF + 34]), "+f"(d[OFF + 35]), "+f"(d[OFF + 36]), "+f"(d[OFF + 37]), "+f"(d[OFF + 38]), "+f"(d[OFF + 39]), "+f"(d[OFF + 40]), "+f"(d[OFF + 41]), "+f"(d[OFF + 42]), "+f"(d[OFF + 43]), "+f"(d[OFF + 44]), "+f"(d[OFF + 45]), "+f"(d[OFF + 46]), "+f"(d[OFF + 47]), "+f"(d[OFF + 48]), "+f"(d[OFF + 49]), "+f"(d[OFF + 50]), "+f"(d[OFF + 51]), "+f"(d[OFF + 52]), "+f"(d[OFF + 53]), "+f"(d[OFF + 54]), "+f"(d[OFF + 55]), "+f"(d[OFF + 56]), "+f"(d[OFF + 57]), "+f"(d[OFF + 58]), "+f"(d[OFF + 59]), "+f"(d[OFF + 60]), "+f"(d[OFF + 61]), "+f"(d[OFF + 62]), "+f"(d[OFF + 63]), "+f"(d[OFF + 64]), "+f"(d[OFF + 65]), "+f"(d[OFF + 66]), "+f"(d[OFF + 67]), "+f"(d[OFF + 68]), "+f"(d[OFF + 69]), "+f"(d[OFF + 70]), "+f"(d[OFF + 71]), "+f"(d[OFF + 72]), "+f"(d[OFF + 73]), "+f"(d[OFF + 74]), "+f"(d[OFF + 75]), "+f"(d[OFF + 76]), "+f"(d[OFF + 77]), "+f"(d[OFF + 78]), "+f"(d[OFF + 79]), "+f"(d[OFF + 80]), "+f"(d[OFF + 81]), "+f"(d[OFF + 82]), "+f"(d[OFF + 83]), "+f"(d[OFF + 84]), "+f"(d[OFF + 85]), "+f"(d[OFF + 86]), "+f"(d[OFF + 87]), "+f"(d[OFF + 88]), "+f"(d[OFF + 89]), "+f"(d[OFF + 90]), "+f"(d[OFF + 91]), "+f"(d[OFF + 92]), "+f"(d[OFF + 93]), "+f"(d[OFF + 94]), "+f"(d[OFF + 95]), "+f"(d[OFF + 96]), "+f"(d[OFF + 97]), "+f"(d[OFF + 98]), "+f"(d[OFF + 99]), "+f"(d[OFF + 100]), "+f"(d[OFF + 101]), "+f"(d[OFF + 102]), "+f"(d[OFF + 103]), "+f"(d[OFF + 104]), "+f"(d[OFF + 105]), "+f"(d[OFF + 106]), "+f"(d[OFF + 107]), "+f"(d[OFF + 108]), "+f"(d[OFF + 109]), "+f"(d[OFF + 110]), "+f"(d[OFF + 111]), "+f"(d[OFF + 112]), "+f"(d[OFF + 113]), "+f"(d[OFF + 114]), "+f"(d[OFF + 115])
            : "r"(a0), "r"(a1), "r"(a2), "r"(a3), "l"(descB), "n"(1));
    }
};
template <int OFF, int NA> struct WG<208, OFF, false, NA> {
    static __device__ __forceinline__ void mma(float (&d)[NA], uint32_t a0, uint32_t a1, uint32_t a2, uint32_t a3, uint64_t descB) {
        asm volatile(
            "{\n"
            ".reg .pred p;\n"
            "setp.ne.b32 p, %109, 0;\n"
            "wgmma.mma_async.sync.aligned.m64n208k16.f32.bf16.bf16 "
            "{%0, %1, %2, %3, %4, %5, %6, %7, %8, %9, %10, %11, %12, %13, %14, %15, %16, %17, %18, %19, %20, %21, %22, %23, %24, %25, %26, %27, %28, %29, %30, %31, %32, %33, %34, %35, %36, %37, %38, %39, %40, %41, %42, %43, %44, %45, %46, %47, %48, %49, %50, %51, %52, %53, %54, %55, %56, %57, %58, %59, %60, %61, %62, %63, %64, %65, %66, %67, %68, %69, %70, %71, %72, %73, %74, %75, %76, %77, %78, %79, %80, %81, %82, %83, %84, %85, %86, %87, %88, %89, %90, %91, %92, %93, %94, %95, %96, %97, %98, %99, %100, %101, %102, %103}, "
            "{%104, %105, %106, %107}, %108, p, 1, 1, 0;\n"
            "}\n"
            : "=f"(d[OFF + 0]), "=f"(d[OFF + 1]), "=f"(d[OFF + 2]), "=f"(d[OFF + 3]), "=f"(d[OFF + 4]), "=f"(d[OFF + 5]), "=f"(d[OFF + 6]), "=f"(d[OFF + 7]), "=f"(d[OFF + 8]), "=f"(d[OFF + 9]), "=f"(d[OFF + 10]), "=f"(d[OFF + 11]), "=f"(d[OFF + 12]), "=f"(d[OFF + 13]), "=f"(d[OFF + 14]), "=f"(d[OFF + 15]), "=f"(d[OFF + 16]), "=f"(d[OFF + 17]), "=f"(d[OFF + 18]), "=f"(d[OFF + 19]), "=f"(d[OFF + 20]), "=f"(d[OFF + 21]), "=f"(d[OFF + 22]), "=f"(d[OFF + 23]), "=f"(d[OFF + 24]), "=f"(d[OFF + 25]), "=f"(d[OFF + 26]), "=f"(d[OFF + 27]), "=f"(d[OFF + 28]), "=f"(d[OFF + 29]), "=f"(d[OFF + 30]), "=f"(d[OFF + 31]), "=f"(d[OFF + 32]), "=f"(d[OFF + 33]), "=f"(d[OFF + 34]), "=f"(d[OFF + 35]), "=f"(d[OFF + 36]), "=f"(d[OFF + 37]), "=f"(d[OFF + 38]), "=f"(d[OFF + 39]), "=f"(d[OFF + 40]), "=f"(d[OFF + 41]), "=f"(d[OFF + 42]), "=f"(d[OFF + 43]), "=f"(d[OFF + 44]), "=f"(d[OFF + 45]), "=f"(d[OFF + 46]), "=f"(d[OFF + 47]), "=f"(d[OFF + 48]), "=f"(d[OFF + 49]), "=f"(d[OFF + 50]), "=f"(d[OFF + 51]), "=f"(d[OFF + 52]), "=f"(d[OFF + 53]), "=f"(d[OFF + 54]), "=f"(d[OFF + 55]), "=f"(d[OFF + 56]), "=f"(d[OFF + 57]), "=f"(d[OFF + 58]), "=f"(d[OFF + 59]), "=f"(d[OFF + 60]), "=f"(d[OFF + 61]), "=f"(d[OFF + 62]), "=f"(d[OFF + 63]), "=f"(d[OFF + 64]), "=f"(d[OFF + 65]), "=f"(d[OFF + 66]), "=f"(d[OFF + 67]), "=f"(d[OFF + 68]), "=f"(d[OFF + 69]), "=f"(d[OFF + 70]), "=f"(d[OFF + 71]), "=f"(d[OFF + 72]), "=f"(d[OFF + 73]), "=f"(d[OFF + 74]), "=f"(d[OFF + 75]), "=f"(d[OFF + 76]), "=f"(d[OFF + 77]), "=f"(d[OFF + 78]), "=f"(d[OFF + 79]), "=f"(d[OFF + 80]), "=f"(d[OFF + 81]), "=f"(d[OFF + 82]), "=f"(d[OFF + 83]), "=f"(d[OFF + 84]), "=f"(d[OFF + 85]), "=f"(d[OFF + 86]), "=f"(d[OFF + 87]), "=f"(d[OFF + 88]), "=f"(d[OFF + 89]), "=f"(d[OFF + 90]), "=f"(d[OFF + 91]), "=f"(d[OFF + 92]), "=f"(d[OFF + 93]), "=f"(d[OFF + 94]), "=f"(d[OFF + 95]), "=f"(d[OFF + 96]), "=f"(d[OFF + 97]), "=f"(d[OFF + 98]), "=f"(d[OFF + 99]), "=f"(d[OFF + 100]), "=f"(d[OFF + 101]), "=f"(d[OFF + 102]), "=f"(d[OFF + 103])
            : "r"(a0), "r"(a1), "r"(a2), "r"(a3), "l"(descB), "n"(0));
    }
};
template <int OFF, int NA> struct WG<208, OFF, true, NA> {
    static __device__ __forceinline__ void mma(float (&d)[NA], uint32_t a0, uint32_t a1, uint32_t a2, uint32_t a3, uint64_t descB) {
        asm volatile(
            "{\n"
            ".reg .pred p;\n"
            "setp.ne.b32 p, %109, 0;\n"
            "wgmma.mma_async.sync.aligned.m64n208k16.f32.bf16.bf16 "
            "{%0, %1, %2, %3, %4, %5, %6, %7, %8, %9, %10, %11, %12, %13, %14, %15, %16, %17, %18, %19, %20, %21, %22, %23, %24, %25, %26, %27, %28, %29, %30, %31, %32, %33, %34, %35, %36, %37, %38, %39, %40, %41, %42, %43, %44, %45, %46, %47, %48, %49, %50, %51, %52, %53, %54, %55, %56, %57, %58, %59, %60, %61, %62, %63, %64, %65, %66, %67, %68, %69, %70, %71, %72, %73, %74, %75, %76, %77, %78, %79, %80, %81, %82, %83, %84, %85, %86, %87, %88, %89, %90, %91, %92, %93, %94, %95, %96, %97, %98, %99, %100, %101, %102, %103}, "
            "{%104, %105, %106, %107}, %108, p, 1, 1, 0;\n"
            "}\n"
            : "+f"(d[OFF + 0]), "+f"(d[OFF + 1]), "+f"(d[OFF + 2]), "+f"(d[OFF + 3]), "+f"(d[OFF + 4]), "+f"(d[OFF + 5]), "+f"(d[OFF + 6]), "+f"(d[OFF + 7]), "+f"(d[OFF + 8]), "+f"(d[OFF + 9]), "+f"(d[OFF + 10]), "+f"(d[OFF + 11]), "+f"(d[OFF + 12]), "+f"(d[OFF + 13]), "+f"(d[OFF + 14]), "+f"(d[OFF + 15]), "+f"(d[OFF + 16]), "+f"(d[OFF + 17]), "+f"(d[OFF + 18]), "+f"(d[OFF + 19]), "+f"(d[OFF + 20]), "+f"(d[OFF + 21]), "+f"(d[OFF + 22]), "+f"(d[OFF + 23]), "+f"(d[OFF + 24]), "+f"(d[OFF + 25]), "+f"(d[OFF + 26]), "+f"(d[OFF + 27]), "+f"(d[OFF + 28]), "+f"(d[OFF + 29]), "+f"(d[OFF + 30]), "+f"(d[OFF + 31]), "+f"(d[OFF + 32]), "+f"(d[OFF + 33]), "+f"(d[OFF + 34]), "+f"(d[OFF + 35]), "+f"(d[OFF + 36]), "+f"(d[OFF + 37]), "+f"(d[OFF + 38]), "+f"(d[OFF + 39]), "+f"(d[OFF + 40]), "+f"(d[OFF + 41]), "+f"(d[OFF + 42]), "+f"(d[OFF + 43]), "+f"(d[OFF + 44]), "+f"(d[OFF + 45]), "+f"(d[OFF + 46]), "+f"(d[OFF + 47]), "+f"(d[OFF + 48]), "+f"(d[OFF + 49]), "+f"(d[OFF + 50]), "+f"(d[OFF + 51]), "+f"(d[OFF + 52]), "+f"(d[OFF + 53]), "+f"(d[OFF + 54]), "+f"(d[OFF + 55]), "+f"(d[OFF + 56]), "+f"(d[OFF + 57]), "+f"(d[OFF + 58]), "+f"(d[OFF + 59]), "+f"(d[OFF + 60]), "+f"(d[OFF + 61]), "+f"(d[OFF + 62]), "+f"(d[OFF + 63]), "+f"(d[OFF + 64]), "+f"(d[OFF + 65]), "+f"(d[OFF + 66]), "+f"(d[OFF + 67]), "+f"(d[OFF + 68]), "+f"(d[OFF + 69]), "+f"(d[OFF + 70]), "+f"(d[OFF + 71]), "+f"(d[OFF + 72]), "+f"(d[OFF + 73]), "+f"(d[OFF + 74]), "+f"(d[OFF + 75]), "+f"(d[OFF + 76]), "+f"(d[OFF + 77]), "+f"(d[OFF + 78]), "+f"(d[OFF + 79]), "+f"(d[OFF + 80]), "+f"(d[OFF + 81]), "+f"(d[OFF + 82]), "+f"(d[OFF + 83]), "+f"(d[OFF + 84]), "+f"(d[OFF + 85]), "+f"(d[OFF + 86]), "+f"(d[OFF + 87]), "+f"(d[OFF + 88]), "+f"(d[OFF + 89]), "+f"(d[OFF + 90]), "+f"(d[OFF + 91]), "+f"(d[OFF + 92]), "+f"(d[OFF + 93]), "+f"(d[OFF + 94]), "+f"(d[OFF + 95]), "+f"(d[OFF + 96]), "+f"(d[OFF + 97]), "+f"(d[OFF + 98]), "+f"(d[OFF + 99]), "+f"(d[OFF + 100]), "+f"(d[OFF + 101]), "+f"(d[OFF + 102]), "+f"(d[OFF + 103])
            : "r"(a0), "r"(a1), "r"(a2), "r"(a3), "l"(descB), "n"(1));
    }
};
template <int OFF, int NA> struct WG<120, OFF, false, NA> {
    static __device__ __forceinline__ void mma(float (&d)[NA], uint32_t a0, uint32_t a1, uint32_t a2, uint32_t a3, uint64_t descB) {
        asm volatile(
            "{\n"
            ".reg .pred p;\n"
            "setp.ne.b32 p, %65, 0;\n"
            "wgmma.mma_async.sync.aligned.m64n120k16.f32.bf16.bf16 "
            "{%0, %1, %2, %3, %4, %5, %6, %7, %8, %9, %10, %11, %12, %13, %14, %15, %16, %17, %18, %19, %20, %21, %22, %23, %24, %25, %26, %27, %28, %29, %30, %31, %32, %33, %34, %35, %36, %37, %38, %39, %40, %41, %42, %43, %44, %45, %46, %47, %48, %49, %50, %51, %52, %53, %54, %55, %56, %57, %58, %59}, "
            "{%60, %61, %62, %63}, %64, p, 1, 1, 0;\n"
            "}\n"
            : "=f"(d[OFF + 0]), "=f"(d[OFF + 1]), "=f"(d[OFF + 2]), "=f"(d[OFF + 3]), "=f"(d[OFF + 4]), "=f"(d[OFF + 5]), "=f"(d[OFF + 6]), "=f"(d[OFF + 7]), "=f"(d[OFF + 8]), "=f"(d[OFF + 9]), "=f"(d[OFF + 10]), "=f"(d[OFF + 11]), "=f"(d[OFF + 12]), "=f"(d[OFF + 13]), "=f"(d[OFF + 14]), "=f"(d[OFF + 15]), "=f"(d[OFF + 16]), "=f"(d[OFF + 17]), "=f"(d[OFF + 18]), "=f"(d[OFF + 19]), "=f"(d[OFF + 20]), "=f"(d[OFF + 21]), "=f"(d[OFF + 22]), "=f"(d[OFF + 23]), "=f"(d[OFF + 24]), "=f"(d[OFF + 25]), "=f"(d[OFF + 26]), "=f"(d[OFF + 27]), "=f"(d[OFF + 28]), "=f"(d[OFF + 29]), "=f"(d[OFF + 30]), "=f"(d[OFF + 31]), "=f"(d[OFF + 32]), "=f"(d[OFF + 33]), "=f"(d[OFF + 34]), "=f"(d[OFF + 35]), "=f"(d[OFF + 36]), "=f"(d[OFF + 37]), "=f"(d[OFF + 38]), "=f"(d[OFF + 39]), "=f"(d[OFF + 40]), "=f"(d[OFF + 41]), "=f"(d[OFF + 42]), "=f"(d[OFF + 43]), "=f"(d[OFF + 44]), "=f"(d[OFF + 45]), "=f"(d[OFF + 46]), "=f"(d[OFF + 47]), "=f"(d[OFF + 48]), "=f"(d[OFF + 49]), "=f"(d[OFF + 50]), "=f"(d[OFF + 51]), "=f"(d[OFF + 52]), "=f"(d[OFF + 53]), "=f"(d[OFF + 54]), "=f"(d[OFF + 55]), "=f"(d[OFF + 56]), "=f"(d[OFF + 57]), "=f"(d[OFF + 58]), "=f"(d[OFF + 59])
            : "r"(a0), "r"(a1), "r"(a2), "r"(a3), "l"(descB), "n"(0));
    }
};
template <int OFF, int NA> struct WG<120, OFF, true, NA> {
    static __device__ __forceinline__ void mma(float (&d)[NA], uint32_t a0, uint32_t a1, uint32_t a2, uint32_t a3, uint64_t descB) {
        asm volatile(
            "{\n"
            ".reg .pred p;\n"
            "setp.ne.b32 p, %65, 0;\n"
            "wgmma.mma_async.sync.aligned.m64n120k16.f32.bf16.bf16 "
            "{%0, %1, %2, %3, %4, %5, %6, %7, %8, %9, %10, %11, %12, %13, %14, %15, %16, %17, %18, %19, %20, %21, %22, %23, %24, %25, %26, %27, %28, %29, %30, %31, %32, %33, %34, %35, %36, %37, %38, %39, %40, %41, %42, %43, %44, %45, %46, %47, %48, %49, %50, %51, %52, %53, %54, %55, %56, %57, %58, %59}, "
            "{%60, %61, %62, %63}, %64, p, 1, 1, 0;\n"
            "}\n"
            : "+f"(d[OFF + 0]), "+f"(d[OFF + 1]), "+f"(d[OFF + 2]), "+f"(d[OFF + 3]), "+f"(d[OFF + 4]), "+f"(d[OFF + 5]), "+f"(d[OFF + 6]), "+f"(d[OFF + 7]), "+f"(d[OFF + 8]), "+f"(d[OFF + 9]), "+f"(d[OFF + 10]), "+f"(d[OFF + 11]), "+f"(d[OFF + 12]), "+f"(d[OFF + 13]), "+f"(d[OFF + 14]), "+f"(d[OFF + 15]), "+f"(d[OFF + 16]), "+f"(d[OFF + 17]), "+f"(d[OFF + 18]), "+f"(d[OFF + 19]), "+f"(d[OFF + 20]), "+f"(d[OFF + 21]), "+f"(d[OFF + 22]), "+f"(d[OFF + 23]), "+f"(d[OFF + 24]), "+f"(d[OFF + 25]), "+f"(d[OFF + 26]), "+f"(d[OFF + 27]), "+f"(d[OFF + 28]), "+f"(d[OFF + 29]), "+f"(d[OFF + 30]), "+f"(d[OFF + 31]), "+f"(d[OFF + 32]), "+f"(d[OFF + 33]), "+f"(d[OFF + 34]), "+f"(d[OFF + 35]), "+f"(d[OFF + 36]), "+f"(d[OFF + 37]), "+f"(d[OFF + 38]), "+f"(d[OFF + 39]), "+f"(d[OFF + 40]), "+f"(d[OFF + 41]), "+f"(d[OFF + 42]), "+f"(d[OFF + 43]), "+f"(d[OFF + 44]), "+f"(d[OFF + 45]), "+f"(d[OFF + 46]), "+f"(d[OFF + 47]), "+f"(d[OFF + 48]), "+f"(d[OFF + 49]), "+f"(d[OFF + 50]), "+f"(d[OFF + 51]), "+f"(d[OFF + 52]), "+f"(d[OFF + 53]), "+f"(d[OFF + 54]), "+f"(d[OFF + 55]), "+f"(d[OFF + 56]), "+f"(d[OFF + 57]), "+f"(d[OFF + 58]), "+f"(d[OFF + 59])
            : "r"(a0), "r"(a1), "r"(a2), "r"(a3), "l"(descB), "n"(1));
    }
};
template <int OFF, int NA> struct WG<112, OFF, false, NA> {
    static __device__ __forceinline__ void mma(float (&d)[NA], uint32_t a0, uint32_t a1, uint32_t a2, uint32_t a3, uint64_t descB) {
        asm volatile(
            "{\n"
            ".reg .pred p;\n"
            "setp.ne.b32 p, %61, 0;\n"
            "wgmma.mma_async.sync.aligned.m64n112k16.f32.bf16.bf16 "
            "{%0, %1, %2, %3, %4, %5, %6, %7, %8, %9, %10, %11, %12, %13, %14, %15, %16, %17, %18, %19, %20, %21, %22, %23, %24, %25, %26, %27, %28, %29, %30, %31, %32, %33, %34, %35, %36, %37, %38, %39, %40, %41, %42, %43, %44, %45, %46, %47, %48, %49, %50, %51, %52, %53, %54, %55}, "
            "{%56, %57, %58, %59}, %60, p, 1, 1, 0;\n"
            "}\n"
            : "=f"(d[OFF + 0]), "=f"(d[OFF + 1]), "=f"(d[OFF + 2]), "=f"(d[OFF + 3]), "=f"(d[OFF + 4]), "=f"(d[OFF + 5]), "=f"(d[OFF + 6]), "=f"(d[OFF + 7]), "=f"(d[OFF + 8]), "=f"(d[OFF + 9]), "=f"(d[OFF + 10]), "=f"(d[OFF + 11]), "=f"(d[OFF + 12]), "=f"(d[OFF + 13]), "=f"(d[OFF + 14]), "=f"(d[OFF + 15]), "=f"(d[OFF + 16]), "=f"(d[OFF + 17]), "=f"(d[OFF + 18]), "=f"(d[OFF + 19]), "=f"(d[OFF + 20]), "=f"(d[OFF + 21]), "=f"(d[OFF + 22]), "=f"(d[OFF + 23]), "=f"(d[OFF + 24]), "=f"(d[OFF + 25]), "=f"(d[OFF + 26]), "=f"(d[OFF + 27]), "=f"(d[OFF + 28]), "=f"(d[OFF + 29]), "=f"(d[OFF + 30]), "=f"(d[OFF + 31]), "=f"(d[OFF + 32]), "=f"(d[OFF + 33]), "=f"(d[OFF + 34]), "=f"(d[OFF + 35]), "=f"(d[OFF + 36]), "=f"(d[OFF + 37]), "=f"(d[OFF + 38]), "=f"(d[OFF + 39]), "=f"(d[OFF + 40]), "=f"(d[OFF + 41]), "=f"(d[OFF + 42]), "=f"(d[OFF + 43]), "=f"(d[OFF + 44]), "=f"(d[OFF + 45]), "=f"(d[OFF + 46]), "=f"(d[OFF + 47]), "=f"(d[OFF + 48]), "=f"(d[OFF + 49]), "=f"(d[OFF + 50]), "=f"(d[OFF + 51]), "=f"(d[OFF + 52]), "=f"(d[OFF + 53]), "=f"(d[OFF + 54]), "=f"(d[OFF + 55])
            : "r"(a0), "r"(a1), "r"(a2), "r"(a3), "l"(descB), "n"(0));
    }
};
template <int OFF, int NA> struct WG<112, OFF, true, NA> {
    static __device__ __forceinline__ void mma(float (&d)[NA], uint32_t a0, uint32_t a1, uint32_t a2, uint32_t a3, uint64_t descB) {
        asm volatile(
            "{\n"
            ".reg .pred p;\n"
            "setp.ne.b32 p, %61, 0;\n"
            "wgmma.mma_async.sync.aligned.m64n112k16.f32.bf16.bf16 "
            "{%0, %1, %2, %3, %4, %5, %6, %7, %8, %9, %10, %11, %12, %13, %14, %15, %16, %17, %18, %19, %20, %21, %22, %23, %24, %25, %26, %27, %28, %29, %30, %31, %32, %33, %34, %35, %36, %37, %38, %39, %40, %41, %42, %43, %44, %45, %46, %47, %48, %49, %50, %51, %52, %53, %54, %55}, "
            "{%56, %57, %58, %59}, %60, p, 1, 1, 0;\n"
            "}\n"
            : "+f"(d[OFF + 0]), "+f"(d[OFF + 1]), "+f"(d[OFF + 2]), "+f"(d[OFF + 3]), "+f"(d[OFF + 4]), "+f"(d[OFF + 5]), "+f"(d[OFF + 6]), "+f"(d[OFF + 7]), "+f"(d[OFF + 8]), "+f"(d[OFF + 9]), "+f"(d[OFF + 10]), "+f"(d[OFF + 11]), "+f"(d[OFF + 12]), "+f"(d[OFF + 13]), "+f"(d[OFF + 14]), "+f"(d[OFF + 15]), "+f"(d[OFF + 16]), "+f"(d[OFF + 17]), "+f"(d[OFF + 18]), "+f"(d[OFF + 19]), "+f"(d[OFF + 20]), "+f"(d[OFF + 21]), "+f"(d[OFF + 22]), "+f"(d[OFF + 23]), "+f"(d[OFF + 24]), "+f"(d[OFF + 25]), "+f"(d[OFF + 26]), "+f"(d[OFF + 27]), "+f"(d[OFF + 28]), "+f"(d[OFF + 29]), "+f"(d[OFF + 30]), "+f"(d[OFF + 31]), "+f"(d[OFF + 32]), "+f"(d[OFF + 33]), "+f"(d[OFF + 34]), "+f"(d[OFF + 35]), "+f"(d[OFF + 36]), "+f"(d[OFF + 37]), "+f"(d[OFF + 38]), "+f"(d[OFF + 39]), "+f"(d[OFF + 40]), "+f"(d[OFF + 41]), "+f"(d[OFF + 42]), "+f"(d[OFF + 43]), "+f"(d[OFF + 44]), "+f"(d[OFF + 45]), "+f"(d[OFF + 46]), "+f"(d[OFF + 47]), "+f"(d[OFF + 48]), "+f"(d[OFF + 49]), "+f"(d[OFF + 50]), "+f"(d[OFF + 51]), "+f"(d[OFF + 52]), "+f"(d[OFF + 53]), "+f"(d[OFF + 54]), "+f"(d[OFF + 55])
            : "r"(a0), "r"(a1), "r"(a2), "r"(a3), "l"(descB), "n"(1));
    }
};
template <int OFF, int NA> struct WG<96, OFF, false, NA> {
    static __device__ __forceinline__ void mma(float (&d)[NA], uint32_t a0, uint32_t a1, uint32_t a2, uint32_t a3, uint64_t descB) {
        asm volatile(
            "{\n"
            ".reg .pred p;\n"
            "setp.ne.b32 p, %53, 0;\n"
            "wgmma.mma_async.sync.aligned.m64n96k16.f32.bf16.bf16 "
            "{%0, %1, %2, %3, %4, %5, %6, %7, %8, %9, %10, %11, %12, %13, %14, %15, %16, %17, %18, %19, %20, %21, %22, %23, %24, %25, %26, %27, %28, %29, %30, %31, %32, %33, %34, %35, %36, %37, %38, %39, %40, %41, %42, %43, %44, %45, %46, %47}, "
            "{%48, %49, %50, %51}, %52, p, 1, 1, 0;\n"
            "}\n"
            : "=f"(d[OFF + 0]), "=f"(d[OFF + 1]), "=f"(d[OFF + 2]), "=f"(d[OFF + 3]), "=f"(d[OFF + 4]), "=f"(d[OFF + 5]), "=f"(d[OFF + 6]), "=f"(d[OFF + 7]), "=f"(d[OFF + 8]), "=f"(d[OFF + 9]), "=f"(d[OFF + 10]), "=f"(d[OFF + 11]), "=f"(d[OFF + 12]), "=f"(d[OFF + 13]), "=f"(d[OFF + 14]), "=f"(d[OFF + 15]), "=f"(d[OFF + 16]), "=f"(d[OFF + 17]), "=f"(d[OFF + 18]), "=f"(d[OFF + 19]), "=f"(d[OFF + 20]), "=f"(d[OFF + 21]), "=f"(d[OFF + 22]), "=f"(d[OFF + 23]), "=f"(d[OFF + 24]), "=f"(d[OFF + 25]), "=f"(d[OFF + 26]), "=f"(d[OFF + 27]), "=f"(d[OFF + 28]), "=f"(d[OFF + 29]), "=f"(d[OFF + 30]), "=f"(d[OFF + 31]), "=f"(d[OFF + 32]), "=f"(d[OFF + 33]), "=f"(d[OFF + 34]), "=f"(d[OFF + 35]), "=f"(d[OFF + 36]), "=f"(d[OFF + 37]), "=f"(d[OFF + 38]), "=f"(d[OFF + 39]), "=f"(d[OFF + 40]), "=f"(d[OFF + 41]), "=f"(d[OFF + 42]), "=f"(d[OFF + 43]), "=f"(d[OFF + 44]), "=f"(d[OFF + 45]), "=f"(d[OFF + 46]), "=f"(d[OFF + 47])
            : "r"(a0), "r"(a1), "r"(a2), "r"(a3), "l"(descB), "n"(0));
    }
};
template <int OFF, int NA> struct WG<96, OFF, true, NA> {
    static __device__ __forceinline__ void mma(float (&d)[NA], uint32_t a0, uint32_t a1, uint32_t a2, uint32_t a3, uint64_t descB) {
        asm volatile(
            "{\n"
            ".reg .pred p;\n"
            "setp.ne.b32 p, %53, 0;\n"
            "wgmma.mma_async.sync.aligned.m64n96k16.f32.bf16.bf16 "
            "{%0, %1, %2, %3, %4, %5, %6, %7, %8, %9, %10, %11, %12, %13, %14, %15, %16, %17, %18, %19, %20, %21, %22, %23, %24, %25, %26, %27, %28, %29, %30, %31, %32, %33, %34, %35, %36, %37, %38, %39, %40, %41, %42, %43, %44, %45, %46, %47}, "
            "{%48, %49, %50, %51}, %52, p, 1, 1, 0;\n"
            "}\n"
            : "+f"(d[OFF + 0]), "+f"(d[OFF + 1]), "+f"(d[OFF + 2]), "+f"(d[OFF + 3]), "+f"(d[OFF + 4]), "+f"(d[OFF + 5]), "+f"(d[OFF + 6]), "+f"(d[OFF + 7]), "+f"(d[OFF + 8]), "+f"(d[OFF + 9]), "+f"(d[OFF + 10]), "+f"(d[OFF + 11]), "+f"(d[OFF + 12]), "+f"(d[OFF + 13]), "+f"(d[OFF + 14]), "+f"(d[OFF + 15]), "+f"(d[OFF + 16]), "+f"(d[OFF + 17]), "+f"(d[OFF + 18]), "+f"(d[OFF + 19]), "+f"(d[OFF + 20]), "+f"(d[OFF + 21]), "+f"(d[OFF + 22]), "+f"(d[OFF + 23]), "+f"(d[OFF + 24]), "+f"(d[OFF + 25]), "+f"(d[OFF + 26]), "+f"(d[OFF + 27]), "+f"(d[OFF + 28]), "+f"(d[OFF + 29]), "+f"(d[OFF + 30]), "+f"(d[OFF + 31]), "+f"(d[OFF + 32]), "+f"(d[OFF + 33]), "+f"(d[OFF + 34]), "+f"(d[OFF + 35]), "+f"(d[OFF + 36]), "+f"(d[OFF + 37]), "+f"(d[OFF + 38]), "+f"(d[OFF + 39]), "+f"(d[OFF + 40]), "+f"(d[OFF + 41]), "+f"(d[OFF + 42]), "+f"(d[OFF + 43]), "+f"(d[OFF + 44]), "+f"(d[OFF + 45]), "+f"(d[OFF + 46]), "+f"(d[OFF + 47])
            : "r"(a0), "r"(a1), "r"(a2), "r"(a3), "l"(descB), "n"(1));
    }
};
template <int OFF, int NA> struct WG<64, OFF, true, NA> {
    static __device__ __forceinline__ void mma(float (&d)[NA], uint32_t a0, uint32_t a1, uint32_t a2, uint32_t a3, uint64_t descB) {
        asm volatile(
            "{\n"
            ".reg .pred p;\n"
            "setp.ne.b32 p, %37, 0;\n"
            "wgmma.mma_async.sync.aligned.m64n64k16.f32.bf16.bf16 "
            "{%0, %1, %2, %3, %4, %5, %6, %7, %8, %9, %10, %11, %12, %13, %14, %15, %16, %17, %18, %19, %20, %21, %22, %23, %24, %25, %26, %27, %28, %29, %30, %31}, "
            "{%32, %33, %34, %35}, %36, p, 1, 1, 0;\n"
            "}\n"
            : "+f"(d[OFF + 0]), "+f"(d[OFF + 1]), "+f"(d[OFF + 2]), "+f"(d[OFF + 3]), "+f"(d[OFF + 4]), "+f"(d[OFF + 5]), "+f"(d[OFF + 6]), "+f"(d[OFF + 7]), "+f"(d[OFF + 8]), "+f"(d[OFF + 9]), "+f"(d[OFF + 10]), "+f"(d[OFF + 11]), "+f"(d[OFF + 12]), "+f"(d[OFF + 13]), "+f"(d[OFF + 14]), "+f"(d[OFF + 15]), "+f"(d[OFF + 16]), "+f"(d[OFF + 17]), "+f"(d[OFF + 18]), "+f"(d[OFF + 19]), "+f"(d[OFF + 20]), "+f"(d[OFF + 21]), "+f"(d[OFF + 22]), "+f"(d[OFF + 23]), "+f"(d[OFF + 24]), "+f"(d[OFF + 25]), "+f"(d[OFF + 26]), "+f"(d[OFF + 27]), "+f"(d[OFF + 28]), "+f"(d[OFF + 29]), "+f"(d[OFF + 30]), "+f"(d[OFF + 31])
            : "r"(a0), "r"(a1), "r"(a2), "r"(a3), "l"(descB), "n"(1));
    }
};
template <int OFF, int NA> struct WG<48, OFF, true, NA> {
    static __device__ __forceinline__ void mma(float (&d)[NA], uint32_t a0, uint32_t a1, uint32_t a2, uint32_t a3, uint64_t descB) {
        asm volatile(
            "{\n"
            ".reg .pred p;\n"
            "setp.ne.b32 p, %29, 0;\n"
            "wgmma.mma_async.sync.aligned.m64n48k16.f32.bf16.bf16 "
            "{%0, %1, %2, %3, %4, %5, %6, %7, %8, %9, %10, %11, %12, %13, %14, %15, %16, %17, %18, %19, %20, %21, %22, %23}, "
            "{%24, %25, %26, %27}, %28, p, 1, 1, 0;\n"
            "}\n"
            : "+f"(d[OFF + 0]), "+f"(d[OFF + 1]), "+f"(d[OFF + 2]), "+f"(d[OFF + 3]), "+f"(d[OFF + 4]), "+f"(d[OFF + 5]), "+f"(d[OFF + 6]), "+f"(d[OFF + 7]), "+f"(d[OFF + 8]), "+f"(d[OFF + 9]), "+f"(d[OFF + 10]), "+f"(d[OFF + 11]), "+f"(d[OFF + 12]), "+f"(d[OFF + 13]), "+f"(d[OFF + 14]), "+f"(d[OFF + 15]), "+f"(d[OFF + 16]), "+f"(d[OFF + 17]), "+f"(d[OFF + 18]), "+f"(d[OFF + 19]), "+f"(d[OFF + 20]), "+f"(d[OFF + 21]), "+f"(d[OFF + 22]), "+f"(d[OFF + 23])
            : "r"(a0), "r"(a1), "r"(a2), "r"(a3), "l"(descB), "n"(1));
    }
};
template <int OFF, int NA> struct WG<32, OFF, true, NA> {
    static __device__ __forceinline__ void mma(float (&d)[NA], uint32_t a0, uint32_t a1, uint32_t a2, uint32_t a3, uint64_t descB) {
        asm volatile(
            "{\n"
            ".reg .pred p;\n"
            "setp.ne.b32 p, %21, 0;\n"
            "wgmma.mma_async.sync.aligned.m64n32k16.f32.bf16.bf16 "
            "{%0, %1, %2, %3, %4, %5, %6, %7, %8, %9, %10, %11, %12, %13, %14, %15}, "
            "{%16, %17, %18, %19}, %20, p, 1, 1, 0;\n"
            "}\n"
            : "+f"(d[OFF + 0]), "+f"(d[OFF + 1]), "+f"(d[OFF + 2]), "+f"(d[OFF + 3]), "+f"(d[OFF + 4]), "+f"(d[OFF + 5]), "+f"(d[OFF + 6]), "+f"(d[OFF + 7]), "+f"(d[OFF + 8]), "+f"(d[OFF + 9]), "+f"(d[OFF + 10]), "+f"(d[OFF + 11]), "+f"(d[OFF + 12]), "+f"(d[OFF + 13]), "+f"(d[OFF + 14]), "+f"(d[OFF + 15])
            : "r"(a0), "r"(a1), "r"(a2), "r"(a3), "l"(descB), "n"(1));
    }
};

__host__ __device__ constexpr int gate_time(int d) { return d == 0 ? DLY_POLL : DLY_P1 + (d - 1) * DLY_PS; }
__device__ __forceinline__ void unit_pos(uint32_t u, uint32_t& q, uint32_t& fg) {
    static_assert(W1_FG == 64 && W2_FG == 48, "unit order");
    const uint32_t r = u - NQ * W1_FG, q2 = (r * 1366) >> 16;
    q = u < NQ * W1_FG ? u >> 6 : q2;
    fg = u < NQ * W1_FG ? u & 63 : W1_FG + r - q2 * 48;
}
template <class T> __device__ __forceinline__ T* add_off(T* p, uint32_t bytes) {
    uint64_t r;
    asm("{\n.reg .b64 o;\ncvt.u64.u32 o, %2;\nadd.u64 %0, %1, o;\n}\n" : "=l"(r) : "l"(p), "r"(bytes));
    return (T*)r;
}
__device__ __forceinline__ uint32_t unit_src(uint32_t q, uint32_t fg) { return q * (32 * kN * 4) + fg * 128; }
__device__ __forceinline__ uint32_t lane_src(int lane) { return (lane >> 3) * (2 * kN * 4) + (lane & 7) * 16; }
__device__ __forceinline__ uint32_t unit_dst(uint32_t q, uint32_t fg) {
    return ((fg >> 2) * KSTEPS + (q >> 1)) * 8192 + (fg & 3) * 2048 + (q & 1) * 512;
}
__device__ __forceinline__ uint32_t lane_dst(int lane) { return ((lane >> 2) & 1) * 1024 + (lane & 3) * 64 + (lane >> 3) * 16; }
__device__ __forceinline__ uint32_t lane_unit(int lane) {
    return ((lane >> 3) & 1) * 256 + (((lane >> 4) ^ (lane >> 3)) & 1) * 64 + (lane & 3) * 16 + ((lane >> 2) & 1) * 8;
}
__device__ __forceinline__ constexpr int unit_row(int i) { return 16 * (i >> 2) + 8 * ((i >> 1) & 1) + (i & 1); }
__device__ __forceinline__ void load_unit(uint4 (&v)[8], const int* p) {
#pragma unroll
    for (int i = 0; i < 8; i++) v[i] = ldg_stream(p + (size_t)unit_row(i) * kN);
}
__device__ __forceinline__ uint32_t bytes4(uint32_t v0, uint32_t v1, uint32_t v2, uint32_t v3) {
    return prmt(prmt(v0, v1, 0x0040), prmt(v2, v3, 0x0040), 0x5410);
}
__device__ __forceinline__ void pk_gather(uint32_t (&e)[4], uint32_t (&o)[4], const uint4 (&v)[8]) {
    e[0] = bytes4(v[0].x, v[2].x, v[4].x, v[6].x); o[0] = bytes4(v[1].x, v[3].x, v[5].x, v[7].x);
    e[1] = bytes4(v[0].y, v[2].y, v[4].y, v[6].y); o[1] = bytes4(v[1].y, v[3].y, v[5].y, v[7].y);
    e[2] = bytes4(v[0].z, v[2].z, v[4].z, v[6].z); o[2] = bytes4(v[1].z, v[3].z, v[5].z, v[7].z);
    e[3] = bytes4(v[0].w, v[2].w, v[4].w, v[6].w); o[3] = bytes4(v[1].w, v[3].w, v[5].w, v[7].w);
}

__device__ __forceinline__ void tile0_of(int c, int& fp, int& m0) {
    if (c < 18) { fp = c >= 9; m0 = min((c - 9 * fp) * N0, kM - N0); }
    else { fp = 2 + ((c - 18) >> 3); m0 = ((c - 18) & 7) * N0; }
}
__device__ __forceinline__ void tile1_of(int c, int& fp, int& m0) {
    if (c < 6) { fp = 2 + c; m0 = kM - N1; }
    else { fp = 8 + (c - 6) / 10; m0 = min(((c - 6) % 10) * N1, kM - N1); }
}

__device__ __forceinline__ void ll_fetch(u64 (&c)[4], const char* p) {
    asm volatile("ld.relaxed.gpu.global.b64 %0, [%4];\nld.relaxed.gpu.global.b64 %1, [%4 + 128];\n"
                 "ld.relaxed.gpu.global.b64 %2, [%4 + 512];\nld.relaxed.gpu.global.b64 %3, [%4 + 640];"
                 : "=l"(c[0]), "=l"(c[1]), "=l"(c[2]), "=l"(c[3]) : "l"(p) : "memory");
}
__device__ __forceinline__ void ll_copy(uint32_t dst, const char* src, uint32_t bar) {
    asm volatile("{\n.reg .pred p;\nelect.sync _|p, 0xffffffff;\n"
                 "@p cp.async.bulk.shared::cluster.global.mbarrier::complete_tx::bytes [%0], [%1], 1024, [%2];\n}\n"
                 ::"r"(dst), "l"(src), "r"(bar) : "memory");
}
__device__ __forceinline__ void ll_read(u64 (&c)[4], uint32_t a) {
    asm volatile("ld.volatile.shared.b64 %0, [%4];\nld.volatile.shared.b64 %1, [%4 + 128];\n"
                 "ld.volatile.shared.b64 %2, [%4 + 512];\nld.volatile.shared.b64 %3, [%4 + 640];"
                 : "=l"(c[0]), "=l"(c[1]), "=l"(c[2]), "=l"(c[3]) : "r"(a) : "memory");
}
template <int OFF>
__device__ __forceinline__ void ll_check(u64 (&c)[4], uint32_t a, const char* p, uint32_t tag) {
    asm volatile(
        "{\n.reg .pred p, q;\n.reg .b32 l, h0, h1, h2, h3, x, i, o;\n.reg .b64 g;\n"
        "mov.u32 i, 0;\n"
        "L_%=:\n"
        "mov.b64 {l, h0}, %0;\nmov.b64 {l, h1}, %1;\nmov.b64 {l, h2}, %2;\nmov.b64 {l, h3}, %3;\n"
        "lop3.b32 x, %6, h0, h1, 0x7e;\n"
        "lop3.b32 x, x, %6, h2, 0xf6;\n"
        "lop3.b32 x, x, %6, h3, 0xf6;\n"
        "setp.ne.u32 p, x, 0;\n"
        "vote.sync.any.pred p, p, 0xffffffff;\n"
        "@!p bra D_%=;\n"
        "and.b32 o, %4, 1023;\ncvt.u64.u32 g, o;\nadd.u64 g, g, %5;\n"
        "sub.u32 o, %6, 16;\n"
        "setp.eq.u32 q, h0, o;\nsetp.eq.or.u32 q, h1, o, q;\nsetp.eq.or.u32 q, h2, o, q;\nsetp.eq.or.u32 q, h3, o, q;\n"
        "setp.ge.or.u32 q, i, %8, q;\n"
        "vote.sync.any.pred q, q, 0xffffffff;\n"
        "@!q ld.volatile.shared.b64 %0, [%4 + %9];\n@!q ld.volatile.shared.b64 %1, [%4 + %9 + 128];\n"
        "@!q ld.volatile.shared.b64 %2, [%4 + %9 + 512];\n@!q ld.volatile.shared.b64 %3, [%4 + %9 + 640];\n"
        "@q ld.relaxed.gpu.global.b64 %0, [g];\n@q ld.relaxed.gpu.global.b64 %1, [g + 128];\n"
        "@q ld.relaxed.gpu.global.b64 %2, [g + 512];\n@q ld.relaxed.gpu.global.b64 %3, [g + 640];\n"
        "add.u32 i, i, 1;\n"
        "setp.lt.u32 p, i, %7;\n"
        "@p bra L_%=;\n"
        "D_%=:\n}\n"
        : "+l"(c[0]), "+l"(c[1]), "+l"(c[2]), "+l"(c[3])
        : "r"(a), "l"(p), "r"(tag), "n"(SPIN_LIMIT >> 4), "n"(NSPIN), "n"(OFF) : "memory");
}
__device__ __forceinline__ void ll_poll(u64 (&c)[4], const char* p, uint32_t tag) {
    unsigned it = 0;
    while (__any_sync(0xffffffffu, (((uint32_t)(c[0] >> 32) ^ tag) | ((uint32_t)(c[1] >> 32) ^ tag) |
                                    ((uint32_t)(c[2] >> 32) ^ tag) | ((uint32_t)(c[3] >> 32) ^ tag)) != 0) &&
           ++it < (SPIN_LIMIT >> 4))
        ll_fetch(c, p);
}
__device__ __forceinline__ void decode_alu(uint32_t& r0, uint32_t& r1, uint32_t& r2, uint32_t& r3, uint32_t w,
                                           const uint32_t (&lt)[8]) {
    const uint32_t s0 = w & 0x77777777u, s1 = s0 >> 16, w4 = w * 16;
    const uint32_t m0 = prmt(w4, w, 0xd9c8), m1 = prmt(w4, w, 0xfbea);
    const uint32_t l0 = (prmt(lt[0], lt[1], s0) & ~m0) | (prmt(lt[2], lt[3], s0) & m0);
    const uint32_t h0 = (prmt(lt[4], lt[5], s0) & ~m0) | (prmt(lt[6], lt[7], s0) & m0);
    const uint32_t l1 = (prmt(lt[0], lt[1], s1) & ~m1) | (prmt(lt[2], lt[3], s1) & m1);
    const uint32_t h1 = (prmt(lt[4], lt[5], s1) & ~m1) | (prmt(lt[6], lt[7], s1) & m1);
    r0 = prmt(l0, h0, 0x5140); r1 = prmt(l0, h0, 0x7362);
    r2 = prmt(l1, h1, 0x5140); r3 = prmt(l1, h1, 0x7362);
}
__device__ __forceinline__ void decode(uint32_t (&a)[16], const u64 (&c)[4], uint32_t tblv, const uint32_t (&lt)[8]) {
#pragma unroll
    for (int i = 0; i < 4; i++) {
        const int b = (i >> 1) * 8 + (i & 1);
        if (i < 4 - NALU) {
#pragma unroll
            for (int j = 0; j < 4; j++) a[b + 2 * j] = lds32(dp4a_u((uint32_t)c[i], (uint32_t)(TBLC * 4) << (8 * j), tblv));
        } else {
            decode_alu(a[b], a[b + 2], a[b + 4], a[b + 6], (uint32_t)c[i], lt);
        }
    }
}

__host__ __device__ constexpr int slot_of(int j) { return j < 16 ? j % 6 : (int)(0x6105342610532610ull >> (4 * (j - 16))) & 7; }
__host__ __device__ constexpr int slot_addr(int t, int s) {
    return t && (s < 2 || s == 6) ? (s == 6 ? 1 : 2 * s) * N1 * 128 : SLOT_OFF + s * SLOT_BYTES;
}
constexpr int JSTG = 25;
constexpr int STG_C0 = slot_addr(0, 6) - 2 * E0 * 128, STG_C1 = slot_addr(0, 4);
__host__ __device__ constexpr int loads_before(int j) {
    int n = 0;
    for (int i = 0; i < j; i++) n += slot_of(i) == slot_of(j);
    return n;
}
__host__ __device__ constexpr int uses_before(int j) {
    return loads_before(j) + (j >= 16 && (slot_of(j) == 4 || slot_of(j) == 5));
}
__host__ __device__ constexpr uint64_t prod_tbl(int j0) {
    uint64_t t = 0;
    for (int j = j0; j < j0 + 16; j++) t |= (uint64_t)(slot_of(j) | (((uses_before(j) + 1) & 1) << 3)) << (4 * (j - j0));
    return t;
}
__host__ __device__ constexpr uint64_t addr_tbl(int t) {
    uint64_t r = 0;
    for (int s = 0; s < NSLOTS; s++) r |= (uint64_t)(slot_addr(t, s) / 1024) << (8 * s);
    return r;
}
__host__ __device__ constexpr int dec_upto(int j) { return j < 14 ? j + 1 + (j >= RAMP1) + (j >= RAMP2) : j + 2 + (j >= RAMP3); }
__host__ __device__ constexpr bool ramp_first(int d) {
    return d == RAMP1 + 1 || d == RAMP2 + 2 || d == RAMP3 + 2;
}
__host__ __device__ constexpr bool read_early(int d) {
    return d > RLATE && d < NSL && !ramp_first(d - 2) && !ramp_first(d - 3) && d != 18 && d != 20 && d != 21;
}
__host__ __device__ constexpr bool get_early(int d) { return ramp_first(d); }

__device__ __forceinline__ void fence_a(uint32_t (&a)[16]) {
#pragma unroll
    for (int i = 0; i < 16; i++) asm volatile("" : "+r"(a[i])::"memory");
}
template <int J, int N, int COL>
__device__ __forceinline__ void mma_slice(float (&acc)[N0 / 2], uint32_t (&a)[4][16]) {
    constexpr int off = (slot_addr(J / KSTEPS, slot_of(J)) + COL * 128) / 16, b = J % 4;
    constexpr uint64_t d0 = make_desc(SMEM_BASE);
    WG<N, COL / 2, (J % KSTEPS) != 0, N0 / 2>::mma(acc, a[b][0], a[b][1], a[b][2], a[b][3], d0 + off);
    WG<N, COL / 2, true, N0 / 2>::mma(acc, a[b][4], a[b][5], a[b][6], a[b][7], d0 + (off + 2));
    WG<N, COL / 2, true, N0 / 2>::mma(acc, a[b][8], a[b][9], a[b][10], a[b][11], d0 + (off + 4));
    WG<N, COL / 2, true, N0 / 2>::mma(acc, a[b][12], a[b][13], a[b][14], a[b][15], d0 + (off + 6));
}
template <int N> __device__ __forceinline__ void rename_acc(float (&acc)[N0 / 2]) {
#pragma unroll
    for (int i = 0; i < N / 2; i++) asm volatile("mov.b32 %0, %1;" : "=f"(acc[i]) : "f"(acc[i]) : "memory");
}
template <int N, int COL, bool FENCE>
__device__ __forceinline__ void stage_out(float (&acc)[N0 / 2], uint32_t sa, float s0, float s1) {
#pragma unroll
    for (int i = COL / 2; i < (COL + N) / 2; i++) asm volatile("" : "+f"(acc[i])::"memory");
#pragma unroll
    for (int j = COL / 8; j + 1 < (COL + N) / 8; j += 2) {
        const uint32_t r0 = pack_bf16x2(acc[4 * j + 0] * s0, acc[4 * j + 1] * s0);
        const uint32_t r1 = pack_bf16x2(acc[4 * j + 2] * s1, acc[4 * j + 3] * s1);
        const uint32_t r2 = pack_bf16x2(acc[4 * j + 4] * s0, acc[4 * j + 5] * s0);
        const uint32_t r3 = pack_bf16x2(acc[4 * j + 6] * s1, acc[4 * j + 7] * s1);
        asm volatile("stmatrix.sync.aligned.m8n8.x4.trans.shared.b16 [%0], {%1, %2, %3, %4};"
                     ::"r"(sa + j * 1024), "r"(r0), "r"(r1), "r"(r2), "r"(r3) : "memory");
    }
    if constexpr ((N / 8) & 1) {
        constexpr int j = (COL + N) / 8 - 1;
        const uint32_t r0 = pack_bf16x2(acc[4 * j + 0] * s0, acc[4 * j + 1] * s0);
        const uint32_t r1 = pack_bf16x2(acc[4 * j + 2] * s1, acc[4 * j + 3] * s1);
        asm volatile("stmatrix.sync.aligned.m8n8.x2.trans.shared.b16 [%0], {%1, %2};"
                     ::"r"(sa + j * 1024), "r"(r0), "r"(r1) : "memory");
    }
    if constexpr (FENCE) asm volatile("fence.proxy.async.shared::cta;" ::: "memory");
}

struct Maps { CUtensorMap m[8]; };

__global__ void __cluster_dims__(2, 1, 1) __launch_bounds__(NUM_THREADS, 1)
nf4_gemm_kernel(const int* __restrict__ qw, u64* __restrict__ ll, unsigned* __restrict__ epoch,
                const __nv_bfloat16* __restrict__ lut, const __nv_bfloat16* __restrict__ scales,
                const __grid_constant__ Maps tm) {
    extern __shared__ __align__(1024) uint8_t smem_raw[];
    const uint32_t t_start = clock32();
    const int lane = threadIdx.x & 31;
    if (threadIdx.x < 32)
        asm volatile("prefetch.global.L2 [%0];" ::"l"(add_off(qw, unit_src(blockIdx.x / W1_FG, blockIdx.x % W1_FG) + lane * (kN * 4))) : "memory");
    const int warp = __shfl_sync(0xffffffffu, threadIdx.x >> 5, 0);
    const uint32_t sb = smem_u32(smem_raw);
    const uint32_t bar_full = sb + BAR_OFF;
    const uint32_t bar_empty = bar_full + NSLOTS * 8;
    const uint32_t bar_tbl = bar_empty + NSLOTS * 8;
    const uint32_t bar_code = bar_tbl + 8;
    const uint32_t bar_stg = bar_code + 8;
    const int crank = blockIdx.x & 1, cluster = blockIdx.x >> 1;

    if (warp != 8) cluster_arrive_relaxed();
    if (warp < 8) {
        const int wg = warp >> 2;
        const uint32_t tag = ld_ca_u32(epoch + lane);
        const uint32_t lv = ldg_u16(reinterpret_cast<const unsigned short*>(lut) + (lane & 15));
        int fp0, fp1, mm;
        tile0_of(cluster, fp0, mm);
        tile1_of(cluster, fp1, mm);
        const int ft0 = fp0 * 2 + crank, ft1 = fp1 * 2 + crank;
        const unsigned short* sc16 = reinterpret_cast<const unsigned short*>(scales) + warp * 16 + (lane >> 2);
        uint32_t sc0 = ldg_u16(sc16 + ft0 * FT), sc0h = ldg_u16(sc16 + ft0 * FT + 8);
        uint32_t sc1 = ldg_u16(sc16 + ft1 * FT), sc1h = ldg_u16(sc16 + ft1 * FT + 8);
        {
            constexpr int EPS = 128 / TBLC;
#pragma unroll
            for (int k = 0; k < 32 / EPS; k++) {
                const int e = warp * 32 + k * EPS + lane / (TBLC / 4);
                const uint32_t v = __shfl_sync(0xffffffffu, lv, e & 15) | (__shfl_sync(0xffffffffu, lv, e >> 4) << 16);
                asm volatile("st.shared.v4.u32 [%0], {%1, %1, %1, %1};"
                             ::"r"(sb + TBL_OFF + warp * (TBLC * 128) + k * 512 + lane * 16), "r"(v) : "memory");
            }
        }
        asm volatile("setmaxnreg.inc.sync.aligned.u32 %0;" ::"n"(CREGS));
        cluster_wait();
        mbar_arrive(bar_tbl);
        TS(132);
        sc0 |= sc0h << 16;
        sc1 |= sc1h << 16;
        const char* ll0 = keep(reinterpret_cast<const char*>(ll) + (ft0 * (KSTEPS * 8192) + warp * 1024 + lane), 0);
        const char* ll1 = keep(reinterpret_cast<const char*>(ll) + (ft1 * (KSTEPS * 8192) + warp * 1024 + lane), 0);
        const uint32_t cbuf = sb + COD_OFF + warp * 1024;
        const uint32_t tblv = keep(sb + TBL_OFF + (lane % TBLC) * 4, lane);
        const uint32_t cempty = keep(lane < 2 ? mapa(bar_empty, lane) : 0, lane);
        const uint32_t sa0 = keep(sb + (((lane >> 4) * 8 + (lane & 7)) * 128) +
                                  ((((warp & 3) * 2 + ((lane >> 3) & 1)) ^ (lane & 7)) << 4), lane);
        uint32_t lt[8];
        {
            const uint32_t p01 = __shfl_sync(0xffffffffu, lv, 4 * lane) | (__shfl_sync(0xffffffffu, lv, 4 * lane + 1) << 16);
            const uint32_t p23 = __shfl_sync(0xffffffffu, lv, 4 * lane + 2) | (__shfl_sync(0xffffffffu, lv, 4 * lane + 3) << 16);
            const uint32_t pl = prmt(p01, p23, lane & 4 ? 0x7531 : 0x6420);
#pragma unroll
            for (int i = 0; i < 8; i++) lt[i] = __shfl_sync(0xffffffffu, pl, i & 1 ? i : i + (lane & 24));
        }
        uint32_t a[4][16];
        float acc[N0 / 2];

        auto src = [&](auto dc) {
            constexpr int D = decltype(dc)::value;
            return (D < KSTEPS ? ll0 : ll1) + (D % KSTEPS) * 8192;
        };
        u64 c[4];
        const uint32_t aw = keep(cbuf + lane_unit(lane), lane);
        auto fetch = [&](auto dc) {
            constexpr int D = decltype(dc)::value;
            if constexpr (D < NGATE) delay_until(t_start, gate_time(D));
            if constexpr (D < NSL) ll_copy(cbuf + (D & 1) * 8192, src(dc), bar_code);
        };
        auto get = [&](auto dc) {
            constexpr int D = decltype(dc)::value;
            if constexpr (D + 1 <= FLATE) fetch(IC<D + 1>{});
            if constexpr (!read_early(D)) ll_read(c, aw + (D & 1) * 8192);
            ll_check<(D & 1) * 8192>(c, aw, src(dc), tag + D % KSTEPS);
            if constexpr (D + 2 >= NGATE) fetch(IC<D + 2>{});
        };
        auto dec = [&](auto dc) {
            constexpr int D = decltype(dc)::value;
            decode(a[D % 4], c, tblv, lt);
            if constexpr (D + 2 > FLATE && D + 2 < NGATE) fetch(IC<D + 2>{});
            if constexpr (read_early(D + 1)) ll_read(c, aw + ((D + 1) & 1) * 8192);
            if constexpr (get_early(D + 1)) get(IC<D + 1>{});
        };
        auto wait_full = [&](auto jc) {
            constexpr int J = decltype(jc)::value;
            mbar_wait(bar_full + slot_of(J) * 8, loads_before(J) & 1);
        };
        auto release = [&](auto jc) {
            constexpr int J = decltype(jc)::value;
            if constexpr (J <= JSTG + 1) mbar_arrive_pair(cempty + slot_of(J) * 8, cempty);
        };
        auto step = [&](auto jc) {
            constexpr int J = decltype(jc)::value, D = dec_upto(J - 1) + 1;
            fence_a(a[J % 4]);
            wgmma_fence();
            mma_slice<J, (J < KSTEPS ? N0 : N1), 0>(acc, a);
            wgmma_commit();
            TS(J);
            if constexpr (!get_early(D)) get(IC<D>{});
            if constexpr (J >= NEARLY) wait_full(IC<J + 1>{});
            wgmma_wait<1>();
            if constexpr (J != 0 && J != 18) release(IC<J - 1>{});
            dec(IC<D>{});
            if constexpr (dec_upto(J) > D) { get(IC<D + 1>{}); dec(IC<D + 1>{}); }
            if constexpr (J < NEARLY) wait_full(IC<J + 1>{});
        };
        static_assert(FLATE >= 1 && FLATE < NGATE && RLATE >= FLATE && RLATE < RAMP1 && RAMP1 + 2 < RAMP2 && RAMP2 < 14 &&
                      RAMP3 > 20 && RAMP3 < 28, "code schedule");
        static_assert(slot_of(10) == 4 && slot_of(11) == 5 && uses_before(11) == 1 && STG_C1 + 2 * E1 * 128 <= STG_C0, "staging");

        mbar_wait(bar_tbl, 0);
        TS(133);
        delay_until(t_start, gate_time(0));
        ll_fetch(c, src(IC<0>{}) + (aw & 1023));
        fetch(IC<1>{});
        ll_poll(c, src(IC<0>{}) + (aw & 1023), tag);
        dec(IC<0>{});
        TS(134);
        wait_full(IC<0>{});
        TS(137);
        static_for<0, 14>(step);
        {
            const float s0 = __uint_as_float(sc0 << 16), s1 = __uint_as_float(sc0 & 0xffff0000u);
            const uint32_t sa = sa0 + STG_C0 + wg * (E0 * 128), sc = sa0 + STG_C1 - E0 * 128 + wg * (E1 * 128);
            auto group = [&](auto jc, auto nc, auto cc) {
                fence_a(a[decltype(jc)::value % 4]);
                wgmma_fence();
                mma_slice<decltype(jc)::value, decltype(nc)::value, decltype(cc)::value>(acc, a);
                wgmma_commit();
            };
            wait_full(IC<15>{});
            TS(140);
            wgmma_wait<0>();
            rename_acc<N0>(acc);
            group(IC<14>{}, IC<E0>{}, IC<0>{});
            release(IC<13>{});
            get(IC<17>{});
            mbar_wait(bar_empty + 5 * 8, 1);
            group(IC<15>{}, IC<E0>{}, IC<0>{});
            TS(14);
            dec(IC<17>{});
            TS(141);
            group(IC<14>{}, IC<E1>{}, IC<E0>{});
            TS(15);
            wgmma_wait<1>();
            stage_out<EI, 0, false>(acc, sa, s0, s1);
            group(IC<15>{}, IC<E1>{}, IC<E0>{});
            TS(142);
            wait_full(IC<16>{});
            wgmma_wait<1>();
            release(IC<14>{});
            TS(143);
            stage_out<E0 - EI, EI, true>(acc, sa, s0, s1);
            mbar_arrive(bar_stg + wg * 8);
            TS(144);
            group(IC<16>{}, IC<S0>{}, IC<0>{});
            wait_full(IC<17>{});
            wgmma_wait<1>();
            release(IC<15>{});
            TS(16);
            stage_out<EI, E0, false>(acc, sc, s0, s1);
            group(IC<17>{}, IC<S0>{}, IC<0>{});
            TS(128);
            stage_out<E1 - EI, E0 + EI, true>(acc, sc, s0, s1);
            mbar_arrive(bar_stg + 16 + wg * 8);
            TS(129);
            group(IC<16>{}, IC<S1>{}, IC<S0>{});
            get(IC<18>{}); dec(IC<18>{});
            group(IC<17>{}, IC<S1>{}, IC<S0>{});
            TS(17);
            get(IC<19>{});
            wait_full(IC<18>{});
            wgmma_wait<1>();
            release(IC<16>{});
            dec(IC<19>{});
            TS(145);
            wgmma_wait<0>();
            rename_acc<N1>(acc);
            release(IC<17>{});
            TS(146);
        }
        static_for<18, NSL - 4>(step);
        {
            constexpr int J0 = NSL - 4;
            const float s0 = __uint_as_float(sc1 << 16), s1 = __uint_as_float(sc1 & 0xffff0000u);
            const uint32_t sa = sa0 + (wg ? slot_addr(1, slot_of(JSTG + 1)) : slot_addr(1, slot_of(JSTG)));
            wait_full(IC<J0 + 1>{}); wait_full(IC<J0 + 2>{});
            fence_a(a[0]); fence_a(a[1]); fence_a(a[2]);
            TS(160);
            wgmma_wait<0>();
            rename_acc<N1>(acc);
            wgmma_fence();
            mma_slice<J0, CA, 0>(acc, a);
            TS(J0);
            release(IC<J0 - 1>{});
            get(IC<NSL - 1>{}); dec(IC<NSL - 1>{});
            asm volatile("{\n.reg .pred p;\nelect.sync _|p, 0xffffffff;\n"
                         "@p mbarrier.arrive.expect_tx.shared::cta.b64 _, [%0], %1;\n}\n" ::"r"(bar_code), "n"((NSL - 1) * 1024) : "memory");
            wgmma_fence();
            mma_slice<J0 + 1, CA, 0>(acc, a);
            mma_slice<J0 + 2, CA, 0>(acc, a);
            wait_full(IC<NSL - 1>{});
            fence_a(a[3]);
            wgmma_fence();
            mma_slice<J0 + 3, CA, 0>(acc, a);
            wgmma_commit();
            static_for<1, 5>([&](auto cc) {
                constexpr int C = decltype(cc)::value;
                constexpr int N = C == 1 ? CA : C == 2 ? CB : CC, COL = C == 3 ? 2 * CA + CB : C * CA;
                constexpr int NP = C <= 2 ? CA : C == 3 ? CB : CC, COLP = C == 4 ? 2 * CA + CB : (C - 1) * CA;
                if constexpr (C < 4) {
                    wgmma_fence();
                    mma_slice<J0, N, COL>(acc, a);
                    wgmma_commit();
                    if constexpr (C == 1)
                        mbar_wait(bar_empty + (wg ? slot_of(JSTG + 1) : slot_of(JSTG)) * 8, (wg ? uses_before(JSTG + 1) : uses_before(JSTG)) & 1);
                    wgmma_wait<1>();
                } else {
                    wgmma_wait<0>();
                    TS(130);
                }
                TS(160 + C * 4);
                stage_out<NP, COLP, true>(acc, sa, s0, s1);
                bar_arrive_id(5 + C + wg * 4, 160);
                TS(160 + C * 4 + 1);
                if constexpr (C < 4) {
                    wgmma_fence();
                    static_for<J0 + 1, NSL>([&](auto jc) { mma_slice<decltype(jc)::value, N, COL>(acc, a); });
                    wgmma_commit();
                    TS(J0 + C);
                }
            });
            TS(131);
        }
    } else {
      if (warp >= 9) {
        {
            const int pw = warp - 9;
            int u = pw * NUM_CTAS + blockIdx.x;
            uint32_t q = u / W1_FG, fg = u % W1_FG;
            const int* qwk = keep(add_off(qw, lane_src(lane)), lane);
            u64* llk = keep(add_off(ll, lane_dst(lane)), lane);
            const unsigned* ep = epoch + lane;
            asm volatile("setmaxnreg.dec.sync.aligned.u32 %0;" ::"n"(504 - 2 * CREGS));
            const uint32_t tag = ld_ca_u32(ep);
            if (pw > 0) delay_until(t_start, DLY_R0 + pw * DLY_R);
            uint4 v[8];
            load_unit(v, add_off(qwk, unit_src(q, fg)));
#pragma unroll 1
            for (;;) {
                u64* dst = add_off(llk, unit_dst(q, fg));
                const uint32_t sl = q >> 1;
                static_assert(RSTOP % NUM_AUX == 0, "pack rounds");
                u += u < (RSTOP - 1) * NUM_CTAS ? NUM_AUX * NUM_CTAS : pw == 2 ? NUM_UNITS : 2 * NUM_CTAS;
                unit_pos(min(u, NUM_UNITS - 1), q, fg);
                const int* p = add_off(qwk, unit_src(q, fg));
                uint32_t e[4], o[4], w[4];
                pk_gather(e, o, v);
#pragma unroll
                for (int k = 0; k < 4; k++)
                    asm("lop3.b32 %0, %1, %2, 0x0f0f0f0f, 0xe4;" : "=r"(w[k]) : "r"(e[k]), "r"(o[k] << 4));
                ll_store2(dst, w[0], w[1], tag + sl);
                ll_store2((u64*)((uint64_t)dst ^ 320), w[2], w[3], tag + sl);
                if (u >= NUM_UNITS) break;
                load_unit(v, p);
            }
        }
        const CUtensorMap* maps = keep(&tm.m[3] + lane, 0);
        named_bar_arrive<4, 128>();
        cluster_wait();
        int fp, m0;
        if (warp == 11) {
            tile0_of(cluster, fp, m0);
            const int f0 = (fp * 2 + crank) * FT;
#pragma unroll 1
            for (int ch = 0; ch < 2; ch++) {
                const uint32_t src = sb + (ch ? STG_C1 : STG_C0);
                const int rows = ch ? E1 : E0, step = ch ? BX1 : BX0;
                int h = 0;
#pragma unroll 1
                for (unsigned it = 0; it < 16 * SPIN_LIMIT && !mbar_test(bar_stg + ch * 16 + h * 8, 0); it++) { h ^= 1; __nanosleep(20); }
#pragma unroll 1
                for (int k = 0; k < 2; k++, h ^= 1) {
                    mbar_wait(bar_stg + ch * 16 + h * 8, 0);
#pragma unroll 1
                    for (int r = 0; r < rows; r += step) {
                        asm volatile("{\n.reg .pred p;\nelect.sync _|p, 0xffffffff;\n"
                                     "@p cp.async.bulk.tensor.2d.global.shared::cta.bulk_group [%0, {%2, %3}], [%1];\n"
                                     "cp.async.bulk.commit_group;\ncp.async.bulk.wait_group.read 1;\n}\n"
                                     ::"l"(maps + 3 + ch), "r"(src + (h * rows + r) * 128), "r"(f0 + h * 64), "r"(m0 + ch * E0 + r)
                                     : "memory");
                    }
                }
                asm volatile("cp.async.bulk.wait_group.read 0;" ::: "memory");
                __syncwarp();
                if (lane < 2) mbar_arrive_cluster_n(mapa(bar_empty + (5 - ch) * 8, lane), 8);
                TSG(604 + ch * 2);
            }
        } else {
            const int wg = warp - 9;
            tile1_of(cluster, fp, m0);
            const int f0 = (fp * 2 + crank) * FT + wg * 64;
            const uint32_t src = sb + (wg ? slot_addr(1, slot_of(JSTG + 1)) : slot_addr(1, slot_of(JSTG)));
#pragma unroll 1
            for (int ch = 0; ch < 4; ch++) {
                const int r0 = ch < 3 ? ch * CA : 2 * CA + CB;
                const CUtensorMap* map = maps + max(ch - 1, 0);
                bar_sync_id(6 + wg * 4 + ch, 160);
                if (lane == 0) {
                    tma_store_2d(map, src + r0 * 128, f0, m0 + r0);
                    asm volatile("cp.async.bulk.commit_group;" ::: "memory");
                }
            }
            if (lane == 0) asm volatile("cp.async.bulk.wait_group.read 0;" ::: "memory");
            __syncwarp();
            TSG(600 + wg * 2);
        }
      } else {
        asm volatile("setmaxnreg.dec.sync.aligned.u32 %0;" ::"n"(504 - 2 * CREGS));
        if ((sb & 0xFFFFFF) != SMEM_BASE) __trap();
        if (lane == 0) {
            for (int s = 0; s < NSLOTS; s++) {
                mbar_init(bar_full + s * 8, 1);
                mbar_init(bar_empty + s * 8, 16);
            }
            mbar_init(bar_tbl, 256);
            mbar_init(bar_code, 8);
            for (int i = 0; i < 4; i++) mbar_init(bar_stg + i * 8, 128);
            asm volatile("fence.mbarrier_init.release.cluster;" ::: "memory");
        }
        __syncwarp();
        cluster_arrive_relaxed();
        const CUtensorMap* maps = keep(&tm.m[0] + lane, 0);
        unsigned* epk = keep(epoch + lane, 0);
        if (lane == 0) prefetch_map(maps + crank);
        TSG(512);
        int fp, m0;
        tile0_of(cluster, fp, m0);
        cluster_wait();
#pragma unroll 1
        for (int t = 0; t < 2; t++) {
            const int lo = t == 0 ? 120 : 104, row = m0 + crank * lo;
            const CUtensorMap* map = maps + (t ? 2 : crank);
            const uint32_t bytes = (t ? N1 : N0) * 128, dst = sb + crank * lo * 128;
            uint64_t tbl = t ? prod_tbl(16) : prod_tbl(0);
            const uint64_t adr = t ? addr_tbl(1) : addr_tbl(0);
#pragma unroll 1
            for (int ks = 0; ks < KSTEPS; ks++, tbl >>= 4) {
                const uint32_t slot = (uint32_t)tbl & 7;
                if (t == 0 && ks > 0 && ks < 6) delay_until(t_start, DLY_X0 + ks * DLY_XS);
                mbar_wait(bar_empty + slot * 8, ((uint32_t)tbl >> 3) & 1);
                asm volatile(
                    "{\n.reg .pred p;\nelect.sync _|p, 0xffffffff;\n"
                    "@p mbarrier.arrive.expect_tx.shared::cta.b64 _, [%2], %5;\n"
                    "@p cp.async.bulk.tensor.2d.shared::cluster.global.mbarrier::complete_tx::bytes.multicast::cluster"
                    " [%0], [%1, {%3, %4}], [%2], %6;\n}\n"
                    ::"r"(dst + (((uint32_t)(adr >> (8 * slot)) & 255) << 10)), "l"(map), "r"(bar_full + slot * 8), "r"(ks * BK), "r"(row), "r"(bytes),
                    "h"((uint16_t)3) : "memory");
                TSG(514 + (t * 18 + ks) * 2);
            }
            tile1_of(cluster, fp, m0);
            if (t == 0 && lane >= 2 && lane < 8) prefetch_map(maps + lane);
        }
        named_bar_sync<4, 128>();
        const uint32_t tag = ld_ca_u32(epk + lane);
        unsigned old = 0;
        if (lane == 0) old = atomicAdd(epk + 32, tag != 0 ? 1u : 0u);
        if (__shfl_sync(0xffffffffu, old, 0) == NUM_CTAS - 1) {
            if (lane == 0) epk[32] = 0;
            epk[lane] = tag == 0xfffffff0u ? 16 : tag + 16;
        }
        mbar_wait(bar_code, 0);
      }
    }
}

__global__ void generic_kernel(const __nv_bfloat16* __restrict__ x, const int* __restrict__ qw,
                               const __nv_bfloat16* __restrict__ lut, const __nv_bfloat16* __restrict__ scales,
                               __nv_bfloat16* __restrict__ out, int M, int N, int K, int G) {
    const int n = blockIdx.x * blockDim.x + threadIdx.x;
    const int m = blockIdx.y;
    if (n >= N) return;
    float acc = 0.f;
    for (int k = 0; k < K; k++) {
        const float l = __bfloat162float(lut[qw[(size_t)k * N + n] & 15]);
        const float s = __bfloat162float(scales[(size_t)(k / G) * N + n]);
        const float w = __bfloat162float(__float2bfloat16_rn(l * s));
        acc += __bfloat162float(x[(size_t)m * K + k]) * w;
    }
    out[(size_t)m * N + n] = __float2bfloat16_rn(acc);
}

typedef CUresult (*PFN_encodeTiled)(CUtensorMap*, CUtensorMapDataType, cuuint32_t, void*, const cuuint64_t*,
                                    const cuuint64_t*, const cuuint32_t*, const cuuint32_t*, CUtensorMapInterleave,
                                    CUtensorMapSwizzle, CUtensorMapL2promotion, CUtensorMapFloatOOBfill);

bool make_map_2d(PFN_encodeTiled fn, CUtensorMap* map, void* base, uint64_t inner, uint64_t outer, uint32_t box_inner,
                 uint32_t box_outer) {
    cuuint64_t dims[2] = {inner, outer};
    cuuint64_t strides[1] = {inner * 2};
    cuuint32_t box[2] = {box_inner, box_outer};
    cuuint32_t estr[2] = {1, 1};
    return fn(map, CU_TENSOR_MAP_DATA_TYPE_BFLOAT16, 2, base, dims, strides, box, estr, CU_TENSOR_MAP_INTERLEAVE_NONE,
              CU_TENSOR_MAP_SWIZZLE_128B, CU_TENSOR_MAP_L2_PROMOTION_L2_128B,
              CU_TENSOR_MAP_FLOAT_OOB_FILL_NONE) == CUDA_SUCCESS;
}

}

extern "C" void kernel_launch(void* const* d_in, const int* in_sizes, int n_in, void* d_out, int out_size) {
    const __nv_bfloat16* x = (const __nv_bfloat16*)d_in[0];
    const int* qw = (const int*)d_in[1];
    const __nv_bfloat16* lut = (const __nv_bfloat16*)d_in[2];
    const __nv_bfloat16* scales = (const __nv_bfloat16*)d_in[3];
    __nv_bfloat16* out = (__nv_bfloat16*)d_out;

    const double Kd = sqrt((double)in_sizes[0] * (double)in_sizes[1] / (double)out_size);
    const int K = (int)(Kd + 0.5);
    const int M = in_sizes[0] / K, N = in_sizes[1] / K;
    const int ng = in_sizes[3] / N;
    const int G = K / ng;

    bool fast = (M == kM && N == kN && K == kK && ng == 1 && in_sizes[2] >= 16);
    PFN_encodeTiled enc = nullptr;
    Maps tm;
    void *ll = nullptr, *epoch = nullptr;
    if (fast) {
        cudaDriverEntryPointQueryResult qres;
        void* fp = nullptr;
        if (cudaGetDriverEntryPoint("cuTensorMapEncodeTiled", &fp, cudaEnableDefault, &qres) != cudaSuccess || !fp) fast = false;
        enc = (PFN_encodeTiled)fp;
    }
    static_assert(2 * CA + CB + CC == N1 && S0 <= E0, "chunks");
    if (fast) {
        fast = make_map_2d(enc, &tm.m[0], (void*)x, kK, kM, BK, 120) &&
               make_map_2d(enc, &tm.m[1], (void*)x, kK, kM, BK, 112) &&
               make_map_2d(enc, &tm.m[2], (void*)x, kK, kM, BK, 104) &&
               make_map_2d(enc, &tm.m[3], (void*)out, kN, kM, 64, CA) &&
               make_map_2d(enc, &tm.m[4], (void*)out, kN, kM, 64, CB) &&
               make_map_2d(enc, &tm.m[5], (void*)out, kN, kM, 64, CC) &&
               make_map_2d(enc, &tm.m[6], (void*)out, kN, kM, 64, BX0) &&
               make_map_2d(enc, &tm.m[7], (void*)out, kN, kM, 64, BX1) &&
               cudaGetSymbolAddress(&ll, g_ll) == cudaSuccess && cudaGetSymbolAddress(&epoch, g_epoch) == cudaSuccess;
    }
    cudaLaunchConfig_t cfg = {};
    cfg.gridDim = dim3(NUM_CTAS);
    cfg.blockDim = dim3(NUM_THREADS);
    cfg.dynamicSmemBytes = SMEM_TOTAL;
    cfg.stream = cudaStreamPerThread;
    if (fast) {
        int nclusters = 0;
        fast = cudaFuncSetAttribute(nf4_gemm_kernel, cudaFuncAttributeMaxDynamicSharedMemorySize, SMEM_TOTAL) == cudaSuccess &&
               cudaOccupancyMaxActiveClusters(&nclusters, nf4_gemm_kernel, &cfg) == cudaSuccess &&
               nclusters >= NUM_CTAS / 2;
    }
    if (!fast) {
        generic_kernel<<<dim3((N + 127) / 128, M), 128>>>(x, qw, lut, scales, out, M, N, K, G);
        return;
    }
    cudaLaunchKernelEx(&cfg, nf4_gemm_kernel, qw, (u64*)ll, (unsigned*)epoch, lut, scales, tm);
}
```

```cpp
#include <cuda_runtime.h>
#include <cuda_bf16.h>
#include <cuda.h>
#include <stdint.h>
#include <stdio.h>
#include <math.h>

namespace {

constexpr int kM = 2048, kN = 3584, kK = 1024;
constexpr int FT = 128;
constexpr int N0 = 232, N1 = 208;
constexpr int BK = 64, KSTEPS = kK / BK;
constexpr int NSL = 2 * KSTEPS;
constexpr int NSLOTS = 7;
constexpr int SLOT_BYTES = N0 * 128;
constexpr int SLOT_OFF = 3 * N1 * 128 - 2 * SLOT_BYTES;
#define TBLC 16
constexpr int TBL_OFF = SLOT_OFF + 6 * SLOT_BYTES;
constexpr int COD_OFF = TBL_OFF + TBLC * 1024;
#define NBUF 2
constexpr int BAR_OFF = COD_OFF + NBUF * 8192;
constexpr int SMEM_TOTAL = BAR_OFF + 256;
constexpr int NUM_THREADS = 384;
constexpr int NUM_CTAS = 132;
constexpr int NUM_AUX = 3;
constexpr int CREGS = 224;
constexpr int NQ = kK / 32, NUM_UNITS = NQ * (kN / 32);
constexpr int W1_FG = 64, W2_FG = kN / 32 - W1_FG;
#define DLY_R0 200
#define DLY_R 400
#define DLY_X0 1000
#define DLY_XS 900
#define DLY_POLL 2600
#define DLY_P1 3200
#define DLY_PS 700
#define NGATE 8
#define FLATE 3
#define RLATE 4
#define NEARLY 4
#define RAMP1 8
#define RAMP2 12
#define RAMP3 24
#define NSPIN 24
#define NALU 2
#define RSTOP 18
#define BX0 24
#define BX1 8
#define FR1 (NBUF > 2 ? 12 : 99)
#define RL2 21
#define RL3 99
#define EI 64
constexpr int E0 = 120, E1 = N0 - E0, S0 = 112, S1 = N1 - S0;
#define CHK 0x4688
__host__ __device__ constexpr int chunk_n(int c) { return ((CHK >> (4 * c)) & 15) * 8; }
__host__ __device__ constexpr int chunk_col(int c) { return c ? chunk_col(c - 1) + chunk_n(c - 1) : 0; }
constexpr int NCH = CHK > 0xfffff ? 6 : CHK > 0xffff ? 5 : CHK > 0xfff ? 4 : 3;
static_assert(chunk_col(NCH) == N1 && S0 <= E0, "chunks");
constexpr unsigned SPIN_LIMIT = 1u << 20;

__device__ __align__(1024) unsigned long long g_ll[(size_t)(kN / FT) * NQ * FT * 4];
__device__ __align__(256) unsigned int g_epoch[64] = {16, 16, 16, 16, 16, 16, 16, 16, 16, 16, 16, 16, 16, 16, 16, 16,
                                                      16, 16, 16, 16, 16, 16, 16, 16, 16, 16, 16, 16, 16, 16, 16, 16};

#define TS(idx) do {} while (0)
#define TSW(idx) do {} while (0)
#define TSG(idx) do {} while (0)

template <int I> struct IC { static constexpr int value = I; };
template <int B, int E, class F> __device__ __forceinline__ void static_for(F&& f) {
    if constexpr (B < E) { f(IC<B>{}); static_for<B + 1, E>(f); }
}

__device__ __forceinline__ uint32_t smem_u32(const void* p) { return (uint32_t)__cvta_generic_to_shared(p); }
__device__ __forceinline__ uint32_t keep(uint32_t v, int lane) {
    asm volatile("shfl.sync.idx.b32 %0, %0, %1, 0x1f, 0xffffffff;" : "+r"(v) : "r"(lane));
    return v;
}
template <class T> __device__ __forceinline__ T* keep(T* p, int lane) {
    const uint64_t v = (uint64_t)p;
    return (T*)(((uint64_t)keep((uint32_t)(v >> 32), lane) << 32) | keep((uint32_t)v, lane));
}
__device__ __forceinline__ void mbar_init(uint32_t bar, uint32_t count) {
    asm volatile("mbarrier.init.shared::cta.b64 [%0], %1;" ::"r"(bar), "r"(count) : "memory");
}
__device__ __forceinline__ uint32_t clock32() { uint64_t c; asm volatile("mov.u64 %0, %%clock64;" : "=l"(c)); return (uint32_t)c; }
__device__ __forceinline__ void mbar_arrive(uint32_t bar) {
    asm volatile("mbarrier.arrive.shared::cta.b64 _, [%0];" ::"r"(bar) : "memory");
}
__device__ __forceinline__ uint32_t mapa(uint32_t a, uint32_t rank) {
    uint32_t r;
    asm("mapa.shared::cluster.u32 %0, %1, %2;" : "=r"(r) : "r"(a), "r"(rank));
    return r;
}
__device__ __forceinline__ void mbar_arrive_pair(uint32_t cbar, uint32_t base) {
    asm volatile("{\n.reg .pred p;\nsetp.ne.u32 p, %1, 0;\n@p mbarrier.arrive.shared::cluster.b64 _, [%0];\n}\n"
                 ::"r"(cbar), "r"(base) : "memory");
}
__device__ __forceinline__ void mbar_arrive_cluster_n(uint32_t cbar, uint32_t n) {
    asm volatile("mbarrier.arrive.shared::cluster.b64 _, [%0], %1;" ::"r"(cbar), "r"(n) : "memory");
}
__device__ __forceinline__ void delay_until(uint32_t t0, int clks) {
    while (__any_sync(0xffffffffu, (int)(clock32() - t0) < clks)) {}
}
__device__ __forceinline__ bool mbar_test(uint32_t bar, uint32_t parity) {
    uint32_t ok;
    asm volatile("{\n.reg .pred p;\nmbarrier.test_wait.parity.shared::cta.b64 p, [%1], %2;\nvote.sync.all.pred p, p, 0xffffffff;\nselp.u32 %0, 1, 0, p;\n}\n"
                 : "=r"(ok) : "r"(bar), "r"(parity) : "memory");
    return ok != 0;
}
__device__ __forceinline__ void mbar_wait(uint32_t bar, uint32_t parity) {
    asm volatile(
        "{\n.reg .pred p;\n.reg .u32 i;\n"
        "mbarrier.try_wait.parity.shared::cta.b64 p, [%0], %1;\n"
        "@p bra D_%=;\n"
        "mov.u32 i, 0;\n"
        "L_%=:\n"
        "mbarrier.try_wait.parity.shared::cta.b64 p, [%0], %1;\n"
        "@p bra D_%=;\n"
        "add.u32 i, i, 1;\n"
        "setp.lt.u32 p, i, %2;\n"
        "@p bra L_%=;\n"
        "D_%=:\n}\n"
        ::"r"(bar), "r"(parity), "n"(SPIN_LIMIT) : "memory");
}
__device__ __forceinline__ void prefetch_map(const CUtensorMap* map) {
    asm volatile("prefetch.tensormap [%0];" ::"l"(map) : "memory");
}
constexpr uint32_t SMEM_BASE = 1024;
__host__ __device__ constexpr uint64_t make_desc(uint32_t saddr) {
    return (uint64_t)((saddr & 0x3FFFF) >> 4) | ((uint64_t)1 << 16) | ((uint64_t)(1024 >> 4) << 32) | ((uint64_t)1 << 62);
}
__device__ __forceinline__ void wgmma_fence() { asm volatile("wgmma.fence.sync.aligned;" ::: "memory"); }
__device__ __forceinline__ void wgmma_commit() { asm volatile("wgmma.commit_group.sync.aligned;" ::: "memory"); }
template <int N> __device__ __forceinline__ void wgmma_wait() {
    asm volatile("wgmma.wait_group.sync.aligned %0;" ::"n"(N) : "memory");
}
__device__ __forceinline__ uint32_t pack_bf16x2(float lo, float hi) {
    uint32_t r;
    asm("cvt.rn.bf16x2.f32 %0, %1, %2;" : "=r"(r) : "f"(hi), "f"(lo));
    return r;
}
__device__ __forceinline__ uint32_t lds32(uint32_t addr) {
    uint32_t v;
    asm("ld.shared.u32 %0, [%1];" : "=r"(v) : "r"(addr));
    return v;
}
__device__ __forceinline__ uint32_t dp4a_u(uint32_t a, uint32_t b, uint32_t c) {
    uint32_t d;
    asm("dp4a.u32.u32 %0, %1, %2, %3;" : "=r"(d) : "r"(a), "r"(b), "r"(c));
    return d;
}
__device__ __forceinline__ uint32_t prmt(uint32_t a, uint32_t b, uint32_t s) {
    uint32_t d;
    asm("prmt.b32 %0, %1, %2, %3;" : "=r"(d) : "r"(a), "r"(b), "r"(s));
    return d;
}
template <int ID, int NT> __device__ __forceinline__ void named_bar_sync() {
    asm volatile("bar.sync %0, %1;" ::"n"(ID), "n"(NT) : "memory");
}
template <int ID, int NT> __device__ __forceinline__ void named_bar_arrive() {
    asm volatile("bar.arrive %0, %1;" ::"n"(ID), "n"(NT) : "memory");
}
__device__ __forceinline__ void cluster_arrive_relaxed() { asm volatile("barrier.cluster.arrive.relaxed.aligned;" ::: "memory"); }
__device__ __forceinline__ void cluster_wait() { asm volatile("barrier.cluster.wait.acquire.aligned;" ::: "memory"); }
__device__ __forceinline__ uint4 ldg_stream(const int* p) {
    uint4 v;
    asm volatile("ld.global.L1::no_allocate.L2::128B.v4.u32 {%0, %1, %2, %3}, [%4];"
                 : "=r"(v.x), "=r"(v.y), "=r"(v.z), "=r"(v.w) : "l"(p));
    return v;
}
__device__ __forceinline__ uint32_t ldg_u16(const unsigned short* p) {
    uint32_t v;
    asm volatile("ld.global.nc.u16 %0, [%1];" : "=r"(v) : "l"(p));
    return v;
}
__device__ __forceinline__ unsigned ld_ca_u32(const unsigned* p) {
    unsigned v;
    asm volatile("ld.global.ca.u32 %0, [%1];" : "=r"(v) : "l"(p) : "memory");
    return v;
}
typedef unsigned long long u64;
__device__ __forceinline__ void ll_store2(u64* p, uint32_t w0, uint32_t w1, uint32_t tag) {
    asm volatile("{\n.reg .b64 a, b;\nmov.b64 a, {%1, %3};\nmov.b64 b, {%2, %3};\n"
                 "st.relaxed.gpu.global.v2.b64 [%0], {a, b};\n}\n" ::"l"(p), "r"(w0), "r"(w1), "r"(tag) : "memory");
}

template <int N, int OFF, bool ACC, int NA> struct WG;
template <int OFF, int NA> struct WG<232, OFF, false, NA> {
    static __device__ __forceinline__ void mma(float (&d)[NA], uint32_t a0, uint32_t a1, uint32_t a2, uint32_t a3, uint64_t descB) {
        asm volatile(
            "{\n"
            ".reg .pred p;\n"
            "setp.ne.b32 p, %121, 0;\n"
            "wgmma.mma_async.sync.aligned.m64n232k16.f32.bf16.bf16 "
            "{%0, %1, %2, %3, %4, %5, %6, %7, %8, %9, %10, %11, %12, %13, %14, %15, %16, %17, %18, %19, %20, %21, %22, %23, %24, %25, %26, %27, %28, %29, %30, %31, %32, %33, %34, %35, %36, %37, %38, %39, %40, %41, %42, %43, %44, %45, %46, %47, %48, %49, %50, %51, %52, %53, %54, %55, %56, %57, %58, %59, %60, %61, %62, %63, %64, %65, %66, %67, %68, %69, %70, %71, %72, %73, %74, %75, %76, %77, %78, %79, %80, %81, %82, %83, %84, %85, %86, %87, %88, %89, %90, %91, %92, %93, %94, %95, %96, %97, %98, %99, %100, %101, %102, %103, %104, %105, %106, %107, %108, %109, %110, %111, %112, %113, %114, %115}, "
            "{%116, %117, %118, %119}, %120, p, 1, 1, 0;\n"
            "}\n"
            : "=f"(d[OFF + 0]), "=f"(d[OFF + 1]), "=f"(d[OFF + 2]), "=f"(d[OFF + 3]), "=f"(d[OFF + 4]), "=f"(d[OFF + 5]), "=f"(d[OFF + 6]), "=f"(d[OFF + 7]), "=f"(d[OFF + 8]), "=f"(d[OFF + 9]), "=f"(d[OFF + 10]), "=f"(d[OFF + 11]), "=f"(d[OFF + 12]), "=f"(d[OFF + 13]), "=f"(d[OFF + 14]), "=f"(d[OFF + 15]), "=f"(d[OFF + 16]), "=f"(d[OFF + 17]), "=f"(d[OFF + 18]), "=f"(d[OFF + 19]), "=f"(d[OFF + 20]), "=f"(d[OFF + 21]), "=f"(d[OFF + 22]), "=f"(d[OFF + 23]), "=f"(d[OFF + 24]), "=f"(d[OFF + 25]), "=f"(d[OFF + 26]), "=f"(d[OFF + 27]), "=f"(d[OFF + 28]), "=f"(d[OFF + 29]), "=f"(d[OFF + 30]), "=f"(d[OFF + 31]), "=f"(d[OFF + 32]), "=f"(d[OFF + 33]), "=f"(d[OFF + 34]), "=f"(d[OFF + 35]), "=f"(d[OFF + 36]), "=f"(d[OFF + 37]), "=f"(d[OFF + 38]), "=f"(d[OFF + 39]), "=f"(d[OFF + 40]), "=f"(d[OFF + 41]), "=f"(d[OFF + 42]), "=f"(d[OFF + 43]), "=f"(d[OFF + 44]), "=f"(d[OFF + 45]), "=f"(d[OFF + 46]), "=f"(d[OFF + 47]), "=f"(d[OFF + 48]), "=f"(d[OFF + 49]), "=f"(d[OFF + 50]), "=f"(d[OFF + 51]), "=f"(d[OFF + 52]), "=f"(d[OFF + 53]), "=f"(d[OFF + 54]), "=f"(d[OFF + 55]), "=f"(d[OFF + 56]), "=f"(d[OFF + 57]), "=f"(d[OFF + 58]), "=f"(d[OFF + 59]), "=f"(d[OFF + 60]), "=f"(d[OFF + 61]), "=f"(d[OFF + 62]), "=f"(d[OFF + 63]), "=f"(d[OFF + 64]), "=f"(d[OFF + 65]), "=f"(d[OFF + 66]), "=f"(d[OFF + 67]), "=f"(d[OFF + 68]), "=f"(d[OFF + 69]), "=f"(d[OFF + 70]), "=f"(d[OFF + 71]), "=f"(d[OFF + 72]), "=f"(d[OFF + 73]), "=f"(d[OFF + 74]), "=f"(d[OFF + 75]), "=f"(d[OFF + 76]), "=f"(d[OFF + 77]), "=f"(d[OFF + 78]), "=f"(d[OFF + 79]), "=f"(d[OFF + 80]), "=f"(d[OFF + 81]), "=f"(d[OFF + 82]), "=f"(d[OFF + 83]), "=f"(d[OFF + 84]), "=f"(d[OFF + 85]), "=f"(d[OFF + 86]), "=f"(d[OFF + 87]), "=f"(d[OFF + 88]), "=f"(d[OFF + 89]), "=f"(d[OFF + 90]), "=f"(d[OFF + 91]), "=f"(d[OFF + 92]), "=f"(d[OFF + 93]), "=f"(d[OFF + 94]), "=f"(d[OFF + 95]), "=f"(d[OFF + 96]), "=f"(d[OFF + 97]), "=f"(d[OFF + 98]), "=f"(d[OFF + 99]), "=f"(d[OFF + 100]), "=f"(d[OFF + 101]), "=f"(d[OFF + 102]), "=f"(d[OFF + 103]), "=f"(d[OFF + 104]), "=f"(d[OFF + 105]), "=f"(d[OFF + 106]), "=f"(d[OFF + 107]), "=f"(d[OFF + 108]), "=f"(d[OFF + 109]), "=f"(d[OFF + 110]), "=f"(d[OFF + 111]), "=f"(d[OFF + 112]), "=f"(d[OFF + 113]), "=f"(d[OFF + 114]), "=f"(d[OFF + 115])
            : "r"(a0), "r"(a1), "r"(a2), "r"(a3), "l"(descB), "n"(0));
    }
};
template <int OFF, int NA> struct WG<232, OFF, true, NA> {
    static __device__ __forceinline__ void mma(float (&d)[NA], uint32_t a0, uint32_t a1, uint32_t a2, uint32_t a3, uint64_t descB) {
        asm volatile(
            "{\n"
            ".reg .pred p;\n"
            "setp.ne.b32 p, %121, 0;\n"
            "wgmma.mma_async.sync.aligned.m64n232k16.f32.bf16.bf16 "
            "{%0, %1, %2, %3, %4, %5, %6, %7, %8, %9, %10, %11, %12, %13, %14, %15, %16, %17, %18, %19, %20, %21, %22, %23, %24, %25, %26, %27, %28, %29, %30, %31, %32, %33, %34, %35, %36, %37, %38, %39, %40, %41, %42, %43, %44, %45, %46, %47, %48, %49, %50, %51, %52, %53, %54, %55, %56, %57, %58, %59, %60, %61, %62, %63, %64, %65, %66, %67, %68, %69, %70, %71, %72, %73, %74, %75, %76, %77, %78, %79, %80, %81, %82, %83, %84, %85, %86, %87, %88, %89, %90, %91, %92, %93, %94, %95, %96, %97, %98, %99, %100, %101, %102, %103, %104, %105, %106, %107, %108, %109, %110, %111, %112, %113, %114, %115}, "
            "{%116, %117, %118, %119}, %120, p, 1, 1, 0;\n"
            "}\n"
            : "+f"(d[OFF + 0]), "+f"(d[OFF + 1]), "+f"(d[OFF + 2]), "+f"(d[OFF + 3]), "+f"(d[OFF + 4]), "+f"(d[OFF + 5]), "+f"(d[OFF + 6]), "+f"(d[OFF + 7]), "+f"(d[OFF + 8]), "+f"(d[OFF + 9]), "+f"(d[OFF + 10]), "+f"(d[OFF + 11]), "+f"(d[OFF + 12]), "+f"(d[OFF + 13]), "+f"(d[OFF + 14]), "+f"(d[OFF + 15]), "+f"(d[OFF + 16]), "+f"(d[OFF + 17]), "+f"(d[OFF + 18]), "+f"(d[OFF + 19]), "+f"(d[OFF + 20]), "+f"(d[OFF + 21]), "+f"(d[OFF + 22]), "+f"(d[OFF + 23]), "+f"(d[OFF + 24]), "+f"(d[OFF + 25]), "+f"(d[OFF + 26]), "+f"(d[OFF + 27]), "+f"(d[OFF + 28]), "+f"(d[OFF + 29]), "+f"(d[OFF + 30]), "+f"(d[OFF + 31]), "+f"(d[OFF + 32]), "+f"(d[OFF + 33]), "+f"(d[OFF + 34]), "+f"(d[OFF + 35]), "+f"(d[OFF + 36]), "+f"(d[OFF + 37]), "+f"(d[OFF + 38]), "+f"(d[OFF + 39]), "+f"(d[OFF + 40]), "+f"(d[OFF + 41]), "+f"(d[OFF + 42]), "+f"(d[OFF + 43]), "+f"(d[OFF + 44]), "+f"(d[OFF + 45]), "+f"(d[OFF + 46]), "+f"(d[OFF + 47]), "+f"(d[OFF + 48]), "+f"(d[OFF + 49]), "+f"(d[OFF + 50]), "+f"(d[OFF + 51]), "+f"(d[OFF + 52]), "+f"(d[OFF + 53]), "+f"(d[OFF + 54]), "+f"(d[OFF + 55]), "+f"(d[OFF + 56]), "+f"(d[OFF + 57]), "+f"(d[OFF + 58]), "+f"(d[OFF + 59]), "+f"(d[OFF + 60]), "+f"(d[OFF + 61]), "+f"(d[OFF + 62]), "+f"(d[OFF + 63]), "+f"(d[OFF + 64]), "+f"(d[OFF + 65]), "+f"(d[OFF + 66]), "+f"(d[OFF + 67]), "+f"(d[OFF + 68]), "+f"(d[OFF + 69]), "+f"(d[OFF + 70]), "+f"(d[OFF + 71]), "+f"(d[OFF + 72]), "+f"(d[OFF + 73]), "+f"(d[OFF + 74]), "+f"(d[OFF + 75]), "+f"(d[OFF + 76]), "+f"(d[OFF + 77]), "+f"(d[OFF + 78]), "+f"(d[OFF + 79]), "+f"(d[OFF + 80]), "+f"(d[OFF + 81]), "+f"(d[OFF + 82]), "+f"(d[OFF + 83]), "+f"(d[OFF + 84]), "+f"(d[OFF + 85]), "+f"(d[OFF + 86]), "+f"(d[OFF + 87]), "+f"(d[OFF + 88]), "+f"(d[OFF + 89]), "+f"(d[OFF + 90]), "+f"(d[OFF + 91]), "+f"(d[OFF + 92]), "+f"(d[OFF + 93]), "+f"(d[OFF + 94]), "+f"(d[OFF + 95]), "+f"(d[OFF + 96]), "+f"(d[OFF + 97]), "+f"(d[OFF + 98]), "+f"(d[OFF + 99]), "+f"(d[OFF + 100]), "+f"(d[OFF + 101]), "+f"(d[OFF + 102]), "+f"(d[OFF + 103]), "+f"(d[OFF + 104]), "+f"(d[OFF + 105]), "+f"(d[OFF + 106]), "+f"(d[OFF + 107]), "+f"(d[OFF + 108]), "+f"(d[OFF + 109]), "+f"(d[OFF + 110]), "+f"(d[OFF + 111]), "+f"(d[OFF + 112]), "+f"(d[OFF + 113]), "+f"(d[OFF + 114]), "+f"(d[OFF + 115])
            : "r"(a0), "r"(a1), "r"(a2), "r"(a3), "l"(descB), "n"(1));
    }
};
template <int OFF, int NA> struct WG<208, OFF, false, NA> {
    static __device__ __forceinline__ void mma(float (&d)[NA], uint32_t a0, uint32_t a1, uint32_t a2, uint32_t a3, uint64_t descB) {
        asm volatile(
            "{\n"
            ".reg .pred p;\n"
            "setp.ne.b32 p, %109, 0;\n"
            "wgmma.mma_async.sync.aligned.m64n208k16.f32.bf16.bf16 "
            "{%0, %1, %2, %3, %4, %5, %6, %7, %8, %9, %10, %11, %12, %13, %14, %15, %16, %17, %18, %19, %20, %21, %22, %23, %24, %25, %26, %27, %28, %29, %30, %31, %32, %33, %34, %35, %36, %37, %38, %39, %40, %41, %42, %43, %44, %45, %46, %47, %48, %49, %50, %51, %52, %53, %54, %55, %56, %57, %58, %59, %60, %61, %62, %63, %64, %65, %66, %67, %68, %69, %70, %71, %72, %73, %74, %75, %76, %77, %78, %79, %80, %81, %82, %83, %84, %85, %86, %87, %88, %89, %90, %91, %92, %93, %94, %95, %96, %97, %98, %99, %100, %101, %102, %103}, "
            "{%104, %105, %106, %107}, %108, p, 1, 1, 0;\n"
            "}\n"
            : "=f"(d[OFF + 0]), "=f"(d[OFF + 1]), "=f"(d[OFF + 2]), "=f"(d[OFF + 3]), "=f"(d[OFF + 4]), "=f"(d[OFF + 5]), "=f"(d[OFF + 6]), "=f"(d[OFF + 7]), "=f"(d[OFF + 8]), "=f"(d[OFF + 9]), "=f"(d[OFF + 10]), "=f"(d[OFF + 11]), "=f"(d[OFF + 12]), "=f"(d[OFF + 13]), "=f"(d[OFF + 14]), "=f"(d[OFF + 15]), "=f"(d[OFF + 16]), "=f"(d[OFF + 17]), "=f"(d[OFF + 18]), "=f"(d[OFF + 19]), "=f"(d[OFF + 20]), "=f"(d[OFF + 21]), "=f"(d[OFF + 22]), "=f"(d[OFF + 23]), "=f"(d[OFF + 24]), "=f"(d[OFF + 25]), "=f"(d[OFF + 26]), "=f"(d[OFF + 27]), "=f"(d[OFF + 28]), "=f"(d[OFF + 29]), "=f"(d[OFF + 30]), "=f"(d[OFF + 31]), "=f"(d[OFF + 32]), "=f"(d[OFF + 33]), "=f"(d[OFF + 34]), "=f"(d[OFF + 35]), "=f"(d[OFF + 36]), "=f"(d[OFF + 37]), "=f"(d[OFF + 38]), "=f"(d[OFF + 39]), "=f"(d[OFF + 40]), "=f"(d[OFF + 41]), "=f"(d[OFF + 42]), "=f"(d[OFF + 43]), "=f"(d[OFF + 44]), "=f"(d[OFF + 45]), "=f"(d[OFF + 46]), "=f"(d[OFF + 47]), "=f"(d[OFF + 48]), "=f"(d[OFF + 49]), "=f"(d[OFF + 50]), "=f"(d[OFF + 51]), "=f"(d[OFF + 52]), "=f"(d[OFF + 53]), "=f"(d[OFF + 54]), "=f"(d[OFF + 55]), "=f"(d[OFF + 56]), "=f"(d[OFF + 57]), "=f"(d[OFF + 58]), "=f"(d[OFF + 59]), "=f"(d[OFF + 60]), "=f"(d[OFF + 61]), "=f"(d[OFF + 62]), "=f"(d[OFF + 63]), "=f"(d[OFF + 64]), "=f"(d[OFF + 65]), "=f"(d[OFF + 66]), "=f"(d[OFF + 67]), "=f"(d[OFF + 68]), "=f"(d[OFF + 69]), "=f"(d[OFF + 70]), "=f"(d[OFF + 71]), "=f"(d[OFF + 72]), "=f"(d[OFF + 73]), "=f"(d[OFF + 74]), "=f"(d[OFF + 75]), "=f"(d[OFF + 76]), "=f"(d[OFF + 77]), "=f"(d[OFF + 78]), "=f"(d[OFF + 79]), "=f"(d[OFF + 80]), "=f"(d[OFF + 81]), "=f"(d[OFF + 82]), "=f"(d[OFF + 83]), "=f"(d[OFF + 84]), "=f"(d[OFF + 85]), "=f"(d[OFF + 86]), "=f"(d[OFF + 87]), "=f"(d[OFF + 88]), "=f"(d[OFF + 89]), "=f"(d[OFF + 90]), "=f"(d[OFF + 91]), "=f"(d[OFF + 92]), "=f"(d[OFF + 93]), "=f"(d[OFF + 94]), "=f"(d[OFF + 95]), "=f"(d[OFF + 96]), "=f"(d[OFF + 97]), "=f"(d[OFF + 98]), "=f"(d[OFF + 99]), "=f"(d[OFF + 100]), "=f"(d[OFF + 101]), "=f"(d[OFF + 102]), "=f"(d[OFF + 103])
            : "r"(a0), "r"(a1), "r"(a2), "r"(a3), "l"(descB), "n"(0));
    }
};
template <int OFF, int NA> struct WG<208, OFF, true, NA> {
    static __device__ __forceinline__ void mma(float (&d)[NA], uint32_t a0, uint32_t a1, uint32_t a2, uint32_t a3, uint64_t descB) {
        asm volatile(
            "{\n"
            ".reg .pred p;\n"
            "setp.ne.b32 p, %109, 0;\n"
            "wgmma.mma_async.sync.aligned.m64n208k16.f32.bf16.bf16 "
            "{%0, %1, %2, %3, %4, %5, %6, %7, %8, %9, %10, %11, %12, %13, %14, %15, %16, %17, %18, %19, %20, %21, %22, %23, %24, %25, %26, %27, %28, %29, %30, %31, %32, %33, %34, %35, %36, %37, %38, %39, %40, %41, %42, %43, %44, %45, %46, %47, %48, %49, %50, %51, %52, %53, %54, %55, %56, %57, %58, %59, %60, %61, %62, %63, %64, %65, %66, %67, %68, %69, %70, %71, %72, %73, %74, %75, %76, %77, %78, %79, %80, %81, %82, %83, %84, %85, %86, %87, %88, %89, %90, %91, %92, %93, %94, %95, %96, %97, %98, %99, %100, %101, %102, %103}, "
            "{%104, %105, %106, %107}, %108, p, 1, 1, 0;\n"
            "}\n"
            : "+f"(d[OFF + 0]), "+f"(d[OFF + 1]), "+f"(d[OFF + 2]), "+f"(d[OFF + 3]), "+f"(d[OFF + 4]), "+f"(d[OFF + 5]), "+f"(d[OFF + 6]), "+f"(d[OFF + 7]), "+f"(d[OFF + 8]), "+f"(d[OFF + 9]), "+f"(d[OFF + 10]), "+f"(d[OFF + 11]), "+f"(d[OFF + 12]), "+f"(d[OFF + 13]), "+f"(d[OFF + 14]), "+f"(d[OFF + 15]), "+f"(d[OFF + 16]), "+f"(d[OFF + 17]), "+f"(d[OFF + 18]), "+f"(d[OFF + 19]), "+f"(d[OFF + 20]), "+f"(d[OFF + 21]), "+f"(d[OFF + 22]), "+f"(d[OFF + 23]), "+f"(d[OFF + 24]), "+f"(d[OFF + 25]), "+f"(d[OFF + 26]), "+f"(d[OFF + 27]), "+f"(d[OFF + 28]), "+f"(d[OFF + 29]), "+f"(d[OFF + 30]), "+f"(d[OFF + 31]), "+f"(d[OFF + 32]), "+f"(d[OFF + 33]), "+f"(d[OFF + 34]), "+f"(d[OFF + 35]), "+f"(d[OFF + 36]), "+f"(d[OFF + 37]), "+f"(d[OFF + 38]), "+f"(d[OFF + 39]), "+f"(d[OFF + 40]), "+f"(d[OFF + 41]), "+f"(d[OFF + 42]), "+f"(d[OFF + 43]), "+f"(d[OFF + 44]), "+f"(d[OFF + 45]), "+f"(d[OFF + 46]), "+f"(d[OFF + 47]), "+f"(d[OFF + 48]), "+f"(d[OFF + 49]), "+f"(d[OFF + 50]), "+f"(d[OFF + 51]), "+f"(d[OFF + 52]), "+f"(d[OFF + 53]), "+f"(d[OFF + 54]), "+f"(d[OFF + 55]), "+f"(d[OFF + 56]), "+f"(d[OFF + 57]), "+f"(d[OFF + 58]), "+f"(d[OFF + 59]), "+f"(d[OFF + 60]), "+f"(d[OFF + 61]), "+f"(d[OFF + 62]), "+f"(d[OFF + 63]), "+f"(d[OFF + 64]), "+f"(d[OFF + 65]), "+f"(d[OFF + 66]), "+f"(d[OFF + 67]), "+f"(d[OFF + 68]), "+f"(d[OFF + 69]), "+f"(d[OFF + 70]), "+f"(d[OFF + 71]), "+f"(d[OFF + 72]), "+f"(d[OFF + 73]), "+f"(d[OFF + 74]), "+f"(d[OFF + 75]), "+f"(d[OFF + 76]), "+f"(d[OFF + 77]), "+f"(d[OFF + 78]), "+f"(d[OFF + 79]), "+f"(d[OFF + 80]), "+f"(d[OFF + 81]), "+f"(d[OFF + 82]), "+f"(d[OFF + 83]), "+f"(d[OFF + 84]), "+f"(d[OFF + 85]), "+f"(d[OFF + 86]), "+f"(d[OFF + 87]), "+f"(d[OFF + 88]), "+f"(d[OFF + 89]), "+f"(d[OFF + 90]), "+f"(d[OFF + 91]), "+f"(d[OFF + 92]), "+f"(d[OFF + 93]), "+f"(d[OFF + 94]), "+f"(d[OFF + 95]), "+f"(d[OFF + 96]), "+f"(d[OFF + 97]), "+f"(d[OFF + 98]), "+f"(d[OFF + 99]), "+f"(d[OFF + 100]), "+f"(d[OFF + 101]), "+f"(d[OFF + 102]), "+f"(d[OFF + 103])
            : "r"(a0), "r"(a1), "r"(a2), "r"(a3), "l"(descB), "n"(1));
    }
};
template <int OFF, int NA> struct WG<120, OFF, false, NA> {
    static __device__ __forceinline__ void mma(float (&d)[NA], uint32_t a0, uint32_t a1, uint32_t a2, uint32_t a3, uint64_t descB) {
        asm volatile(
            "{\n"
            ".reg .pred p;\n"
            "setp.ne.b32 p, %65, 0;\n"
            "wgmma.mma_async.sync.aligned.m64n120k16.f32.bf16.bf16 "
            "{%0, %1, %2, %3, %4, %5, %6, %7, %8, %9, %10, %11, %12, %13, %14, %15, %16, %17, %18, %19, %20, %21, %22, %23, %24, %25, %26, %27, %28, %29, %30, %31, %32, %33, %34, %35, %36, %37, %38, %39, %40, %41, %42, %43, %44, %45, %46, %47, %48, %49, %50, %51, %52, %53, %54, %55, %56, %57, %58, %59}, "
            "{%60, %61, %62, %63}, %64, p, 1, 1, 0;\n"
            "}\n"
            : "=f"(d[OFF + 0]), "=f"(d[OFF + 1]), "=f"(d[OFF + 2]), "=f"(d[OFF + 3]), "=f"(d[OFF + 4]), "=f"(d[OFF + 5]), "=f"(d[OFF + 6]), "=f"(d[OFF + 7]), "=f"(d[OFF + 8]), "=f"(d[OFF + 9]), "=f"(d[OFF + 10]), "=f"(d[OFF + 11]), "=f"(d[OFF + 12]), "=f"(d[OFF + 13]), "=f"(d[OFF + 14]), "=f"(d[OFF + 15]), "=f"(d[OFF + 16]), "=f"(d[OFF + 17]), "=f"(d[OFF + 18]), "=f"(d[OFF + 19]), "=f"(d[OFF + 20]), "=f"(d[OFF + 21]), "=f"(d[OFF + 22]), "=f"(d[OFF + 23]), "=f"(d[OFF + 24]), "=f"(d[OFF + 25]), "=f"(d[OFF + 26]), "=f"(d[OFF + 27]), "=f"(d[OFF + 28]), "=f"(d[OFF + 29]), "=f"(d[OFF + 30]), "=f"(d[OFF + 31]), "=f"(d[OFF + 32]), "=f"(d[OFF + 33]), "=f"(d[OFF + 34]), "=f"(d[OFF + 35]), "=f"(d[OFF + 36]), "=f"(d[OFF + 37]), "=f"(d[OFF + 38]), "=f"(d[OFF + 39]), "=f"(d[OFF + 40]), "=f"(d[OFF + 41]), "=f"(d[OFF + 42]), "=f"(d[OFF + 43]), "=f"(d[OFF + 44]), "=f"(d[OFF + 45]), "=f"(d[OFF + 46]), "=f"(d[OFF + 47]), "=f"(d[OFF + 48]), "=f"(d[OFF + 49]), "=f"(d[OFF + 50]), "=f"(d[OFF + 51]), "=f"(d[OFF + 52]), "=f"(d[OFF + 53]), "=f"(d[OFF + 54]), "=f"(d[OFF + 55]), "=f"(d[OFF + 56]), "=f"(d[OFF + 57]), "=f"(d[OFF + 58]), "=f"(d[OFF + 59])
            : "r"(a0), "r"(a1), "r"(a2), "r"(a3), "l"(descB), "n"(0));
    }
};
template <int OFF, int NA> struct WG<120, OFF, true, NA> {
    static __device__ __forceinline__ void mma(float (&d)[NA], uint32_t a0, uint32_t a1, uint32_t a2, uint32_t a3, uint64_t descB) {
        asm volatile(
            "{\n"
            ".reg .pred p;\n"
            "setp.ne.b32 p, %65, 0;\n"
            "wgmma.mma_async.sync.aligned.m64n120k16.f32.bf16.bf16 "
            "{%0, %1, %2, %3, %4, %5, %6, %7, %8, %9, %10, %11, %12, %13, %14, %15, %16, %17, %18, %19, %20, %21, %22, %23, %24, %25, %26, %27, %28, %29, %30, %31, %32, %33, %34, %35, %36, %37, %38, %39, %40, %41, %42, %43, %44, %45, %46, %47, %48, %49, %50, %51, %52, %53, %54, %55, %56, %57, %58, %59}, "
            "{%60, %61, %62, %63}, %64, p, 1, 1, 0;\n"
            "}\n"
            : "+f"(d[OFF + 0]), "+f"(d[OFF + 1]), "+f"(d[OFF + 2]), "+f"(d[OFF + 3]), "+f"(d[OFF + 4]), "+f"(d[OFF + 5]), "+f"(d[OFF + 6]), "+f"(d[OFF + 7]), "+f"(d[OFF + 8]), "+f"(d[OFF + 9]), "+f"(d[OFF + 10]), "+f"(d[OFF + 11]), "+f"(d[OFF + 12]), "+f"(d[OFF + 13]), "+f"(d[OFF + 14]), "+f"(d[OFF + 15]), "+f"(d[OFF + 16]), "+f"(d[OFF + 17]), "+f"(d[OFF + 18]), "+f"(d[OFF + 19]), "+f"(d[OFF + 20]), "+f"(d[OFF + 21]), "+f"(d[OFF + 22]), "+f"(d[OFF + 23]), "+f"(d[OFF + 24]), "+f"(d[OFF + 25]), "+f"(d[OFF + 26]), "+f"(d[OFF + 27]), "+f"(d[OFF + 28]), "+f"(d[OFF + 29]), "+f"(d[OFF + 30]), "+f"(d[OFF + 31]), "+f"(d[OFF + 32]), "+f"(d[OFF + 33]), "+f"(d[OFF + 34]), "+f"(d[OFF + 35]), "+f"(d[OFF + 36]), "+f"(d[OFF + 37]), "+f"(d[OFF + 38]), "+f"(d[OFF + 39]), "+f"(d[OFF + 40]), "+f"(d[OFF + 41]), "+f"(d[OFF + 42]), "+f"(d[OFF + 43]), "+f"(d[OFF + 44]), "+f"(d[OFF + 45]), "+f"(d[OFF + 46]), "+f"(d[OFF + 47]), "+f"(d[OFF + 48]), "+f"(d[OFF + 49]), "+f"(d[OFF + 50]), "+f"(d[OFF + 51]), "+f"(d[OFF + 52]), "+f"(d[OFF + 53]), "+f"(d[OFF + 54]), "+f"(d[OFF + 55]), "+f"(d[OFF + 56]), "+f"(d[OFF + 57]), "+f"(d[OFF + 58]), "+f"(d[OFF + 59])
            : "r"(a0), "r"(a1), "r"(a2), "r"(a3), "l"(descB), "n"(1));
    }
};
template <int OFF, int NA> struct WG<112, OFF, false, NA> {
    static __device__ __forceinline__ void mma(float (&d)[NA], uint32_t a0, uint32_t a1, uint32_t a2, uint32_t a3, uint64_t descB) {
        asm volatile(
            "{\n"
            ".reg .pred p;\n"
            "setp.ne.b32 p, %61, 0;\n"
            "wgmma.mma_async.sync.aligned.m64n112k16.f32.bf16.bf16 "
            "{%0, %1, %2, %3, %4, %5, %6, %7, %8, %9, %10, %11, %12, %13, %14, %15, %16, %17, %18, %19, %20, %21, %22, %23, %24, %25, %26, %27, %28, %29, %30, %31, %32, %33, %34, %35, %36, %37, %38, %39, %40, %41, %42, %43, %44, %45, %46, %47, %48, %49, %50, %51, %52, %53, %54, %55}, "
            "{%56, %57, %58, %59}, %60, p, 1, 1, 0;\n"
            "}\n"
            : "=f"(d[OFF + 0]), "=f"(d[OFF + 1]), "=f"(d[OFF + 2]), "=f"(d[OFF + 3]), "=f"(d[OFF + 4]), "=f"(d[OFF + 5]), "=f"(d[OFF + 6]), "=f"(d[OFF + 7]), "=f"(d[OFF + 8]), "=f"(d[OFF + 9]), "=f"(d[OFF + 10]), "=f"(d[OFF + 11]), "=f"(d[OFF + 12]), "=f"(d[OFF + 13]), "=f"(d[OFF + 14]), "=f"(d[OFF + 15]), "=f"(d[OFF + 16]), "=f"(d[OFF + 17]), "=f"(d[OFF + 18]), "=f"(d[OFF + 19]), "=f"(d[OFF + 20]), "=f"(d[OFF + 21]), "=f"(d[OFF + 22]), "=f"(d[OFF + 23]), "=f"(d[OFF + 24]), "=f"(d[OFF + 25]), "=f"(d[OFF + 26]), "=f"(d[OFF + 27]), "=f"(d[OFF + 28]), "=f"(d[OFF + 29]), "=f"(d[OFF + 30]), "=f"(d[OFF + 31]), "=f"(d[OFF + 32]), "=f"(d[OFF + 33]), "=f"(d[OFF + 34]), "=f"(d[OFF + 35]), "=f"(d[OFF + 36]), "=f"(d[OFF + 37]), "=f"(d[OFF + 38]), "=f"(d[OFF + 39]), "=f"(d[OFF + 40]), "=f"(d[OFF + 41]), "=f"(d[OFF + 42]), "=f"(d[OFF + 43]), "=f"(d[OFF + 44]), "=f"(d[OFF + 45]), "=f"(d[OFF + 46]), "=f"(d[OFF + 47]), "=f"(d[OFF + 48]), "=f"(d[OFF + 49]), "=f"(d[OFF + 50]), "=f"(d[OFF + 51]), "=f"(d[OFF + 52]), "=f"(d[OFF + 53]), "=f"(d[OFF + 54]), "=f"(d[OFF + 55])
            : "r"(a0), "r"(a1), "r"(a2), "r"(a3), "l"(descB), "n"(0));
    }
};
template <int OFF, int NA> struct WG<112, OFF, true, NA> {
    static __device__ __forceinline__ void mma(float (&d)[NA], uint32_t a0, uint32_t a1, uint32_t a2, uint32_t a3, uint64_t descB) {
        asm volatile(
            "{\n"
            ".reg .pred p;\n"
            "setp.ne.b32 p, %61, 0;\n"
            "wgmma.mma_async.sync.aligned.m64n112k16.f32.bf16.bf16 "
            "{%0, %1, %2, %3, %4, %5, %6, %7, %8, %9, %10, %11, %12, %13, %14, %15, %16, %17, %18, %19, %20, %21, %22, %23, %24, %25, %26, %27, %28, %29, %30, %31, %32, %33, %34, %35, %36, %37, %38, %39, %40, %41, %42, %43, %44, %45, %46, %47, %48, %49, %50, %51, %52, %53, %54, %55}, "
            "{%56, %57, %58, %59}, %60, p, 1, 1, 0;\n"
            "}\n"
            : "+f"(d[OFF + 0]), "+f"(d[OFF + 1]), "+f"(d[OFF + 2]), "+f"(d[OFF + 3]), "+f"(d[OFF + 4]), "+f"(d[OFF + 5]), "+f"(d[OFF + 6]), "+f"(d[OFF + 7]), "+f"(d[OFF + 8]), "+f"(d[OFF + 9]), "+f"(d[OFF + 10]), "+f"(d[OFF + 11]), "+f"(d[OFF + 12]), "+f"(d[OFF + 13]), "+f"(d[OFF + 14]), "+f"(d[OFF + 15]), "+f"(d[OFF + 16]), "+f"(d[OFF + 17]), "+f"(d[OFF + 18]), "+f"(d[OFF + 19]), "+f"(d[OFF + 20]), "+f"(d[OFF + 21]), "+f"(d[OFF + 22]), "+f"(d[OFF + 23]), "+f"(d[OFF + 24]), "+f"(d[OFF + 25]), "+f"(d[OFF + 26]), "+f"(d[OFF + 27]), "+f"(d[OFF + 28]), "+f"(d[OFF + 29]), "+f"(d[OFF + 30]), "+f"(d[OFF + 31]), "+f"(d[OFF + 32]), "+f"(d[OFF + 33]), "+f"(d[OFF + 34]), "+f"(d[OFF + 35]), "+f"(d[OFF + 36]), "+f"(d[OFF + 37]), "+f"(d[OFF + 38]), "+f"(d[OFF + 39]), "+f"(d[OFF + 40]), "+f"(d[OFF + 41]), "+f"(d[OFF + 42]), "+f"(d[OFF + 43]), "+f"(d[OFF + 44]), "+f"(d[OFF + 45]), "+f"(d[OFF + 46]), "+f"(d[OFF + 47]), "+f"(d[OFF + 48]), "+f"(d[OFF + 49]), "+f"(d[OFF + 50]), "+f"(d[OFF + 51]), "+f"(d[OFF + 52]), "+f"(d[OFF + 53]), "+f"(d[OFF + 54]), "+f"(d[OFF + 55])
            : "r"(a0), "r"(a1), "r"(a2), "r"(a3), "l"(descB), "n"(1));
    }
};
template <int OFF, int NA> struct WG<96, OFF, false, NA> {
    static __device__ __forceinline__ void mma(float (&d)[NA], uint32_t a0, uint32_t a1, uint32_t a2, uint32_t a3, uint64_t descB) {
        asm volatile(
            "{\n"
            ".reg .pred p;\n"
            "setp.ne.b32 p, %53, 0;\n"
            "wgmma.mma_async.sync.aligned.m64n96k16.f32.bf16.bf16 "
            "{%0, %1, %2, %3, %4, %5, %6, %7, %8, %9, %10, %11, %12, %13, %14, %15, %16, %17, %18, %19, %20, %21, %22, %23, %24, %25, %26, %27, %28, %29, %30, %31, %32, %33, %34, %35, %36, %37, %38, %39, %40, %41, %42, %43, %44, %45, %46, %47}, "
            "{%48, %49, %50, %51}, %52, p, 1, 1, 0;\n"
            "}\n"
            : "=f"(d[OFF + 0]), "=f"(d[OFF + 1]), "=f"(d[OFF + 2]), "=f"(d[OFF + 3]), "=f"(d[OFF + 4]), "=f"(d[OFF + 5]), "=f"(d[OFF + 6]), "=f"(d[OFF + 7]), "=f"(d[OFF + 8]), "=f"(d[OFF + 9]), "=f"(d[OFF + 10]), "=f"(d[OFF + 11]), "=f"(d[OFF + 12]), "=f"(d[OFF + 13]), "=f"(d[OFF + 14]), "=f"(d[OFF + 15]), "=f"(d[OFF + 16]), "=f"(d[OFF + 17]), "=f"(d[OFF + 18]), "=f"(d[OFF + 19]), "=f"(d[OFF + 20]), "=f"(d[OFF + 21]), "=f"(d[OFF + 22]), "=f"(d[OFF + 23]), "=f"(d[OFF + 24]), "=f"(d[OFF + 25]), "=f"(d[OFF + 26]), "=f"(d[OFF + 27]), "=f"(d[OFF + 28]), "=f"(d[OFF + 29]), "=f"(d[OFF + 30]), "=f"(d[OFF + 31]), "=f"(d[OFF + 32]), "=f"(d[OFF + 33]), "=f"(d[OFF + 34]), "=f"(d[OFF + 35]), "=f"(d[OFF + 36]), "=f"(d[OFF + 37]), "=f"(d[OFF + 38]), "=f"(d[OFF + 39]), "=f"(d[OFF + 40]), "=f"(d[OFF + 41]), "=f"(d[OFF + 42]), "=f"(d[OFF + 43]), "=f"(d[OFF + 44]), "=f"(d[OFF + 45]), "=f"(d[OFF + 46]), "=f"(d[OFF + 47])
            : "r"(a0), "r"(a1), "r"(a2), "r"(a3), "l"(descB), "n"(0));
    }
};
template <int OFF, int NA> struct WG<96, OFF, true, NA> {
    static __device__ __forceinline__ void mma(float (&d)[NA], uint32_t a0, uint32_t a1, uint32_t a2, uint32_t a3, uint64_t descB) {
        asm volatile(
            "{\n"
            ".reg .pred p;\n"
            "setp.ne.b32 p, %53, 0;\n"
            "wgmma.mma_async.sync.aligned.m64n96k16.f32.bf16.bf16 "
            "{%0, %1, %2, %3, %4, %5, %6, %7, %8, %9, %10, %11, %12, %13, %14, %15, %16, %17, %18, %19, %20, %21, %22, %23, %24, %25, %26, %27, %28, %29, %30, %31, %32, %33, %34, %35, %36, %37, %38, %39, %40, %41, %42, %43, %44, %45, %46, %47}, "
            "{%48, %49, %50, %51}, %52, p, 1, 1, 0;\n"
            "}\n"
            : "+f"(d[OFF + 0]), "+f"(d[OFF + 1]), "+f"(d[OFF + 2]), "+f"(d[OFF + 3]), "+f"(d[OFF + 4]), "+f"(d[OFF + 5]), "+f"(d[OFF + 6]), "+f"(d[OFF + 7]), "+f"(d[OFF + 8]), "+f"(d[OFF + 9]), "+f"(d[OFF + 10]), "+f"(d[OFF + 11]), "+f"(d[OFF + 12]), "+f"(d[OFF + 13]), "+f"(d[OFF + 14]), "+f"(d[OFF + 15]), "+f"(d[OFF + 16]), "+f"(d[OFF + 17]), "+f"(d[OFF + 18]), "+f"(d[OFF + 19]), "+f"(d[OFF + 20]), "+f"(d[OFF + 21]), "+f"(d[OFF + 22]), "+f"(d[OFF + 23]), "+f"(d[OFF + 24]), "+f"(d[OFF + 25]), "+f"(d[OFF + 26]), "+f"(d[OFF + 27]), "+f"(d[OFF + 28]), "+f"(d[OFF + 29]), "+f"(d[OFF + 30]), "+f"(d[OFF + 31]), "+f"(d[OFF + 32]), "+f"(d[OFF + 33]), "+f"(d[OFF + 34]), "+f"(d[OFF + 35]), "+f"(d[OFF + 36]), "+f"(d[OFF + 37]), "+f"(d[OFF + 38]), "+f"(d[OFF + 39]), "+f"(d[OFF + 40]), "+f"(d[OFF + 41]), "+f"(d[OFF + 42]), "+f"(d[OFF + 43]), "+f"(d[OFF + 44]), "+f"(d[OFF + 45]), "+f"(d[OFF + 46]), "+f"(d[OFF + 47])
            : "r"(a0), "r"(a1), "r"(a2), "r"(a3), "l"(descB), "n"(1));
    }
};
template <int OFF, int NA> struct WG<64, OFF, true, NA> {
    static __device__ __forceinline__ void mma(float (&d)[NA], uint32_t a0, uint32_t a1, uint32_t a2, uint32_t a3, uint64_t descB) {
        asm volatile(
            "{\n"
            ".reg .pred p;\n"
            "setp.ne.b32 p, %37, 0;\n"
            "wgmma.mma_async.sync.aligned.m64n64k16.f32.bf16.bf16 "
            "{%0, %1, %2, %3, %4, %5, %6, %7, %8, %9, %10, %11, %12, %13, %14, %15, %16, %17, %18, %19, %20, %21, %22, %23, %24, %25, %26, %27, %28, %29, %30, %31}, "
            "{%32, %33, %34, %35}, %36, p, 1, 1, 0;\n"
            "}\n"
            : "+f"(d[OFF + 0]), "+f"(d[OFF + 1]), "+f"(d[OFF + 2]), "+f"(d[OFF + 3]), "+f"(d[OFF + 4]), "+f"(d[OFF + 5]), "+f"(d[OFF + 6]), "+f"(d[OFF + 7]), "+f"(d[OFF + 8]), "+f"(d[OFF + 9]), "+f"(d[OFF + 10]), "+f"(d[OFF + 11]), "+f"(d[OFF + 12]), "+f"(d[OFF + 13]), "+f"(d[OFF + 14]), "+f"(d[OFF + 15]), "+f"(d[OFF + 16]), "+f"(d[OFF + 17]), "+f"(d[OFF + 18]), "+f"(d[OFF + 19]), "+f"(d[OFF + 20]), "+f"(d[OFF + 21]), "+f"(d[OFF + 22]), "+f"(d[OFF + 23]), "+f"(d[OFF + 24]), "+f"(d[OFF + 25]), "+f"(d[OFF + 26]), "+f"(d[OFF + 27]), "+f"(d[OFF + 28]), "+f"(d[OFF + 29]), "+f"(d[OFF + 30]), "+f"(d[OFF + 31])
            : "r"(a0), "r"(a1), "r"(a2), "r"(a3), "l"(descB), "n"(1));
    }
};
template <int OFF, int NA> struct WG<48, OFF, true, NA> {
    static __device__ __forceinline__ void mma(float (&d)[NA], uint32_t a0, uint32_t a1, uint32_t a2, uint32_t a3, uint64_t descB) {
        asm volatile(
            "{\n"
            ".reg .pred p;\n"
            "setp.ne.b32 p, %29, 0;\n"
            "wgmma.mma_async.sync.aligned.m64n48k16.f32.bf16.bf16 "
            "{%0, %1, %2, %3, %4, %5, %6, %7, %8, %9, %10, %11, %12, %13, %14, %15, %16, %17, %18, %19, %20, %21, %22, %23}, "
            "{%24, %25, %26, %27}, %28, p, 1, 1, 0;\n"
            "}\n"
            : "+f"(d[OFF + 0]), "+f"(d[OFF + 1]), "+f"(d[OFF + 2]), "+f"(d[OFF + 3]), "+f"(d[OFF + 4]), "+f"(d[OFF + 5]), "+f"(d[OFF + 6]), "+f"(d[OFF + 7]), "+f"(d[OFF + 8]), "+f"(d[OFF + 9]), "+f"(d[OFF + 10]), "+f"(d[OFF + 11]), "+f"(d[OFF + 12]), "+f"(d[OFF + 13]), "+f"(d[OFF + 14]), "+f"(d[OFF + 15]), "+f"(d[OFF + 16]), "+f"(d[OFF + 17]), "+f"(d[OFF + 18]), "+f"(d[OFF + 19]), "+f"(d[OFF + 20]), "+f"(d[OFF + 21]), "+f"(d[OFF + 22]), "+f"(d[OFF + 23])
            : "r"(a0), "r"(a1), "r"(a2), "r"(a3), "l"(descB), "n"(1));
    }
};
template <int OFF, int NA> struct WG<32, OFF, true, NA> {
    static __device__ __forceinline__ void mma(float (&d)[NA], uint32_t a0, uint32_t a1, uint32_t a2, uint32_t a3, uint64_t descB) {
        asm volatile(
            "{\n"
            ".reg .pred p;\n"
            "setp.ne.b32 p, %21, 0;\n"
            "wgmma.mma_async.sync.aligned.m64n32k16.f32.bf16.bf16 "
            "{%0, %1, %2, %3, %4, %5, %6, %7, %8, %9, %10, %11, %12, %13, %14, %15}, "
            "{%16, %17, %18, %19}, %20, p, 1, 1, 0;\n"
            "}\n"
            : "+f"(d[OFF + 0]), "+f"(d[OFF + 1]), "+f"(d[OFF + 2]), "+f"(d[OFF + 3]), "+f"(d[OFF + 4]), "+f"(d[OFF + 5]), "+f"(d[OFF + 6]), "+f"(d[OFF + 7]), "+f"(d[OFF + 8]), "+f"(d[OFF + 9]), "+f"(d[OFF + 10]), "+f"(d[OFF + 11]), "+f"(d[OFF + 12]), "+f"(d[OFF + 13]), "+f"(d[OFF + 14]), "+f"(d[OFF + 15])
            : "r"(a0), "r"(a1), "r"(a2), "r"(a3), "l"(descB), "n"(1));
    }
};

__host__ __device__ constexpr int gate_time(int d) { return d == 0 ? DLY_POLL : DLY_P1 + (d - 1) * DLY_PS; }
__device__ __forceinline__ void unit_pos(uint32_t u, uint32_t& q, uint32_t& fg) {
    static_assert(W1_FG == 64 && W2_FG == 48, "unit order");
    const uint32_t r = u - NQ * W1_FG, q2 = (r * 1366) >> 16;
    q = u < NQ * W1_FG ? u >> 6 : q2;
    fg = u < NQ * W1_FG ? u & 63 : W1_FG + r - q2 * 48;
}
template <class T> __device__ __forceinline__ T* add_off(T* p, uint32_t bytes) {
    uint64_t r;
    asm("{\n.reg .b64 o;\ncvt.u64.u32 o, %2;\nadd.u64 %0, %1, o;\n}\n" : "=l"(r) : "l"(p), "r"(bytes));
    return (T*)r;
}
__device__ __forceinline__ uint32_t unit_src(uint32_t q, uint32_t fg) { return q * (32 * kN * 4) + fg * 128; }
__device__ __forceinline__ uint32_t lane_src(int lane) { return (lane >> 3) * (2 * kN * 4) + (lane & 7) * 16; }
__device__ __forceinline__ uint32_t unit_dst(uint32_t q, uint32_t fg) {
    return ((fg >> 2) * KSTEPS + (q >> 1)) * 8192 + (fg & 3) * 2048 + (q & 1) * 512;
}
__device__ __forceinline__ uint32_t lane_dst(int lane) { return ((lane >> 2) & 1) * 1024 + (lane & 3) * 64 + (lane >> 3) * 16; }
__device__ __forceinline__ uint32_t lane_unit(int lane) {
    return ((lane >> 3) & 1) * 256 + (((lane >> 4) ^ (lane >> 3)) & 1) * 64 + (lane & 3) * 16 + ((lane >> 2) & 1) * 8;
}
__device__ __forceinline__ constexpr int unit_row(int i) { return 16 * (i >> 2) + 8 * ((i >> 1) & 1) + (i & 1); }
__device__ __forceinline__ void load_unit(uint4 (&v)[8], const int* p) {
#pragma unroll
    for (int i = 0; i < 8; i++) v[i] = ldg_stream(p + (size_t)unit_row(i) * kN);
}
__device__ __forceinline__ uint32_t bytes4(uint32_t v0, uint32_t v1, uint32_t v2, uint32_t v3) {
    return prmt(prmt(v0, v1, 0x0040), prmt(v2, v3, 0x0040), 0x5410);
}
__device__ __forceinline__ void pk_gather(uint32_t (&e)[4], uint32_t (&o)[4], const uint4 (&v)[8]) {
    e[0] = bytes4(v[0].x, v[2].x, v[4].x, v[6].x); o[0] = bytes4(v[1].x, v[3].x, v[5].x, v[7].x);
    e[1] = bytes4(v[0].y, v[2].y, v[4].y, v[6].y); o[1] = bytes4(v[1].y, v[3].y, v[5].y, v[7].y);
    e[2] = bytes4(v[0].z, v[2].z, v[4].z, v[6].z); o[2] = bytes4(v[1].z, v[3].z, v[5].z, v[7].z);
    e[3] = bytes4(v[0].w, v[2].w, v[4].w, v[6].w); o[3] = bytes4(v[1].w, v[3].w, v[5].w, v[7].w);
}

__device__ __forceinline__ void tile0_of(int c, int& fp, int& m0) {
    if (c < 18) { fp = c >= 9; m0 = min((c - 9 * fp) * N0, kM - N0); }
    else { fp = 2 + ((c - 18) >> 3); m0 = ((c - 18) & 7) * N0; }
}
__device__ __forceinline__ void tile1_of(int c, int& fp, int& m0) {
    if (c < 6) { fp = 2 + c; m0 = kM - N1; }
    else { fp = 8 + (c - 6) / 10; m0 = min(((c - 6) % 10) * N1, kM - N1); }
}

__device__ __forceinline__ void ll_fetch(u64 (&c)[4], const char* p) {
    asm volatile("ld.relaxed.gpu.global.b64 %0, [%4];\nld.relaxed.gpu.global.b64 %1, [%4 + 128];\n"
                 "ld.relaxed.gpu.global.b64 %2, [%4 + 512];\nld.relaxed.gpu.global.b64 %3, [%4 + 640];"
                 : "=l"(c[0]), "=l"(c[1]), "=l"(c[2]), "=l"(c[3]) : "l"(p) : "memory");
}
__device__ __forceinline__ void ll_copy(uint32_t dst, const char* src, uint32_t bar) {
    asm volatile("{\n.reg .pred p;\nelect.sync _|p, 0xffffffff;\n"
                 "@p cp.async.bulk.shared::cluster.global.mbarrier::complete_tx::bytes [%0], [%1], 1024, [%2];\n}\n"
                 ::"r"(dst), "l"(src), "r"(bar) : "memory");
}
__device__ __forceinline__ void ll_read(u64 (&c)[4], uint32_t a) {
    asm volatile("ld.volatile.shared.b64 %0, [%4];\nld.volatile.shared.b64 %1, [%4 + 128];\n"
                 "ld.volatile.shared.b64 %2, [%4 + 512];\nld.volatile.shared.b64 %3, [%4 + 640];"
                 : "=l"(c[0]), "=l"(c[1]), "=l"(c[2]), "=l"(c[3]) : "r"(a) : "memory");
}
template <int OFF>
__device__ __forceinline__ void ll_check(u64 (&c)[4], uint32_t a, const char* p, uint32_t tag) {
    asm volatile(
        "{\n.reg .pred p, q;\n.reg .b32 l, h0, h1, h2, h3, x, i, o;\n.reg .b64 g;\n"
        "mov.u32 i, 0;\n"
        "L_%=:\n"
        "mov.b64 {l, h0}, %0;\nmov.b64 {l, h1}, %1;\nmov.b64 {l, h2}, %2;\nmov.b64 {l, h3}, %3;\n"
        "lop3.b32 x, %6, h0, h1, 0x7e;\n"
        "lop3.b32 x, x, %6, h2, 0xf6;\n"
        "lop3.b32 x, x, %6, h3, 0xf6;\n"
        "setp.ne.u32 p, x, 0;\n"
        "vote.sync.any.pred p, p, 0xffffffff;\n"
        "@!p bra D_%=;\n"
        "and.b32 o, %4, 1023;\ncvt.u64.u32 g, o;\nadd.u64 g, g, %5;\n"
        "sub.u32 o, %6, 16;\n"
        "setp.eq.u32 q, h0, o;\nsetp.eq.or.u32 q, h1, o, q;\nsetp.eq.or.u32 q, h2, o, q;\nsetp.eq.or.u32 q, h3, o, q;\n"
        "setp.ge.or.u32 q, i, %8, q;\n"
        "vote.sync.any.pred q, q, 0xffffffff;\n"
        "@!q ld.volatile.shared.b64 %0, [%4 + %9];\n@!q ld.volatile.shared.b64 %1, [%4 + %9 + 128];\n"
        "@!q ld.volatile.shared.b64 %2, [%4 + %9 + 512];\n@!q ld.volatile.shared.b64 %3, [%4 + %9 + 640];\n"
        "@q ld.relaxed.gpu.global.b64 %0, [g];\n@q ld.relaxed.gpu.global.b64 %1, [g + 128];\n"
        "@q ld.relaxed.gpu.global.b64 %2, [g + 512];\n@q ld.relaxed.gpu.global.b64 %3, [g + 640];\n"
        "add.u32 i, i, 1;\n"
        "setp.lt.u32 p, i, %7;\n"
        "@p bra L_%=;\n"
        "D_%=:\n}\n"
        : "+l"(c[0]), "+l"(c[1]), "+l"(c[2]), "+l"(c[3])
        : "r"(a), "l"(p), "r"(tag), "n"(SPIN_LIMIT >> 4), "n"(NSPIN), "n"(OFF) : "memory");
}
__device__ __forceinline__ void ll_poll(u64 (&c)[4], const char* p, uint32_t tag) {
    unsigned it = 0;
    while (__any_sync(0xffffffffu, (((uint32_t)(c[0] >> 32) ^ tag) | ((uint32_t)(c[1] >> 32) ^ tag) |
                                    ((uint32_t)(c[2] >> 32) ^ tag) | ((uint32_t)(c[3] >> 32) ^ tag)) != 0) &&
           ++it < (SPIN_LIMIT >> 4))
        ll_fetch(c, p);
}
__device__ __forceinline__ void decode_alu(uint32_t& r0, uint32_t& r1, uint32_t& r2, uint32_t& r3, uint32_t w,
                                           const uint32_t (&lt)[8]) {
    const uint32_t s0 = w & 0x77777777u, s1 = s0 >> 16, w4 = w * 16;
    const uint32_t m0 = prmt(w4, w, 0xd9c8), m1 = prmt(w4, w, 0xfbea);
    const uint32_t l0 = (prmt(lt[0], lt[1], s0) & ~m0) | (prmt(lt[2], lt[3], s0) & m0);
    const uint32_t h0 = (prmt(lt[4], lt[5], s0) & ~m0) | (prmt(lt[6], lt[7], s0) & m0);
    const uint32_t l1 = (prmt(lt[0], lt[1], s1) & ~m1) | (prmt(lt[2], lt[3], s1) & m1);
    const uint32_t h1 = (prmt(lt[4], lt[5], s1) & ~m1) | (prmt(lt[6], lt[7], s1) & m1);
    r0 = prmt(l0, h0, 0x5140); r1 = prmt(l0, h0, 0x7362);
    r2 = prmt(l1, h1, 0x5140); r3 = prmt(l1, h1, 0x7362);
}
__device__ __forceinline__ void decode(uint32_t (&a)[16], const u64 (&c)[4], uint32_t tblv, const uint32_t (&lt)[8],
                                       const uint32_t (&mu)[4]) {
#pragma unroll
    for (int i = 0; i < 4; i++) {
        const int b = (i >> 1) * 8 + (i & 1);
        if (i < 4 - NALU) {
#pragma unroll
            for (int j = 0; j < 4; j++) a[b + 2 * j] = lds32(dp4a_u((uint32_t)c[i], mu[j], tblv));
        } else {
            decode_alu(a[b], a[b + 2], a[b + 4], a[b + 6], (uint32_t)c[i], lt);
        }
    }
}

__host__ __device__ constexpr int slot_of(int j) { return j < 16 ? j % 6 : (int)(0x6105342610532610ull >> (4 * (j - 16))) & 7; }
__host__ __device__ constexpr int slot_addr(int t, int s) {
    return t && (s < 2 || s == 6) ? (s == 6 ? 1 : 2 * s) * N1 * 128 : SLOT_OFF + s * SLOT_BYTES;
}
constexpr int JSTG = 25;
constexpr int STG_C0 = slot_addr(0, 6) - 2 * E0 * 128, STG_C1 = slot_addr(0, 4);
__host__ __device__ constexpr int loads_before(int j) {
    int n = 0;
    for (int i = 0; i < j; i++) n += slot_of(i) == slot_of(j);
    return n;
}
__host__ __device__ constexpr int uses_before(int j) {
    return loads_before(j) + (j >= 16 && (slot_of(j) == 4 || slot_of(j) == 5));
}
__host__ __device__ constexpr uint64_t prod_tbl(int j0) {
    uint64_t t = 0;
    for (int j = j0; j < j0 + 16; j++) t |= (uint64_t)(slot_of(j) | (((uses_before(j) + 1) & 1) << 3)) << (4 * (j - j0));
    return t;
}
__host__ __device__ constexpr uint64_t addr_tbl(int t) {
    uint64_t r = 0;
    for (int s = 0; s < NSLOTS; s++) r |= (uint64_t)(slot_addr(t, s) / 1024) << (8 * s);
    return r;
}
__host__ __device__ constexpr int dec_upto(int j) { return j < 14 ? j + 1 + (j >= RAMP1) + (j >= RAMP2) : j + 2 + (j >= RAMP3); }
__host__ __device__ constexpr bool ramp_first(int d) {
    return d == RAMP1 + 1 || d == RAMP2 + 2 || d == RAMP3 + 2;
}
__host__ __device__ constexpr int fetch_upto(int d) { return d + 2 + (d >= FR1); }
__host__ __device__ constexpr bool read_early(int d) {
    return d > RLATE && d < NSL && d != 18 && (d >= FR1 + 3 || (!ramp_first(d - 2) && !ramp_first(d - 3) && (d < 20 || d > RL2 || ramp_first(d) || ramp_first(d - 1)) && (d < RL3 || d > 16 || ramp_first(d) || ramp_first(d - 1))));
}
__host__ __device__ constexpr bool get_early(int d) { return ramp_first(d) && d <= FR1; }

__device__ __forceinline__ void fence_a(uint32_t (&a)[16]) {
#pragma unroll
    for (int i = 0; i < 16; i++) asm volatile("" : "+r"(a[i])::"memory");
}
template <int J, int N, int COL>
__device__ __forceinline__ void mma_slice(float (&acc)[N0 / 2], uint32_t (&a)[4][16]) {
    constexpr int off = (slot_addr(J / KSTEPS, slot_of(J)) + COL * 128) / 16, b = J % 4;
    constexpr uint64_t d0 = make_desc(SMEM_BASE);
    WG<N, COL / 2, (J % KSTEPS) != 0, N0 / 2>::mma(acc, a[b][0], a[b][1], a[b][2], a[b][3], d0 + off);
    WG<N, COL / 2, true, N0 / 2>::mma(acc, a[b][4], a[b][5], a[b][6], a[b][7], d0 + (off + 2));
    WG<N, COL / 2, true, N0 / 2>::mma(acc, a[b][8], a[b][9], a[b][10], a[b][11], d0 + (off + 4));
    WG<N, COL / 2, true, N0 / 2>::mma(acc, a[b][12], a[b][13], a[b][14], a[b][15], d0 + (off + 6));
}
template <int N> __device__ __forceinline__ void rename_acc(float (&acc)[N0 / 2]) {
#pragma unroll
    for (int i = 0; i < N / 2; i++) asm volatile("mov.b32 %0, %1;" : "=f"(acc[i]) : "f"(acc[i]) : "memory");
}
template <int N, int COL, bool FENCE>
__device__ __forceinline__ void stage_out(float (&acc)[N0 / 2], uint32_t sa, const float s0, const float s1) {
#pragma unroll
    for (int i = COL / 2; i < (COL + N) / 2; i++) asm volatile("" : "+f"(acc[i])::"memory");
#pragma unroll
    for (int j = COL / 8; j + 1 < (COL + N) / 8; j += 2) {
        const uint32_t r0 = pack_bf16x2(acc[4 * j + 0] * s0, acc[4 * j + 1] * s0);
        const uint32_t r1 = pack_bf16x2(acc[4 * j + 2] * s1, acc[4 * j + 3] * s1);
        const uint32_t r2 = pack_bf16x2(acc[4 * j + 4] * s0, acc[4 * j + 5] * s0);
        const uint32_t r3 = pack_bf16x2(acc[4 * j + 6] * s1, acc[4 * j + 7] * s1);
        asm volatile("stmatrix.sync.aligned.m8n8.x4.trans.shared.b16 [%0], {%1, %2, %3, %4};"
                     ::"r"(sa + j * 1024), "r"(r0), "r"(r1), "r"(r2), "r"(r3) : "memory");
    }
    if constexpr ((N / 8) & 1) {
        constexpr int j = (COL + N) / 8 - 1;
        const uint32_t r0 = pack_bf16x2(acc[4 * j + 0] * s0, acc[4 * j + 1] * s0);
        const uint32_t r1 = pack_bf16x2(acc[4 * j + 2] * s1, acc[4 * j + 3] * s1);
        asm volatile("stmatrix.sync.aligned.m8n8.x2.trans.shared.b16 [%0], {%1, %2};"
                     ::"r"(sa + j * 1024), "r"(r0), "r"(r1) : "memory");
    }
    if constexpr (FENCE) asm volatile("fence.proxy.async.shared::cta;" ::: "memory");
}

struct Maps { CUtensorMap m[5 + NCH]; };

__global__ void __cluster_dims__(2, 1, 1) __launch_bounds__(NUM_THREADS, 1)
nf4_gemm_kernel(const int* __restrict__ qw, u64* __restrict__ ll, unsigned* __restrict__ epoch,
                const __nv_bfloat16* __restrict__ lut, const __nv_bfloat16* __restrict__ scales,
                const __grid_constant__ Maps tm) {
    extern __shared__ __align__(1024) uint8_t smem_raw[];
    const uint32_t t_start = clock32();
    const int lane = threadIdx.x & 31;
    if (threadIdx.x < 32)
        asm volatile("prefetch.global.L2 [%0];" ::"l"(add_off(qw, unit_src(blockIdx.x / W1_FG, blockIdx.x % W1_FG) + lane * (kN * 4))) : "memory");
    const int warp = __shfl_sync(0xffffffffu, threadIdx.x >> 5, 0);
    const uint32_t sb = smem_u32(smem_raw);
    const uint32_t bar_full = sb + BAR_OFF;
    const uint32_t bar_empty = bar_full + NSLOTS * 8;
    const uint32_t bar_tbl = bar_empty + NSLOTS * 8;
    const uint32_t bar_code = bar_tbl + 8;
    const uint32_t bar_stg = bar_code + 8;
    const int crank = blockIdx.x & 1, cluster = blockIdx.x >> 1;

    if (warp == 1) {
        if (lane == 0) {
            for (int i = 0; i < 2 * (2 + NCH); i++) mbar_init(bar_stg + i * 8, 128);
            asm volatile("fence.mbarrier_init.release.cluster;" ::: "memory");
        }
        __syncwarp();
    }
    if (warp != 8) cluster_arrive_relaxed();
    if (warp < 8) {
        const int wg = warp >> 2;
        const uint32_t tagl = ld_ca_u32(epoch + lane);
        const uint32_t lv = ldg_u16(reinterpret_cast<const unsigned short*>(lut) + (lane & 15));
        int fp0, fp1, mm;
        tile0_of(cluster, fp0, mm);
        tile1_of(cluster, fp1, mm);
        const int ft0 = fp0 * 2 + crank, ft1 = fp1 * 2 + crank;
        const unsigned short* sc16 = reinterpret_cast<const unsigned short*>(scales) + warp * 16 + (lane >> 2);
        uint32_t sc0 = ldg_u16(sc16 + ft0 * FT), sc0h = ldg_u16(sc16 + ft0 * FT + 8);
        uint32_t sc1 = ldg_u16(sc16 + ft1 * FT), sc1h = ldg_u16(sc16 + ft1 * FT + 8);
        {
            constexpr int EPS = 128 / TBLC;
#pragma unroll
            for (int k = 0; k < 32 / EPS; k++) {
                const int e = warp * 32 + k * EPS + lane / (TBLC / 4);
                const uint32_t v = __shfl_sync(0xffffffffu, lv, e & 15) | (__shfl_sync(0xffffffffu, lv, e >> 4) << 16);
                asm volatile("st.shared.v4.u32 [%0], {%1, %1, %1, %1};"
                             ::"r"(sb + TBL_OFF + warp * (TBLC * 128) + k * 512 + lane * 16), "r"(v) : "memory");
            }
        }
        asm volatile("setmaxnreg.inc.sync.aligned.u32 %0;" ::"n"(CREGS));
        cluster_wait();
        mbar_arrive(bar_tbl);
        TS(132);
        sc0 |= sc0h << 16;
        sc1 |= sc1h << 16;
        const char* ll0 = keep(reinterpret_cast<const char*>(ll) + (ft0 * (KSTEPS * 8192) + warp * 1024 + lane), 0);
        const char* ll1 = keep(reinterpret_cast<const char*>(ll) + (ft1 * (KSTEPS * 8192) + warp * 1024 + lane), 0);
        const uint32_t cbuf = sb + COD_OFF + warp * 1024;
        const uint32_t tblv = keep(sb + TBL_OFF + (lane % TBLC) * 4, lane);
        const uint32_t cempty = keep(lane < 2 ? mapa(bar_empty, lane) : 0, lane);
        const uint32_t sa0 = keep(sb + (((lane >> 4) * 8 + (lane & 7)) * 128) +
                                  ((((warp & 3) * 2 + ((lane >> 3) & 1)) ^ (lane & 7)) << 4), lane);
        uint32_t lt[8];
        {
            const uint32_t p01 = __shfl_sync(0xffffffffu, lv, 4 * lane) | (__shfl_sync(0xffffffffu, lv, 4 * lane + 1) << 16);
            const uint32_t p23 = __shfl_sync(0xffffffffu, lv, 4 * lane + 2) | (__shfl_sync(0xffffffffu, lv, 4 * lane + 3) << 16);
            const uint32_t pl = prmt(p01, p23, lane & 4 ? 0x7531 : 0x6420);
#pragma unroll
            for (int i = 0; i < 8; i++) lt[i] = __shfl_sync(0xffffffffu, pl, i & 1 ? i : i + (lane & 24));
        }
        uint32_t mu[4];
#pragma unroll
        for (int j = 0; j < 4; j++) mu[j] = keep(((uint32_t)(TBLC * 4) << (8 * j)) + lane, 0);
        uint32_t a[4][16];
        float acc[N0 / 2];

        auto src = [&](auto dc) {
            constexpr int D = decltype(dc)::value;
            return (D < KSTEPS ? ll0 : ll1) + (D % KSTEPS) * 8192;
        };
        const uint32_t tag = __shfl_sync(0xffffffffu, tagl, 0);
        u64 c[4];
        const uint32_t aw = keep(cbuf + lane_unit(lane), lane);
        auto fetch = [&](auto dc) {
            constexpr int D = decltype(dc)::value;
            if constexpr (D < NGATE) delay_until(t_start, gate_time(D));
            if constexpr (D < NSL) ll_copy(cbuf + (D % NBUF) * 8192, src(dc), bar_code);
        };
        auto get = [&](auto dc) {
            constexpr int D = decltype(dc)::value;
            if constexpr (D + 1 <= FLATE) fetch(IC<D + 1>{});
            if constexpr (!read_early(D)) ll_read(c, aw + (D % NBUF) * 8192);
            ll_check<(D % NBUF) * 8192>(c, aw, src(dc), tag + D % KSTEPS);
            if constexpr (D + 2 >= NGATE) static_for<fetch_upto(D - 1) + 1, fetch_upto(D) + 1>(fetch);
        };
        auto dec = [&](auto dc) {
            constexpr int D = decltype(dc)::value;
            decode(a[D % 4], c, tblv, lt, mu);
            if constexpr (D + 2 > FLATE && D + 2 < NGATE) fetch(IC<D + 2>{});
            if constexpr (read_early(D + 1)) ll_read(c, aw + ((D + 1) % NBUF) * 8192);
            if constexpr (get_early(D + 1)) get(IC<D + 1>{});
        };
        auto wait_full = [&](auto jc) {
            constexpr int J = decltype(jc)::value;
            mbar_wait(bar_full + slot_of(J) * 8, loads_before(J) & 1);
        };
        auto release = [&](auto jc) {
            constexpr int J = decltype(jc)::value;
            if constexpr (J <= JSTG + 1) mbar_arrive_pair(cempty + slot_of(J) * 8, cempty);
        };
        auto step = [&](auto jc) {
            constexpr int J = decltype(jc)::value, D = dec_upto(J - 1) + 1;
            fence_a(a[J % 4]);
            wgmma_fence();
            mma_slice<J, (J < KSTEPS ? N0 : N1), 0>(acc, a);
            wgmma_commit();
            TS(J);
            if constexpr (!get_early(D)) get(IC<D>{});
            if constexpr (J >= NEARLY) wait_full(IC<J + 1>{});
            wgmma_wait<1>();
            if constexpr (J != 0 && J != 18) release(IC<J - 1>{});
            dec(IC<D>{});
            if constexpr (dec_upto(J) > D) { get(IC<D + 1>{}); dec(IC<D + 1>{}); }
            if constexpr (J < NEARLY) wait_full(IC<J + 1>{});
        };
        static_assert(FLATE >= 1 && FLATE < NGATE && RLATE >= FLATE && RLATE < RAMP1 && RAMP1 + 2 < RAMP2 && RAMP2 < 14 &&
                      RAMP3 > 20 && RAMP3 < 28, "code schedule");
        static_assert(slot_of(10) == 4 && slot_of(11) == 5 && uses_before(11) == 1 && STG_C1 + 2 * E1 * 128 <= STG_C0, "staging");

        mbar_wait(bar_tbl, 0);
        TS(133);
        delay_until(t_start, gate_time(0));
        ll_fetch(c, src(IC<0>{}) + (aw & 1023));
        fetch(IC<1>{});
        ll_poll(c, src(IC<0>{}) + (aw & 1023), tag);
        dec(IC<0>{});
        TS(134);
        wait_full(IC<0>{});
        TS(137);
        static_for<0, 14>(step);
        {
            const float s0 = __uint_as_float(sc0 << 16), s1 = __uint_as_float(sc0 & 0xffff0000u);
            const uint32_t sa = sa0 + STG_C0 + wg * (E0 * 128), sc = sa0 + STG_C1 - E0 * 128 + wg * (E1 * 128);
            auto group = [&](auto jc, auto nc, auto cc) {
                fence_a(a[decltype(jc)::value % 4]);
                wgmma_fence();
                mma_slice<decltype(jc)::value, decltype(nc)::value, decltype(cc)::value>(acc, a);
                wgmma_commit();
            };
            wait_full(IC<15>{});
            TS(140);
            wgmma_wait<0>();
            rename_acc<N0>(acc);
            group(IC<14>{}, IC<E0>{}, IC<0>{});
            release(IC<13>{});
            get(IC<17>{});
            mbar_wait(bar_empty + 5 * 8, 1);
            group(IC<15>{}, IC<E0>{}, IC<0>{});
            TS(14);
            dec(IC<17>{});
            TS(141);
            group(IC<14>{}, IC<E1>{}, IC<E0>{});
            TS(15);
            wgmma_wait<1>();
            stage_out<EI, 0, false>(acc, sa, s0, s1);
            group(IC<15>{}, IC<E1>{}, IC<E0>{});
            TS(142);
            wait_full(IC<16>{});
            wgmma_wait<1>();
            release(IC<14>{});
            TS(143);
            stage_out<E0 - EI, EI, true>(acc, sa, s0, s1);
            mbar_arrive(bar_stg + wg * 8);
            TS(144);
            group(IC<16>{}, IC<S0>{}, IC<0>{});
            wait_full(IC<17>{});
            wgmma_wait<1>();
            release(IC<15>{});
            TS(16);
            stage_out<EI, E0, false>(acc, sc, s0, s1);
            group(IC<17>{}, IC<S0>{}, IC<0>{});
            TS(128);
            stage_out<E1 - EI, E0 + EI, true>(acc, sc, s0, s1);
            mbar_arrive(bar_stg + 16 + wg * 8);
            TS(129);
            group(IC<16>{}, IC<S1>{}, IC<S0>{});
            get(IC<18>{}); dec(IC<18>{});
            group(IC<17>{}, IC<S1>{}, IC<S0>{});
            TS(17);
            get(IC<19>{});
            wait_full(IC<18>{});
            wgmma_wait<1>();
            release(IC<16>{});
            dec(IC<19>{});
            TS(145);
            wgmma_wait<0>();
            rename_acc<N1>(acc);
            release(IC<17>{});
            TS(146);
        }
        static_for<18, NSL - 4>(step);
        {
            constexpr int J0 = NSL - 4;
            const float s0 = __uint_as_float(sc1 << 16), s1 = __uint_as_float(sc1 & 0xffff0000u);
            const uint32_t sa = sa0 + (wg ? slot_addr(1, slot_of(JSTG + 1)) : slot_addr(1, slot_of(JSTG)));
            wait_full(IC<J0 + 1>{}); wait_full(IC<J0 + 2>{});
            fence_a(a[0]); fence_a(a[1]); fence_a(a[2]);
            TS(160);
            wgmma_wait<0>();
            rename_acc<N1>(acc);
            wgmma_fence();
            mma_slice<J0, chunk_n(0), 0>(acc, a);
            TS(J0);
            release(IC<J0 - 1>{});
            get(IC<NSL - 1>{}); dec(IC<NSL - 1>{});
            asm volatile("{\n.reg .pred p;\nelect.sync _|p, 0xffffffff;\n"
                         "@p mbarrier.arrive.expect_tx.shared::cta.b64 _, [%0], %1;\n}\n" ::"r"(bar_code), "n"((NSL - 1) * 1024) : "memory");
            wgmma_fence();
            mma_slice<J0 + 1, chunk_n(0), 0>(acc, a);
            mma_slice<J0 + 2, chunk_n(0), 0>(acc, a);
            wait_full(IC<NSL - 1>{});
            fence_a(a[3]);
            wgmma_fence();
            mma_slice<J0 + 3, chunk_n(0), 0>(acc, a);
            wgmma_commit();
            static_for<1, NCH + 1>([&](auto cc) {
                constexpr int C = decltype(cc)::value;
                if constexpr (C < NCH) {
                    wgmma_fence();
                    mma_slice<J0, chunk_n(C), chunk_col(C)>(acc, a);
                    wgmma_commit();
                    if constexpr (C == 1)
                        mbar_wait(bar_empty + (wg ? slot_of(JSTG + 1) : slot_of(JSTG)) * 8, (wg ? uses_before(JSTG + 1) : uses_before(JSTG)) & 1);
                    wgmma_wait<1>();
                } else {
                    wgmma_wait<0>();
                    TS(130);
                }
                stage_out<chunk_n(C - 1), chunk_col(C - 1), true>(acc, sa, s0, s1);
                mbar_arrive(bar_stg + (1 + C) * 16 + wg * 8);
                if constexpr (C < NCH) {
                    wgmma_fence();
                    static_for<J0 + 1, NSL>([&](auto jc) { mma_slice<decltype(jc)::value, chunk_n(C), chunk_col(C)>(acc, a); });
                    wgmma_commit();
                    if constexpr (C < 4) TS(J0 + C);
                }
            });
            TS(131);
        }
    } else {
      if (warp >= 9) {
        {
            const int pw = warp - 9;
            int u = pw * NUM_CTAS + blockIdx.x;
            uint32_t q = u / W1_FG, fg = u % W1_FG;
            const int* qwk = keep(add_off(qw, lane_src(lane)), lane);
            u64* llk = keep(add_off(ll, lane_dst(lane)), lane);
            const unsigned* ep = epoch + lane;
            asm volatile("setmaxnreg.dec.sync.aligned.u32 %0;" ::"n"(504 - 2 * CREGS));
            const uint32_t tag = ld_ca_u32(ep);
            if (pw > 0) delay_until(t_start, DLY_R0 + pw * DLY_R);
            uint4 v[8];
            load_unit(v, add_off(qwk, unit_src(q, fg)));
#pragma unroll 1
            for (;;) {
                u64* dst = add_off(llk, unit_dst(q, fg));
                const uint32_t sl = q >> 1;
                static_assert(RSTOP % NUM_AUX == 0, "pack rounds");
                u += u < (RSTOP - 1) * NUM_CTAS ? NUM_AUX * NUM_CTAS : pw == 2 ? NUM_UNITS : 2 * NUM_CTAS;
                unit_pos(min(u, NUM_UNITS - 1), q, fg);
                const int* p = add_off(qwk, unit_src(q, fg));
                uint32_t e[4], o[4], w[4];
                pk_gather(e, o, v);
#pragma unroll
                for (int k = 0; k < 4; k++)
                    asm("lop3.b32 %0, %1, %2, 0x0f0f0f0f, 0xe4;" : "=r"(w[k]) : "r"(e[k]), "r"(o[k] << 4));
                ll_store2(dst, w[0], w[1], tag + sl);
                ll_store2((u64*)((uint64_t)dst ^ 320), w[2], w[3], tag + sl);
                if (u >= NUM_UNITS) break;
                load_unit(v, p);
            }
        }
        const CUtensorMap* maps = keep(&tm.m[3] + lane, 0);
        named_bar_arrive<4, 128>();
        cluster_wait();
        int fp, m0;
        if (warp == 11) {
            tile0_of(cluster, fp, m0);
            const int f0 = (fp * 2 + crank) * FT;
#pragma unroll 1
            for (int ch = 0; ch < 2; ch++) {
                const uint32_t src = sb + (ch ? STG_C1 : STG_C0);
                const int rows = ch ? E1 : E0, step = ch ? BX1 : BX0;
                int h = 0;
#pragma unroll 1
                for (unsigned it = 0; it < 16 * SPIN_LIMIT && !mbar_test(bar_stg + ch * 16 + h * 8, 0); it++) { h ^= 1; __nanosleep(20); }
#pragma unroll 1
                for (int k = 0; k < 2; k++, h ^= 1) {
                    mbar_wait(bar_stg + ch * 16 + h * 8, 0);
#pragma unroll 1
                    for (int r = 0; r < rows; r += step) {
                        asm volatile("{\n.reg .pred p;\nelect.sync _|p, 0xffffffff;\n"
                                     "@p cp.async.bulk.tensor.2d.global.shared::cta.bulk_group [%0, {%2, %3}], [%1];\n"
                                     "cp.async.bulk.commit_group;\ncp.async.bulk.wait_group.read 1;\n}\n"
                                     ::"l"(maps + ch), "r"(src + (h * rows + r) * 128), "r"(f0 + h * 64), "r"(m0 + ch * E0 + r)
                                     : "memory");
                    }
                }
                asm volatile("cp.async.bulk.wait_group.read 0;" ::: "memory");
                __syncwarp();
                if (lane < 2) mbar_arrive_cluster_n(mapa(bar_empty + (5 - ch) * 8, lane), 8);
                TSG(604 + ch * 2);
            }
        } else {
            const int wg = warp - 9;
            tile1_of(cluster, fp, m0);
            const int f0 = (fp * 2 + crank) * FT + wg * 64;
            const uint32_t src = sb + (wg ? slot_addr(1, slot_of(JSTG + 1)) : slot_addr(1, slot_of(JSTG)));
            int r0 = 0;
#pragma unroll 1
            for (int ch = 0; ch < NCH; ch++) {
                mbar_wait(bar_stg + (2 + ch) * 16 + wg * 8, 0);
                asm volatile("{\n.reg .pred p;\nelect.sync _|p, 0xffffffff;\n"
                             "@p cp.async.bulk.tensor.2d.global.shared::cta.bulk_group [%0, {%2, %3}], [%1];\n}\n"
                             ::"l"(maps + 2 + ch), "r"(src + r0 * 128), "r"(f0), "r"(m0 + r0) : "memory");
                r0 += ((CHK >> (4 * ch)) & 15) * 8;
            }
            asm volatile("cp.async.bulk.commit_group;\ncp.async.bulk.wait_group.read 0;" ::: "memory");
            TSG(600 + wg * 2);
        }
      } else {
        asm volatile("setmaxnreg.dec.sync.aligned.u32 %0;" ::"n"(504 - 2 * CREGS));
        if ((sb & 0xFFFFFF) != SMEM_BASE) __trap();
        if (lane == 0) {
            for (int s = 0; s < NSLOTS; s++) {
                mbar_init(bar_full + s * 8, 1);
                mbar_init(bar_empty + s * 8, 16);
            }
            mbar_init(bar_tbl, 256);
            mbar_init(bar_code, 8);
            asm volatile("fence.mbarrier_init.release.cluster;" ::: "memory");
        }
        __syncwarp();
        cluster_arrive_relaxed();
        const CUtensorMap* maps = keep(&tm.m[0] + lane, 0);
        unsigned* epk = keep(epoch + lane, 0);
        if (lane == 0) prefetch_map(maps + crank);
        TSG(512);
        int fp, m0;
        tile0_of(cluster, fp, m0);
        cluster_wait();
#pragma unroll 1
        for (int t = 0; t < 2; t++) {
            const int lo = t == 0 ? 120 : 104, row = m0 + crank * lo;
            const CUtensorMap* map = maps + (t ? 2 : crank);
            const uint32_t bytes = (t ? N1 : N0) * 128, dst = sb + crank * lo * 128;
            uint64_t tbl = t ? prod_tbl(16) : prod_tbl(0);
            const uint64_t adr = t ? addr_tbl(1) : addr_tbl(0);
#pragma unroll 1
            for (int ks = 0; ks < KSTEPS; ks++, tbl >>= 4) {
                const uint32_t slot = (uint32_t)tbl & 7;
                if (t == 0 && ks > 0 && ks < 6) delay_until(t_start, DLY_X0 + ks * DLY_XS);
                mbar_wait(bar_empty + slot * 8, ((uint32_t)tbl >> 3) & 1);
                asm volatile(
                    "{\n.reg .pred p;\nelect.sync _|p, 0xffffffff;\n"
                    "@p mbarrier.arrive.expect_tx.shared::cta.b64 _, [%2], %5;\n"
                    "@p cp.async.bulk.tensor.2d.shared::cluster.global.mbarrier::complete_tx::bytes.multicast::cluster"
                    " [%0], [%1, {%3, %4}], [%2], %6;\n}\n"
                    ::"r"(dst + (((uint32_t)(adr >> (8 * slot)) & 255) << 10)), "l"(map), "r"(bar_full + slot * 8), "r"(ks * BK), "r"(row), "r"(bytes),
                    "h"((uint16_t)3) : "memory");
                TSG(514 + (t * 18 + ks) * 2);
            }
            tile1_of(cluster, fp, m0);
            if (t == 0 && lane >= 2 && lane < 5 + NCH) prefetch_map(maps + lane);
        }
        named_bar_sync<4, 128>();
        const uint32_t tag = ld_ca_u32(epk + lane);
        unsigned old = 0;
        if (lane == 0) old = atomicAdd(epk + 32, tag != 0 ? 1u : 0u);
        if (__shfl_sync(0xffffffffu, old, 0) == NUM_CTAS - 1) {
            if (lane == 0) epk[32] = 0;
            epk[lane] = tag == 0xfffffff0u ? 16 : tag + 16;
        }
        mbar_wait(bar_code, 0);
      }
    }
}

__global__ void generic_kernel(const __nv_bfloat16* __restrict__ x, const int* __restrict__ qw,
                               const __nv_bfloat16* __restrict__ lut, const __nv_bfloat16* __restrict__ scales,
                               __nv_bfloat16* __restrict__ out, int M, int N, int K, int G) {
    const int n = blockIdx.x * blockDim.x + threadIdx.x;
    const int m = blockIdx.y;
    if (n >= N) return;
    float acc = 0.f;
    for (int k = 0; k < K; k++) {
        const float l = __bfloat162float(lut[qw[(size_t)k * N + n] & 15]);
        const float s = __bfloat162float(scales[(size_t)(k / G) * N + n]);
        const float w = __bfloat162float(__float2bfloat16_rn(l * s));
        acc += __bfloat162float(x[(size_t)m * K + k]) * w;
    }
    out[(size_t)m * N + n] = __float2bfloat16_rn(acc);
}

typedef CUresult (*PFN_encodeTiled)(CUtensorMap*, CUtensorMapDataType, cuuint32_t, void*, const cuuint64_t*,
                                    const cuuint64_t*, const cuuint32_t*, const cuuint32_t*, CUtensorMapInterleave,
                                    CUtensorMapSwizzle, CUtensorMapL2promotion, CUtensorMapFloatOOBfill);

bool make_map_2d(PFN_encodeTiled fn, CUtensorMap* map, void* base, uint64_t inner, uint64_t outer, uint32_t box_inner,
                 uint32_t box_outer) {
    cuuint64_t dims[2] = {inner, outer};
    cuuint64_t strides[1] = {inner * 2};
    cuuint32_t box[2] = {box_inner, box_outer};
    cuuint32_t estr[2] = {1, 1};
    return fn(map, CU_TENSOR_MAP_DATA_TYPE_BFLOAT16, 2, base, dims, strides, box, estr, CU_TENSOR_MAP_INTERLEAVE_NONE,
              CU_TENSOR_MAP_SWIZZLE_128B, CU_TENSOR_MAP_L2_PROMOTION_L2_128B,
              CU_TENSOR_MAP_FLOAT_OOB_FILL_NONE) == CUDA_SUCCESS;
}

}

extern "C" void kernel_launch(void* const* d_in, const int* in_sizes, int n_in, void* d_out, int out_size) {
    const __nv_bfloat16* x = (const __nv_bfloat16*)d_in[0];
    const int* qw = (const int*)d_in[1];
    const __nv_bfloat16* lut = (const __nv_bfloat16*)d_in[2];
    const __nv_bfloat16* scales = (const __nv_bfloat16*)d_in[3];
    __nv_bfloat16* out = (__nv_bfloat16*)d_out;

    const double Kd = sqrt((double)in_sizes[0] * (double)in_sizes[1] / (double)out_size);
    const int K = (int)(Kd + 0.5);
    const int M = in_sizes[0] / K, N = in_sizes[1] / K;
    const int ng = in_sizes[3] / N;
    const int G = K / ng;

    bool fast = (M == kM && N == kN && K == kK && ng == 1 && in_sizes[2] >= 16);
    PFN_encodeTiled enc = nullptr;
    Maps tm;
    void *ll = nullptr, *epoch = nullptr;
    if (fast) {
        cudaDriverEntryPointQueryResult qres;
        void* fp = nullptr;
        if (cudaGetDriverEntryPoint("cuTensorMapEncodeTiled", &fp, cudaEnableDefault, &qres) != cudaSuccess || !fp) fast = false;
        enc = (PFN_encodeTiled)fp;
    }
    if (fast) {
        fast = make_map_2d(enc, &tm.m[0], (void*)x, kK, kM, BK, 120) &&
               make_map_2d(enc, &tm.m[1], (void*)x, kK, kM, BK, 112) &&
               make_map_2d(enc, &tm.m[2], (void*)x, kK, kM, BK, 104) &&
               make_map_2d(enc, &tm.m[3], (void*)out, kN, kM, 64, BX0) &&
               make_map_2d(enc, &tm.m[4], (void*)out, kN, kM, 64, BX1) &&
               cudaGetSymbolAddress(&ll, g_ll) == cudaSuccess && cudaGetSymbolAddress(&epoch, g_epoch) == cudaSuccess;
    }
    for (int c = 0; c < NCH && fast; c++) fast = make_map_2d(enc, &tm.m[5 + c], (void*)out, kN, kM, 64, chunk_n(c));
    cudaLaunchConfig_t cfg = {};
    cfg.gridDim = dim3(NUM_CTAS);
    cfg.blockDim = dim3(NUM_THREADS);
    cfg.dynamicSmemBytes = SMEM_TOTAL;
    cfg.stream = cudaStreamPerThread;
    if (fast) {
        int nclusters = 0;
        fast = cudaFuncSetAttribute(nf4_gemm_kernel, cudaFuncAttributeMaxDynamicSharedMemorySize, SMEM_TOTAL) == cudaSuccess &&
               cudaOccupancyMaxActiveClusters(&nclusters, nf4_gemm_kernel, &cfg) == cudaSuccess &&
               nclusters >= NUM_CTAS / 2;
    }
    if (!fast) {
        generic_kernel<<<dim3((N + 127) / 128, M), 128>>>(x, qw, lut, scales, out, M, N, K, G);
        return;
    }
    cudaLaunchKernelEx(&cfg, nf4_gemm_kernel, qw, (u64*)ll, (unsigned*)epoch, lut, scales, tm);
}
```

```cpp
#include <cuda_runtime.h>
#include <cuda_bf16.h>
#include <cuda.h>
#include <stdint.h>
#include <stdio.h>
#include <math.h>

namespace {

constexpr int kM = 2048, kN = 3584, kK = 1024;
constexpr int FT = 128;
constexpr int N0 = 232, N1 = 208;
constexpr int BK = 64, KSTEPS = kK / BK;
constexpr int NSL = 2 * KSTEPS;
constexpr int NSLOTS = 7;
constexpr int SLOT_BYTES = N0 * 128;
constexpr int SLOT_OFF = 3 * N1 * 128 - 2 * SLOT_BYTES;
#define TBLC 16
constexpr int TBL_OFF = SLOT_OFF + 6 * SLOT_BYTES;
constexpr int COD_OFF = TBL_OFF + TBLC * 1024;
constexpr int BAR_OFF = COD_OFF + 2 * 8192;
constexpr int SMEM_TOTAL = BAR_OFF + 256;
constexpr int NUM_THREADS = 384;
constexpr int NUM_CTAS = 132;
constexpr int NUM_AUX = 3;
constexpr int CREGS = 224;
constexpr int NQ = kK / 32, NUM_UNITS = NQ * (kN / 32);
constexpr int W1_FG = 64, W2_FG = kN / 32 - W1_FG;
#define DLY_R0 200
#define DLY_R 400
#define DLY_X0 1000
#define DLY_XS 900
#define DLY_POLL 2600
#define DLY_P1 3200
#define DLY_PS 700
#define NGATE 8
#define FLATE 3
#define RLATE 4
#define NEARLY 4
#define RAMP1 8
#define RAMP2 12
#define RAMP3 24
#define NSPIN 24
#define NALU 2
#define RSTOP 18
#define EI 64
constexpr int E0 = 120, E1 = N0 - E0, S0 = 112, S1 = N1 - S0;
#define CHK 0x4688
__host__ __device__ constexpr int chunk_n(int c) { return ((CHK >> (4 * c)) & 15) * 8; }
__host__ __device__ constexpr int chunk_col(int c) { return c ? chunk_col(c - 1) + chunk_n(c - 1) : 0; }
constexpr int NCH = CHK > 0xfffff ? 6 : CHK > 0xffff ? 5 : CHK > 0xfff ? 4 : 3;
static_assert(chunk_col(NCH) == N1 && S0 <= E0, "chunks");
constexpr unsigned SPIN_LIMIT = 1u << 20;

__device__ __align__(1024) unsigned long long g_ll[(size_t)(kN / FT) * NQ * FT * 4];
__device__ __align__(256) unsigned int g_epoch[64] = {16, 16, 16, 16, 16, 16, 16, 16, 16, 16, 16, 16, 16, 16, 16, 16,
                                                      16, 16, 16, 16, 16, 16, 16, 16, 16, 16, 16, 16, 16, 16, 16, 16};

#define TS(idx) do {} while (0)
#define TSW(idx) do {} while (0)
#define TSG(idx) do {} while (0)

template <int I> struct IC { static constexpr int value = I; };
template <int B, int E, class F> __device__ __forceinline__ void static_for(F&& f) {
    if constexpr (B < E) { f(IC<B>{}); static_for<B + 1, E>(f); }
}

__device__ __forceinline__ uint32_t smem_u32(const void* p) { return (uint32_t)__cvta_generic_to_shared(p); }
__device__ __forceinline__ uint32_t keep(uint32_t v, int lane) {
    asm volatile("shfl.sync.idx.b32 %0, %0, %1, 0x1f, 0xffffffff;" : "+r"(v) : "r"(lane));
    return v;
}
template <class T> __device__ __forceinline__ T* keep(T* p, int lane) {
    const uint64_t v = (uint64_t)p;
    return (T*)(((uint64_t)keep((uint32_t)(v >> 32), lane) << 32) | keep((uint32_t)v, lane));
}
__device__ __forceinline__ void mbar_init(uint32_t bar, uint32_t count) {
    asm volatile("mbarrier.init.shared::cta.b64 [%0], %1;" ::"r"(bar), "r"(count) : "memory");
}
__device__ __forceinline__ uint32_t clock32() { uint64_t c; asm volatile("mov.u64 %0, %%clock64;" : "=l"(c)); return (uint32_t)c; }
__device__ __forceinline__ void mbar_arrive(uint32_t bar) {
    asm volatile("mbarrier.arrive.shared::cta.b64 _, [%0];" ::"r"(bar) : "memory");
}
__device__ __forceinline__ uint32_t mapa(uint32_t a, uint32_t rank) {
    uint32_t r;
    asm("mapa.shared::cluster.u32 %0, %1, %2;" : "=r"(r) : "r"(a), "r"(rank));
    return r;
}
__device__ __forceinline__ void mbar_arrive_pair(uint32_t cbar, uint32_t base) {
    asm volatile("{\n.reg .pred p;\nsetp.ne.u32 p, %1, 0;\n@p mbarrier.arrive.shared::cluster.b64 _, [%0];\n}\n"
                 ::"r"(cbar), "r"(base) : "memory");
}
__device__ __forceinline__ void mbar_arrive_cluster_n(uint32_t cbar, uint32_t n) {
    asm volatile("mbarrier.arrive.shared::cluster.b64 _, [%0], %1;" ::"r"(cbar), "r"(n) : "memory");
}
__device__ __forceinline__ void delay_until(uint32_t t0, int clks) {
    while (__any_sync(0xffffffffu, (int)(clock32() - t0) < clks)) {}
}
__device__ __forceinline__ bool mbar_test(uint32_t bar, uint32_t parity) {
    uint32_t ok;
    asm volatile("{\n.reg .pred p;\nmbarrier.test_wait.parity.shared::cta.b64 p, [%1], %2;\nvote.sync.all.pred p, p, 0xffffffff;\nselp.u32 %0, 1, 0, p;\n}\n"
                 : "=r"(ok) : "r"(bar), "r"(parity) : "memory");
    return ok != 0;
}
__device__ __forceinline__ void mbar_wait(uint32_t bar, uint32_t parity) {
    asm volatile(
        "{\n.reg .pred p;\n.reg .u32 i;\n"
        "mbarrier.try_wait.parity.shared::cta.b64 p, [%0], %1;\n"
        "@p bra D_%=;\n"
        "mov.u32 i, 0;\n"
        "L_%=:\n"
        "mbarrier.try_wait.parity.shared::cta.b64 p, [%0], %1;\n"
        "@p bra D_%=;\n"
        "add.u32 i, i, 1;\n"
        "setp.lt.u32 p, i, %2;\n"
        "@p bra L_%=;\n"
        "D_%=:\n}\n"
        ::"r"(bar), "r"(parity), "n"(SPIN_LIMIT) : "memory");
}
__device__ __forceinline__ void prefetch_map(const CUtensorMap* map) {
    asm volatile("prefetch.tensormap [%0];" ::"l"(map) : "memory");
}
constexpr uint32_t SMEM_BASE = 1024;
__host__ __device__ constexpr uint64_t make_desc(uint32_t saddr) {
    return (uint64_t)((saddr & 0x3FFFF) >> 4) | ((uint64_t)1 << 16) | ((uint64_t)(1024 >> 4) << 32) | ((uint64_t)1 << 62);
}
__device__ __forceinline__ void wgmma_fence() { asm volatile("wgmma.fence.sync.aligned;" ::: "memory"); }
__device__ __forceinline__ void wgmma_commit() { asm volatile("wgmma.commit_group.sync.aligned;" ::: "memory"); }
template <int N> __device__ __forceinline__ void wgmma_wait() {
    asm volatile("wgmma.wait_group.sync.aligned %0;" ::"n"(N) : "memory");
}
__device__ __forceinline__ uint32_t pack_bf16x2(float lo, float hi) {
    uint32_t r;
    asm("cvt.rn.bf16x2.f32 %0, %1, %2;" : "=r"(r) : "f"(hi), "f"(lo));
    return r;
}
__device__ __forceinline__ uint32_t lds32(uint32_t addr) {
    uint32_t v;
    asm("ld.shared.u32 %0, [%1];" : "=r"(v) : "r"(addr));
    return v;
}
__device__ __forceinline__ uint32_t dp4a_u(uint32_t a, uint32_t b, uint32_t c) {
    uint32_t d;
    asm("dp4a.u32.u32 %0, %1, %2, %3;" : "=r"(d) : "r"(a), "r"(b), "r"(c));
    return d;
}
__device__ __forceinline__ uint32_t prmt(uint32_t a, uint32_t b, uint32_t s) {
    uint32_t d;
    asm("prmt.b32 %0, %1, %2, %3;" : "=r"(d) : "r"(a), "r"(b), "r"(s));
    return d;
}
template <int ID, int NT> __device__ __forceinline__ void named_bar_sync() {
    asm volatile("bar.sync %0, %1;" ::"n"(ID), "n"(NT) : "memory");
}
template <int ID, int NT> __device__ __forceinline__ void named_bar_arrive() {
    asm volatile("bar.arrive %0, %1;" ::"n"(ID), "n"(NT) : "memory");
}
__device__ __forceinline__ void cluster_arrive_relaxed() { asm volatile("barrier.cluster.arrive.relaxed.aligned;" ::: "memory"); }
__device__ __forceinline__ void cluster_wait() { asm volatile("barrier.cluster.wait.acquire.aligned;" ::: "memory"); }
__device__ __forceinline__ uint4 ldg_stream(const int* p) {
    uint4 v;
    asm volatile("ld.global.L1::no_allocate.L2::128B.v4.u32 {%0, %1, %2, %3}, [%4];"
                 : "=r"(v.x), "=r"(v.y), "=r"(v.z), "=r"(v.w) : "l"(p));
    return v;
}
__device__ __forceinline__ uint32_t ldg_u16(const unsigned short* p) {
    uint32_t v;
    asm volatile("ld.global.nc.u16 %0, [%1];" : "=r"(v) : "l"(p));
    return v;
}
__device__ __forceinline__ unsigned ld_ca_u32(const unsigned* p) {
    unsigned v;
    asm volatile("ld.global.ca.u32 %0, [%1];" : "=r"(v) : "l"(p) : "memory");
    return v;
}
typedef unsigned long long u64;
__device__ __forceinline__ void ll_store2(u64* p, uint32_t w0, uint32_t w1, uint32_t tag) {
    asm volatile("{\n.reg .b64 a, b;\nmov.b64 a, {%1, %3};\nmov.b64 b, {%2, %3};\n"
                 "st.relaxed.gpu.global.v2.b64 [%0], {a, b};\n}\n" ::"l"(p), "r"(w0), "r"(w1), "r"(tag) : "memory");
}

template <int N, int OFF, bool ACC, int NA> struct WG;
template <int OFF, int NA> struct WG<232, OFF, false, NA> {
    static __device__ __forceinline__ void mma(float (&d)[NA], uint32_t a0, uint32_t a1, uint32_t a2, uint32_t a3, uint64_t descB) {
        asm volatile(
            "{\n"
            ".reg .pred p;\n"
            "setp.ne.b32 p, %121, 0;\n"
            "wgmma.mma_async.sync.aligned.m64n232k16.f32.bf16.bf16 "
            "{%0, %1, %2, %3, %4, %5, %6, %7, %8, %9, %10, %11, %12, %13, %14, %15, %16, %17, %18, %19, %20, %21, %22, %23, %24, %25, %26, %27, %28, %29, %30, %31, %32, %33, %34, %35, %36, %37, %38, %39, %40, %41, %42, %43, %44, %45, %46, %47, %48, %49, %50, %51, %52, %53, %54, %55, %56, %57, %58, %59, %60, %61, %62, %63, %64, %65, %66, %67, %68, %69, %70, %71, %72, %73, %74, %75, %76, %77, %78, %79, %80, %81, %82, %83, %84, %85, %86, %87, %88, %89, %90, %91, %92, %93, %94, %95, %96, %97, %98, %99, %100, %101, %102, %103, %104, %105, %106, %107, %108, %109, %110, %111, %112, %113, %114, %115}, "
            "{%116, %117, %118, %119}, %120, p, 1, 1, 0;\n"
            "}\n"
            : "=f"(d[OFF + 0]), "=f"(d[OFF + 1]), "=f"(d[OFF + 2]), "=f"(d[OFF + 3]), "=f"(d[OFF + 4]), "=f"(d[OFF + 5]), "=f"(d[OFF + 6]), "=f"(d[OFF + 7]), "=f"(d[OFF + 8]), "=f"(d[OFF + 9]), "=f"(d[OFF + 10]), "=f"(d[OFF + 11]), "=f"(d[OFF + 12]), "=f"(d[OFF + 13]), "=f"(d[OFF + 14]), "=f"(d[OFF + 15]), "=f"(d[OFF + 16]), "=f"(d[OFF + 17]), "=f"(d[OFF + 18]), "=f"(d[OFF + 19]), "=f"(d[OFF + 20]), "=f"(d[OFF + 21]), "=f"(d[OFF + 22]), "=f"(d[OFF + 23]), "=f"(d[OFF + 24]), "=f"(d[OFF + 25]), "=f"(d[OFF + 26]), "=f"(d[OFF + 27]), "=f"(d[OFF + 28]), "=f"(d[OFF + 29]), "=f"(d[OFF + 30]), "=f"(d[OFF + 31]), "=f"(d[OFF + 32]), "=f"(d[OFF + 33]), "=f"(d[OFF + 34]), "=f"(d[OFF + 35]), "=f"(d[OFF + 36]), "=f"(d[OFF + 37]), "=f"(d[OFF + 38]), "=f"(d[OFF + 39]), "=f"(d[OFF + 40]), "=f"(d[OFF + 41]), "=f"(d[OFF + 42]), "=f"(d[OFF + 43]), "=f"(d[OFF + 44]), "=f"(d[OFF + 45]), "=f"(d[OFF + 46]), "=f"(d[OFF + 47]), "=f"(d[OFF + 48]), "=f"(d[OFF + 49]), "=f"(d[OFF + 50]), "=f"(d[OFF + 51]), "=f"(d[OFF + 52]), "=f"(d[OFF + 53]), "=f"(d[OFF + 54]), "=f"(d[OFF + 55]), "=f"(d[OFF + 56]), "=f"(d[OFF + 57]), "=f"(d[OFF + 58]), "=f"(d[OFF + 59]), "=f"(d[OFF + 60]), "=f"(d[OFF + 61]), "=f"(d[OFF + 62]), "=f"(d[OFF + 63]), "=f"(d[OFF + 64]), "=f"(d[OFF + 65]), "=f"(d[OFF + 66]), "=f"(d[OFF + 67]), "=f"(d[OFF + 68]), "=f"(d[OFF + 69]), "=f"(d[OFF + 70]), "=f"(d[OFF + 71]), "=f"(d[OFF + 72]), "=f"(d[OFF + 73]), "=f"(d[OFF + 74]), "=f"(d[OFF + 75]), "=f"(d[OFF + 76]), "=f"(d[OFF + 77]), "=f"(d[OFF + 78]), "=f"(d[OFF + 79]), "=f"(d[OFF + 80]), "=f"(d[OFF + 81]), "=f"(d[OFF + 82]), "=f"(d[OFF + 83]), "=f"(d[OFF + 84]), "=f"(d[OFF + 85]), "=f"(d[OFF + 86]), "=f"(d[OFF + 87]), "=f"(d[OFF + 88]), "=f"(d[OFF + 89]), "=f"(d[OFF + 90]), "=f"(d[OFF + 91]), "=f"(d[OFF + 92]), "=f"(d[OFF + 93]), "=f"(d[OFF + 94]), "=f"(d[OFF + 95]), "=f"(d[OFF + 96]), "=f"(d[OFF + 97]), "=f"(d[OFF + 98]), "=f"(d[OFF + 99]), "=f"(d[OFF + 100]), "=f"(d[OFF + 101]), "=f"(d[OFF + 102]), "=f"(d[OFF + 103]), "=f"(d[OFF + 104]), "=f"(d[OFF + 105]), "=f"(d[OFF + 106]), "=f"(d[OFF + 107]), "=f"(d[OFF + 108]), "=f"(d[OFF + 109]), "=f"(d[OFF + 110]), "=f"(d[OFF + 111]), "=f"(d[OFF + 112]), "=f"(d[OFF + 113]), "=f"(d[OFF + 114]), "=f"(d[OFF + 115])
            : "r"(a0), "r"(a1), "r"(a2), "r"(a3), "l"(descB), "n"(0));
    }
};
template <int OFF, int NA> struct WG<232, OFF, true, NA> {
    static __device__ __forceinline__ void mma(float (&d)[NA], uint32_t a0, uint32_t a1, uint32_t a2, uint32_t a3, uint64_t descB) {
        asm volatile(
            "{\n"
            ".reg .pred p;\n"
            "setp.ne.b32 p, %121, 0;\n"
            "wgmma.mma_async.sync.aligned.m64n232k16.f32.bf16.bf16 "
            "{%0, %1, %2, %3, %4, %5, %6, %7, %8, %9, %10, %11, %12, %13, %14, %15, %16, %17, %18, %19, %20, %21, %22, %23, %24, %25, %26, %27, %28, %29, %30, %31, %32, %33, %34, %35, %36, %37, %38, %39, %40, %41, %42, %43, %44, %45, %46, %47, %48, %49, %50, %51, %52, %53, %54, %55, %56, %57, %58, %59, %60, %61, %62, %63, %64, %65, %66, %67, %68, %69, %70, %71, %72, %73, %74, %75, %76, %77, %78, %79, %80, %81, %82, %83, %84, %85, %86, %87, %88, %89, %90, %91, %92, %93, %94, %95, %96, %97, %98, %99, %100, %101, %102, %103, %104, %105, %106, %107, %108, %109, %110, %111, %112, %113, %114, %115}, "
            "{%116, %117, %118, %119}, %120, p, 1, 1, 0;\n"
            "}\n"
            : "+f"(d[OFF + 0]), "+f"(d[OFF + 1]), "+f"(d[OFF + 2]), "+f"(d[OFF + 3]), "+f"(d[OFF + 4]), "+f"(d[OFF + 5]), "+f"(d[OFF + 6]), "+f"(d[OFF + 7]), "+f"(d[OFF + 8]), "+f"(d[OFF + 9]), "+f"(d[OFF + 10]), "+f"(d[OFF + 11]), "+f"(d[OFF + 12]), "+f"(d[OFF + 13]), "+f"(d[OFF + 14]), "+f"(d[OFF + 15]), "+f"(d[OFF + 16]), "+f"(d[OFF + 17]), "+f"(d[OFF + 18]), "+f"(d[OFF + 19]), "+f"(d[OFF + 20]), "+f"(d[OFF + 21]), "+f"(d[OFF + 22]), "+f"(d[OFF + 23]), "+f"(d[OFF + 24]), "+f"(d[OFF + 25]), "+f"(d[OFF + 26]), "+f"(d[OFF + 27]), "+f"(d[OFF + 28]), "+f"(d[OFF + 29]), "+f"(d[OFF + 30]), "+f"(d[OFF + 31]), "+f"(d[OFF + 32]), "+f"(d[OFF + 33]), "+f"(d[OFF + 34]), "+f"(d[OFF + 35]), "+f"(d[OFF + 36]), "+f"(d[OFF + 37]), "+f"(d[OFF + 38]), "+f"(d[OFF + 39]), "+f"(d[OFF + 40]), "+f"(d[OFF + 41]), "+f"(d[OFF + 42]), "+f"(d[OFF + 43]), "+f"(d[OFF + 44]), "+f"(d[OFF + 45]), "+f"(d[OFF + 46]), "+f"(d[OFF + 47]), "+f"(d[OFF + 48]), "+f"(d[OFF + 49]), "+f"(d[OFF + 50]), "+f"(d[OFF + 51]), "+f"(d[OFF + 52]), "+f"(d[OFF + 53]), "+f"(d[OFF + 54]), "+f"(d[OFF + 55]), "+f"(d[OFF + 56]), "+f"(d[OFF + 57]), "+f"(d[OFF + 58]), "+f"(d[OFF + 59]), "+f"(d[OFF + 60]), "+f"(d[OFF + 61]), "+f"(d[OFF + 62]), "+f"(d[OFF + 63]), "+f"(d[OFF + 64]), "+f"(d[OFF + 65]), "+f"(d[OFF + 66]), "+f"(d[OFF + 67]), "+f"(d[OFF + 68]), "+f"(d[OFF + 69]), "+f"(d[OFF + 70]), "+f"(d[OFF + 71]), "+f"(d[OFF + 72]), "+f"(d[OFF + 73]), "+f"(d[OFF + 74]), "+f"(d[OFF + 75]), "+f"(d[OFF + 76]), "+f"(d[OFF + 77]), "+f"(d[OFF + 78]), "+f"(d[OFF + 79]), "+f"(d[OFF + 80]), "+f"(d[OFF + 81]), "+f"(d[OFF + 82]), "+f"(d[OFF + 83]), "+f"(d[OFF + 84]), "+f"(d[OFF + 85]), "+f"(d[OFF + 86]), "+f"(d[OFF + 87]), "+f"(d[OFF + 88]), "+f"(d[OFF + 89]), "+f"(d[OFF + 90]), "+f"(d[OFF + 91]), "+f"(d[OFF + 92]), "+f"(d[OFF + 93]), "+f"(d[OFF + 94]), "+f"(d[OFF + 95]), "+f"(d[OFF + 96]), "+f"(d[OFF + 97]), "+f"(d[OFF + 98]), "+f"(d[OFF + 99]), "+f"(d[OFF + 100]), "+f"(d[OFF + 101]), "+f"(d[OFF + 102]), "+f"(d[OFF + 103]), "+f"(d[OFF + 104]), "+f"(d[OFF + 105]), "+f"(d[OFF + 106]), "+f"(d[OFF + 107]), "+f"(d[OFF + 108]), "+f"(d[OFF + 109]), "+f"(d[OFF + 110]), "+f"(d[OFF + 111]), "+f"(d[OFF + 112]), "+f"(d[OFF + 113]), "+f"(d[OFF + 114]), "+f"(d[OFF + 115])
            : "r"(a0), "r"(a1), "r"(a2), "r"(a3), "l"(descB), "n"(1));
    }
};
template <int OFF, int NA> struct WG<208, OFF, false, NA> {
    static __device__ __forceinline__ void mma(float (&d)[NA], uint32_t a0, uint32_t a1, uint32_t a2, uint32_t a3, uint64_t descB) {
        asm volatile(
            "{\n"
            ".reg .pred p;\n"
            "setp.ne.b32 p, %109, 0;\n"
            "wgmma.mma_async.sync.aligned.m64n208k16.f32.bf16.bf16 "
            "{%0, %1, %2, %3, %4, %5, %6, %7, %8, %9, %10, %11, %12, %13, %14, %15, %16, %17, %18, %19, %20, %21, %22, %23, %24, %25, %26, %27, %28, %29, %30, %31, %32, %33, %34, %35, %36, %37, %38, %39, %40, %41, %42, %43, %44, %45, %46, %47, %48, %49, %50, %51, %52, %53, %54, %55, %56, %57, %58, %59, %60, %61, %62, %63, %64, %65, %66, %67, %68, %69, %70, %71, %72, %73, %74, %75, %76, %77, %78, %79, %80, %81, %82, %83, %84, %85, %86, %87, %88, %89, %90, %91, %92, %93, %94, %95, %96, %97, %98, %99, %100, %101, %102, %103}, "
            "{%104, %105, %106, %107}, %108, p, 1, 1, 0;\n"
            "}\n"
            : "=f"(d[OFF + 0]), "=f"(d[OFF + 1]), "=f"(d[OFF + 2]), "=f"(d[OFF + 3]), "=f"(d[OFF + 4]), "=f"(d[OFF + 5]), "=f"(d[OFF + 6]), "=f"(d[OFF + 7]), "=f"(d[OFF + 8]), "=f"(d[OFF + 9]), "=f"(d[OFF + 10]), "=f"(d[OFF + 11]), "=f"(d[OFF + 12]), "=f"(d[OFF + 13]), "=f"(d[OFF + 14]), "=f"(d[OFF + 15]), "=f"(d[OFF + 16]), "=f"(d[OFF + 17]), "=f"(d[OFF + 18]), "=f"(d[OFF + 19]), "=f"(d[OFF + 20]), "=f"(d[OFF + 21]), "=f"(d[OFF + 22]), "=f"(d[OFF + 23]), "=f"(d[OFF + 24]), "=f"(d[OFF + 25]), "=f"(d[OFF + 26]), "=f"(d[OFF + 27]), "=f"(d[OFF + 28]), "=f"(d[OFF + 29]), "=f"(d[OFF + 30]), "=f"(d[OFF + 31]), "=f"(d[OFF + 32]), "=f"(d[OFF + 33]), "=f"(d[OFF + 34]), "=f"(d[OFF + 35]), "=f"(d[OFF + 36]), "=f"(d[OFF + 37]), "=f"(d[OFF + 38]), "=f"(d[OFF + 39]), "=f"(d[OFF + 40]), "=f"(d[OFF + 41]), "=f"(d[OFF + 42]), "=f"(d[OFF + 43]), "=f"(d[OFF + 44]), "=f"(d[OFF + 45]), "=f"(d[OFF + 46]), "=f"(d[OFF + 47]), "=f"(d[OFF + 48]), "=f"(d[OFF + 49]), "=f"(d[OFF + 50]), "=f"(d[OFF + 51]), "=f"(d[OFF + 52]), "=f"(d[OFF + 53]), "=f"(d[OFF + 54]), "=f"(d[OFF + 55]), "=f"(d[OFF + 56]), "=f"(d[OFF + 57]), "=f"(d[OFF + 58]), "=f"(d[OFF + 59]), "=f"(d[OFF + 60]), "=f"(d[OFF + 61]), "=f"(d[OFF + 62]), "=f"(d[OFF + 63]), "=f"(d[OFF + 64]), "=f"(d[OFF + 65]), "=f"(d[OFF + 66]), "=f"(d[OFF + 67]), "=f"(d[OFF + 68]), "=f"(d[OFF + 69]), "=f"(d[OFF + 70]), "=f"(d[OFF + 71]), "=f"(d[OFF + 72]), "=f"(d[OFF + 73]), "=f"(d[OFF + 74]), "=f"(d[OFF + 75]), "=f"(d[OFF + 76]), "=f"(d[OFF + 77]), "=f"(d[OFF + 78]), "=f"(d[OFF + 79]), "=f"(d[OFF + 80]), "=f"(d[OFF + 81]), "=f"(d[OFF + 82]), "=f"(d[OFF + 83]), "=f"(d[OFF + 84]), "=f"(d[OFF + 85]), "=f"(d[OFF + 86]), "=f"(d[OFF + 87]), "=f"(d[OFF + 88]), "=f"(d[OFF + 89]), "=f"(d[OFF + 90]), "=f"(d[OFF + 91]), "=f"(d[OFF + 92]), "=f"(d[OFF + 93]), "=f"(d[OFF + 94]), "=f"(d[OFF + 95]), "=f"(d[OFF + 96]), "=f"(d[OFF + 97]), "=f"(d[OFF + 98]), "=f"(d[OFF + 99]), "=f"(d[OFF + 100]), "=f"(d[OFF + 101]), "=f"(d[OFF + 102]), "=f"(d[OFF + 103])
            : "r"(a0), "r"(a1), "r"(a2), "r"(a3), "l"(descB), "n"(0));
    }
};
template <int OFF, int NA> struct WG<208, OFF, true, NA> {
    static __device__ __forceinline__ void mma(float (&d)[NA], uint32_t a0, uint32_t a1, uint32_t a2, uint32_t a3, uint64_t descB) {
        asm volatile(
            "{\n"
            ".reg .pred p;\n"
            "setp.ne.b32 p, %109, 0;\n"
            "wgmma.mma_async.sync.aligned.m64n208k16.f32.bf16.bf16 "
            "{%0, %1, %2, %3, %4, %5, %6, %7, %8, %9, %10, %11, %12, %13, %14, %15, %16, %17, %18, %19, %20, %21, %22, %23, %24, %25, %26, %27, %28, %29, %30, %31, %32, %33, %34, %35, %36, %37, %38, %39, %40, %41, %42, %43, %44, %45, %46, %47, %48, %49, %50, %51, %52, %53, %54, %55, %56, %57, %58, %59, %60, %61, %62, %63, %64, %65, %66, %67, %68, %69, %70, %71, %72, %73, %74, %75, %76, %77, %78, %79, %80, %81, %82, %83, %84, %85, %86, %87, %88, %89, %90, %91, %92, %93, %94, %95, %96, %97, %98, %99, %100, %101, %102, %103}, "
            "{%104, %105, %106, %107}, %108, p, 1, 1, 0;\n"
            "}\n"
            : "+f"(d[OFF + 0]), "+f"(d[OFF + 1]), "+f"(d[OFF + 2]), "+f"(d[OFF + 3]), "+f"(d[OFF + 4]), "+f"(d[OFF + 5]), "+f"(d[OFF + 6]), "+f"(d[OFF + 7]), "+f"(d[OFF + 8]), "+f"(d[OFF + 9]), "+f"(d[OFF + 10]), "+f"(d[OFF + 11]), "+f"(d[OFF + 12]), "+f"(d[OFF + 13]), "+f"(d[OFF + 14]), "+f"(d[OFF + 15]), "+f"(d[OFF + 16]), "+f"(d[OFF + 17]), "+f"(d[OFF + 18]), "+f"(d[OFF + 19]), "+f"(d[OFF + 20]), "+f"(d[OFF + 21]), "+f"(d[OFF + 22]), "+f"(d[OFF + 23]), "+f"(d[OFF + 24]), "+f"(d[OFF + 25]), "+f"(d[OFF + 26]), "+f"(d[OFF + 27]), "+f"(d[OFF + 28]), "+f"(d[OFF + 29]), "+f"(d[OFF + 30]), "+f"(d[OFF + 31]), "+f"(d[OFF + 32]), "+f"(d[OFF + 33]), "+f"(d[OFF + 34]), "+f"(d[OFF + 35]), "+f"(d[OFF + 36]), "+f"(d[OFF + 37]), "+f"(d[OFF + 38]), "+f"(d[OFF + 39]), "+f"(d[OFF + 40]), "+f"(d[OFF + 41]), "+f"(d[OFF + 42]), "+f"(d[OFF + 43]), "+f"(d[OFF + 44]), "+f"(d[OFF + 45]), "+f"(d[OFF + 46]), "+f"(d[OFF + 47]), "+f"(d[OFF + 48]), "+f"(d[OFF + 49]), "+f"(d[OFF + 50]), "+f"(d[OFF + 51]), "+f"(d[OFF + 52]), "+f"(d[OFF + 53]), "+f"(d[OFF + 54]), "+f"(d[OFF + 55]), "+f"(d[OFF + 56]), "+f"(d[OFF + 57]), "+f"(d[OFF + 58]), "+f"(d[OFF + 59]), "+f"(d[OFF + 60]), "+f"(d[OFF + 61]), "+f"(d[OFF + 62]), "+f"(d[OFF + 63]), "+f"(d[OFF + 64]), "+f"(d[OFF + 65]), "+f"(d[OFF + 66]), "+f"(d[OFF + 67]), "+f"(d[OFF + 68]), "+f"(d[OFF + 69]), "+f"(d[OFF + 70]), "+f"(d[OFF + 71]), "+f"(d[OFF + 72]), "+f"(d[OFF + 73]), "+f"(d[OFF + 74]), "+f"(d[OFF + 75]), "+f"(d[OFF + 76]), "+f"(d[OFF + 77]), "+f"(d[OFF + 78]), "+f"(d[OFF + 79]), "+f"(d[OFF + 80]), "+f"(d[OFF + 81]), "+f"(d[OFF + 82]), "+f"(d[OFF + 83]), "+f"(d[OFF + 84]), "+f"(d[OFF + 85]), "+f"(d[OFF + 86]), "+f"(d[OFF + 87]), "+f"(d[OFF + 88]), "+f"(d[OFF + 89]), "+f"(d[OFF + 90]), "+f"(d[OFF + 91]), "+f"(d[OFF + 92]), "+f"(d[OFF + 93]), "+f"(d[OFF + 94]), "+f"(d[OFF + 95]), "+f"(d[OFF + 96]), "+f"(d[OFF + 97]), "+f"(d[OFF + 98]), "+f"(d[OFF + 99]), "+f"(d[OFF + 100]), "+f"(d[OFF + 101]), "+f"(d[OFF + 102]), "+f"(d[OFF + 103])
            : "r"(a0), "r"(a1), "r"(a2), "r"(a3), "l"(descB), "n"(1));
    }
};
template <int OFF, int NA> struct WG<120, OFF, false, NA> {
    static __device__ __forceinline__ void mma(float (&d)[NA], uint32_t a0, uint32_t a1, uint32_t a2, uint32_t a3, uint64_t descB) {
        asm volatile(
            "{\n"
            ".reg .pred p;\n"
            "setp.ne.b32 p, %65, 0;\n"
            "wgmma.mma_async.sync.aligned.m64n120k16.f32.bf16.bf16 "
            "{%0, %1, %2, %3, %4, %5, %6, %7, %8, %9, %10, %11, %12, %13, %14, %15, %16, %17, %18, %19, %20, %21, %22, %23, %24, %25, %26, %27, %28, %29, %30, %31, %32, %33, %34, %35, %36, %37, %38, %39, %40, %41, %42, %43, %44, %45, %46, %47, %48, %49, %50, %51, %52, %53, %54, %55, %56, %57, %58, %59}, "
            "{%60, %61, %62, %63}, %64, p, 1, 1, 0;\n"
            "}\n"
            : "=f"(d[OFF + 0]), "=f"(d[OFF + 1]), "=f"(d[OFF + 2]), "=f"(d[OFF + 3]), "=f"(d[OFF + 4]), "=f"(d[OFF + 5]), "=f"(d[OFF + 6]), "=f"(d[OFF + 7]), "=f"(d[OFF + 8]), "=f"(d[OFF + 9]), "=f"(d[OFF + 10]), "=f"(d[OFF + 11]), "=f"(d[OFF + 12]), "=f"(d[OFF + 13]), "=f"(d[OFF + 14]), "=f"(d[OFF + 15]), "=f"(d[OFF + 16]), "=f"(d[OFF + 17]), "=f"(d[OFF + 18]), "=f"(d[OFF + 19]), "=f"(d[OFF + 20]), "=f"(d[OFF + 21]), "=f"(d[OFF + 22]), "=f"(d[OFF + 23]), "=f"(d[OFF + 24]), "=f"(d[OFF + 25]), "=f"(d[OFF + 26]), "=f"(d[OFF + 27]), "=f"(d[OFF + 28]), "=f"(d[OFF + 29]), "=f"(d[OFF + 30]), "=f"(d[OFF + 31]), "=f"(d[OFF + 32]), "=f"(d[OFF + 33]), "=f"(d[OFF + 34]), "=f"(d[OFF + 35]), "=f"(d[OFF + 36]), "=f"(d[OFF + 37]), "=f"(d[OFF + 38]), "=f"(d[OFF + 39]), "=f"(d[OFF + 40]), "=f"(d[OFF + 41]), "=f"(d[OFF + 42]), "=f"(d[OFF + 43]), "=f"(d[OFF + 44]), "=f"(d[OFF + 45]), "=f"(d[OFF + 46]), "=f"(d[OFF + 47]), "=f"(d[OFF + 48]), "=f"(d[OFF + 49]), "=f"(d[OFF + 50]), "=f"(d[OFF + 51]), "=f"(d[OFF + 52]), "=f"(d[OFF + 53]), "=f"(d[OFF + 54]), "=f"(d[OFF + 55]), "=f"(d[OFF + 56]), "=f"(d[OFF + 57]), "=f"(d[OFF + 58]), "=f"(d[OFF + 59])
            : "r"(a0), "r"(a1), "r"(a2), "r"(a3), "l"(descB), "n"(0));
    }
};
template <int OFF, int NA> struct WG<120, OFF, true, NA> {
    static __device__ __forceinline__ void mma(float (&d)[NA], uint32_t a0, uint32_t a1, uint32_t a2, uint32_t a3, uint64_t descB) {
        asm volatile(
            "{\n"
            ".reg .pred p;\n"
            "setp.ne.b32 p, %65, 0;\n"
            "wgmma.mma_async.sync.aligned.m64n120k16.f32.bf16.bf16 "
            "{%0, %1, %2, %3, %4, %5, %6, %7, %8, %9, %10, %11, %12, %13, %14, %15, %16, %17, %18, %19, %20, %21, %22, %23, %24, %25, %26, %27, %28, %29, %30, %31, %32, %33, %34, %35, %36, %37, %38, %39, %40, %41, %42, %43, %44, %45, %46, %47, %48, %49, %50, %51, %52, %53, %54, %55, %56, %57, %58, %59}, "
            "{%60, %61, %62, %63}, %64, p, 1, 1, 0;\n"
            "}\n"
            : "+f"(d[OFF + 0]), "+f"(d[OFF + 1]), "+f"(d[OFF + 2]), "+f"(d[OFF + 3]), "+f"(d[OFF + 4]), "+f"(d[OFF + 5]), "+f"(d[OFF + 6]), "+f"(d[OFF + 7]), "+f"(d[OFF + 8]), "+f"(d[OFF + 9]), "+f"(d[OFF + 10]), "+f"(d[OFF + 11]), "+f"(d[OFF + 12]), "+f"(d[OFF + 13]), "+f"(d[OFF + 14]), "+f"(d[OFF + 15]), "+f"(d[OFF + 16]), "+f"(d[OFF + 17]), "+f"(d[OFF + 18]), "+f"(d[OFF + 19]), "+f"(d[OFF + 20]), "+f"(d[OFF + 21]), "+f"(d[OFF + 22]), "+f"(d[OFF + 23]), "+f"(d[OFF + 24]), "+f"(d[OFF + 25]), "+f"(d[OFF + 26]), "+f"(d[OFF + 27]), "+f"(d[OFF + 28]), "+f"(d[OFF + 29]), "+f"(d[OFF + 30]), "+f"(d[OFF + 31]), "+f"(d[OFF + 32]), "+f"(d[OFF + 33]), "+f"(d[OFF + 34]), "+f"(d[OFF + 35]), "+f"(d[OFF + 36]), "+f"(d[OFF + 37]), "+f"(d[OFF + 38]), "+f"(d[OFF + 39]), "+f"(d[OFF + 40]), "+f"(d[OFF + 41]), "+f"(d[OFF + 42]), "+f"(d[OFF + 43]), "+f"(d[OFF + 44]), "+f"(d[OFF + 45]), "+f"(d[OFF + 46]), "+f"(d[OFF + 47]), "+f"(d[OFF + 48]), "+f"(d[OFF + 49]), "+f"(d[OFF + 50]), "+f"(d[OFF + 51]), "+f"(d[OFF + 52]), "+f"(d[OFF + 53]), "+f"(d[OFF + 54]), "+f"(d[OFF + 55]), "+f"(d[OFF + 56]), "+f"(d[OFF + 57]), "+f"(d[OFF + 58]), "+f"(d[OFF + 59])
            : "r"(a0), "r"(a1), "r"(a2), "r"(a3), "l"(descB), "n"(1));
    }
};
template <int OFF, int NA> struct WG<112, OFF, false, NA> {
    static __device__ __forceinline__ void mma(float (&d)[NA], uint32_t a0, uint32_t a1, uint32_t a2, uint32_t a3, uint64_t descB) {
        asm volatile(
            "{\n"
            ".reg .pred p;\n"
            "setp.ne.b32 p, %61, 0;\n"
            "wgmma.mma_async.sync.aligned.m64n112k16.f32.bf16.bf16 "
            "{%0, %1, %2, %3, %4, %5, %6, %7, %8, %9, %10, %11, %12, %13, %14, %15, %16, %17, %18, %19, %20, %21, %22, %23, %24, %25, %26, %27, %28, %29, %30, %31, %32, %33, %34, %35, %36, %37, %38, %39, %40, %41, %42, %43, %44, %45, %46, %47, %48, %49, %50, %51, %52, %53, %54, %55}, "
            "{%56, %57, %58, %59}, %60, p, 1, 1, 0;\n"
            "}\n"
            : "=f"(d[OFF + 0]), "=f"(d[OFF + 1]), "=f"(d[OFF + 2]), "=f"(d[OFF + 3]), "=f"(d[OFF + 4]), "=f"(d[OFF + 5]), "=f"(d[OFF + 6]), "=f"(d[OFF + 7]), "=f"(d[OFF + 8]), "=f"(d[OFF + 9]), "=f"(d[OFF + 10]), "=f"(d[OFF + 11]), "=f"(d[OFF + 12]), "=f"(d[OFF + 13]), "=f"(d[OFF + 14]), "=f"(d[OFF + 15]), "=f"(d[OFF + 16]), "=f"(d[OFF + 17]), "=f"(d[OFF + 18]), "=f"(d[OFF + 19]), "=f"(d[OFF + 20]), "=f"(d[OFF + 21]), "=f"(d[OFF + 22]), "=f"(d[OFF + 23]), "=f"(d[OFF + 24]), "=f"(d[OFF + 25]), "=f"(d[OFF + 26]), "=f"(d[OFF + 27]), "=f"(d[OFF + 28]), "=f"(d[OFF + 29]), "=f"(d[OFF + 30]), "=f"(d[OFF + 31]), "=f"(d[OFF + 32]), "=f"(d[OFF + 33]), "=f"(d[OFF + 34]), "=f"(d[OFF + 35]), "=f"(d[OFF + 36]), "=f"(d[OFF + 37]), "=f"(d[OFF + 38]), "=f"(d[OFF + 39]), "=f"(d[OFF + 40]), "=f"(d[OFF + 41]), "=f"(d[OFF + 42]), "=f"(d[OFF + 43]), "=f"(d[OFF + 44]), "=f"(d[OFF + 45]), "=f"(d[OFF + 46]), "=f"(d[OFF + 47]), "=f"(d[OFF + 48]), "=f"(d[OFF + 49]), "=f"(d[OFF + 50]), "=f"(d[OFF + 51]), "=f"(d[OFF + 52]), "=f"(d[OFF + 53]), "=f"(d[OFF + 54]), "=f"(d[OFF + 55])
            : "r"(a0), "r"(a1), "r"(a2), "r"(a3), "l"(descB), "n"(0));
    }
};
template <int OFF, int NA> struct WG<112, OFF, true, NA> {
    static __device__ __forceinline__ void mma(float (&d)[NA], uint32_t a0, uint32_t a1, uint32_t a2, uint32_t a3, uint64_t descB) {
        asm volatile(
            "{\n"
            ".reg .pred p;\n"
            "setp.ne.b32 p, %61, 0;\n"
            "wgmma.mma_async.sync.aligned.m64n112k16.f32.bf16.bf16 "
            "{%0, %1, %2, %3, %4, %5, %6, %7, %8, %9, %10, %11, %12, %13, %14, %15, %16, %17, %18, %19, %20, %21, %22, %23, %24, %25, %26, %27, %28, %29, %30, %31, %32, %33, %34, %35, %36, %37, %38, %39, %40, %41, %42, %43, %44, %45, %46, %47, %48, %49, %50, %51, %52, %53, %54, %55}, "
            "{%56, %57, %58, %59}, %60, p, 1, 1, 0;\n"
            "}\n"
            : "+f"(d[OFF + 0]), "+f"(d[OFF + 1]), "+f"(d[OFF + 2]), "+f"(d[OFF + 3]), "+f"(d[OFF + 4]), "+f"(d[OFF + 5]), "+f"(d[OFF + 6]), "+f"(d[OFF + 7]), "+f"(d[OFF + 8]), "+f"(d[OFF + 9]), "+f"(d[OFF + 10]), "+f"(d[OFF + 11]), "+f"(d[OFF + 12]), "+f"(d[OFF + 13]), "+f"(d[OFF + 14]), "+f"(d[OFF + 15]), "+f"(d[OFF + 16]), "+f"(d[OFF + 17]), "+f"(d[OFF + 18]), "+f"(d[OFF + 19]), "+f"(d[OFF + 20]), "+f"(d[OFF + 21]), "+f"(d[OFF + 22]), "+f"(d[OFF + 23]), "+f"(d[OFF + 24]), "+f"(d[OFF + 25]), "+f"(d[OFF + 26]), "+f"(d[OFF + 27]), "+f"(d[OFF + 28]), "+f"(d[OFF + 29]), "+f"(d[OFF + 30]), "+f"(d[OFF + 31]), "+f"(d[OFF + 32]), "+f"(d[OFF + 33]), "+f"(d[OFF + 34]), "+f"(d[OFF + 35]), "+f"(d[OFF + 36]), "+f"(d[OFF + 37]), "+f"(d[OFF + 38]), "+f"(d[OFF + 39]), "+f"(d[OFF + 40]), "+f"(d[OFF + 41]), "+f"(d[OFF + 42]), "+f"(d[OFF + 43]), "+f"(d[OFF + 44]), "+f"(d[OFF + 45]), "+f"(d[OFF + 46]), "+f"(d[OFF + 47]), "+f"(d[OFF + 48]), "+f"(d[OFF + 49]), "+f"(d[OFF + 50]), "+f"(d[OFF + 51]), "+f"(d[OFF + 52]), "+f"(d[OFF + 53]), "+f"(d[OFF + 54]), "+f"(d[OFF + 55])
            : "r"(a0), "r"(a1), "r"(a2), "r"(a3), "l"(descB), "n"(1));
    }
};
template <int OFF, int NA> struct WG<96, OFF, false, NA> {
    static __device__ __forceinline__ void mma(float (&d)[NA], uint32_t a0, uint32_t a1, uint32_t a2, uint32_t a3, uint64_t descB) {
        asm volatile(
            "{\n"
            ".reg .pred p;\n"
            "setp.ne.b32 p, %53, 0;\n"
            "wgmma.mma_async.sync.aligned.m64n96k16.f32.bf16.bf16 "
            "{%0, %1, %2, %3, %4, %5, %6, %7, %8, %9, %10, %11, %12, %13, %14, %15, %16, %17, %18, %19, %20, %21, %22, %23, %24, %25, %26, %27, %28, %29, %30, %31, %32, %33, %34, %35, %36, %37, %38, %39, %40, %41, %42, %43, %44, %45, %46, %47}, "
            "{%48, %49, %50, %51}, %52, p, 1, 1, 0;\n"
            "}\n"
            : "=f"(d[OFF + 0]), "=f"(d[OFF + 1]), "=f"(d[OFF + 2]), "=f"(d[OFF + 3]), "=f"(d[OFF + 4]), "=f"(d[OFF + 5]), "=f"(d[OFF + 6]), "=f"(d[OFF + 7]), "=f"(d[OFF + 8]), "=f"(d[OFF + 9]), "=f"(d[OFF + 10]), "=f"(d[OFF + 11]), "=f"(d[OFF + 12]), "=f"(d[OFF + 13]), "=f"(d[OFF + 14]), "=f"(d[OFF + 15]), "=f"(d[OFF + 16]), "=f"(d[OFF + 17]), "=f"(d[OFF + 18]), "=f"(d[OFF + 19]), "=f"(d[OFF + 20]), "=f"(d[OFF + 21]), "=f"(d[OFF + 22]), "=f"(d[OFF + 23]), "=f"(d[OFF + 24]), "=f"(d[OFF + 25]), "=f"(d[OFF + 26]), "=f"(d[OFF + 27]), "=f"(d[OFF + 28]), "=f"(d[OFF + 29]), "=f"(d[OFF + 30]), "=f"(d[OFF + 31]), "=f"(d[OFF + 32]), "=f"(d[OFF + 33]), "=f"(d[OFF + 34]), "=f"(d[OFF + 35]), "=f"(d[OFF + 36]), "=f"(d[OFF + 37]), "=f"(d[OFF + 38]), "=f"(d[OFF + 39]), "=f"(d[OFF + 40]), "=f"(d[OFF + 41]), "=f"(d[OFF + 42]), "=f"(d[OFF + 43]), "=f"(d[OFF + 44]), "=f"(d[OFF + 45]), "=f"(d[OFF + 46]), "=f"(d[OFF + 47])
            : "r"(a0), "r"(a1), "r"(a2), "r"(a3), "l"(descB), "n"(0));
    }
};
template <int OFF, int NA> struct WG<96, OFF, true, NA> {
    static __device__ __forceinline__ void mma(float (&d)[NA], uint32_t a0, uint32_t a1, uint32_t a2, uint32_t a3, uint64_t descB) {
        asm volatile(
            "{\n"
            ".reg .pred p;\n"
            "setp.ne.b32 p, %53, 0;\n"
            "wgmma.mma_async.sync.aligned.m64n96k16.f32.bf16.bf16 "
            "{%0, %1, %2, %3, %4, %5, %6, %7, %8, %9, %10, %11, %12, %13, %14, %15, %16, %17, %18, %19, %20, %21, %22, %23, %24, %25, %26, %27, %28, %29, %30, %31, %32, %33, %34, %35, %36, %37, %38, %39, %40, %41, %42, %43, %44, %45, %46, %47}, "
            "{%48, %49, %50, %51}, %52, p, 1, 1, 0;\n"
            "}\n"
            : "+f"(d[OFF + 0]), "+f"(d[OFF + 1]), "+f"(d[OFF + 2]), "+f"(d[OFF + 3]), "+f"(d[OFF + 4]), "+f"(d[OFF + 5]), "+f"(d[OFF + 6]), "+f"(d[OFF + 7]), "+f"(d[OFF + 8]), "+f"(d[OFF + 9]), "+f"(d[OFF + 10]), "+f"(d[OFF + 11]), "+f"(d[OFF + 12]), "+f"(d[OFF + 13]), "+f"(d[OFF + 14]), "+f"(d[OFF + 15]), "+f"(d[OFF + 16]), "+f"(d[OFF + 17]), "+f"(d[OFF + 18]), "+f"(d[OFF + 19]), "+f"(d[OFF + 20]), "+f"(d[OFF + 21]), "+f"(d[OFF + 22]), "+f"(d[OFF + 23]), "+f"(d[OFF + 24]), "+f"(d[OFF + 25]), "+f"(d[OFF + 26]), "+f"(d[OFF + 27]), "+f"(d[OFF + 28]), "+f"(d[OFF + 29]), "+f"(d[OFF + 30]), "+f"(d[OFF + 31]), "+f"(d[OFF + 32]), "+f"(d[OFF + 33]), "+f"(d[OFF + 34]), "+f"(d[OFF + 35]), "+f"(d[OFF + 36]), "+f"(d[OFF + 37]), "+f"(d[OFF + 38]), "+f"(d[OFF + 39]), "+f"(d[OFF + 40]), "+f"(d[OFF + 41]), "+f"(d[OFF + 42]), "+f"(d[OFF + 43]), "+f"(d[OFF + 44]), "+f"(d[OFF + 45]), "+f"(d[OFF + 46]), "+f"(d[OFF + 47])
            : "r"(a0), "r"(a1), "r"(a2), "r"(a3), "l"(descB), "n"(1));
    }
};
template <int OFF, int NA> struct WG<64, OFF, true, NA> {
    static __device__ __forceinline__ void mma(float (&d)[NA], uint32_t a0, uint32_t a1, uint32_t a2, uint32_t a3, uint64_t descB) {
        asm volatile(
            "{\n"
            ".reg .pred p;\n"
            "setp.ne.b32 p, %37, 0;\n"
            "wgmma.mma_async.sync.aligned.m64n64k16.f32.bf16.bf16 "
            "{%0, %1, %2, %3, %4, %5, %6, %7, %8, %9, %10, %11, %12, %13, %14, %15, %16, %17, %18, %19, %20, %21, %22, %23, %24, %25, %26, %27, %28, %29, %30, %31}, "
            "{%32, %33, %34, %35}, %36, p, 1, 1, 0;\n"
            "}\n"
            : "+f"(d[OFF + 0]), "+f"(d[OFF + 1]), "+f"(d[OFF + 2]), "+f"(d[OFF + 3]), "+f"(d[OFF + 4]), "+f"(d[OFF + 5]), "+f"(d[OFF + 6]), "+f"(d[OFF + 7]), "+f"(d[OFF + 8]), "+f"(d[OFF + 9]), "+f"(d[OFF + 10]), "+f"(d[OFF + 11]), "+f"(d[OFF + 12]), "+f"(d[OFF + 13]), "+f"(d[OFF + 14]), "+f"(d[OFF + 15]), "+f"(d[OFF + 16]), "+f"(d[OFF + 17]), "+f"(d[OFF + 18]), "+f"(d[OFF + 19]), "+f"(d[OFF + 20]), "+f"(d[OFF + 21]), "+f"(d[OFF + 22]), "+f"(d[OFF + 23]), "+f"(d[OFF + 24]), "+f"(d[OFF + 25]), "+f"(d[OFF + 26]), "+f"(d[OFF + 27]), "+f"(d[OFF + 28]), "+f"(d[OFF + 29]), "+f"(d[OFF + 30]), "+f"(d[OFF + 31])
            : "r"(a0), "r"(a1), "r"(a2), "r"(a3), "l"(descB), "n"(1));
    }
};
template <int OFF, int NA> struct WG<48, OFF, true, NA> {
    static __device__ __forceinline__ void mma(float (&d)[NA], uint32_t a0, uint32_t a1, uint32_t a2, uint32_t a3, uint64_t descB) {
        asm volatile(
            "{\n"
            ".reg .pred p;\n"
            "setp.ne.b32 p, %29, 0;\n"
            "wgmma.mma_async.sync.aligned.m64n48k16.f32.bf16.bf16 "
            "{%0, %1, %2, %3, %4, %5, %6, %7, %8, %9, %10, %11, %12, %13, %14, %15, %16, %17, %18, %19, %20, %21, %22, %23}, "
            "{%24, %25, %26, %27}, %28, p, 1, 1, 0;\n"
            "}\n"
            : "+f"(d[OFF + 0]), "+f"(d[OFF + 1]), "+f"(d[OFF + 2]), "+f"(d[OFF + 3]), "+f"(d[OFF + 4]), "+f"(d[OFF + 5]), "+f"(d[OFF + 6]), "+f"(d[OFF + 7]), "+f"(d[OFF + 8]), "+f"(d[OFF + 9]), "+f"(d[OFF + 10]), "+f"(d[OFF + 11]), "+f"(d[OFF + 12]), "+f"(d[OFF + 13]), "+f"(d[OFF + 14]), "+f"(d[OFF + 15]), "+f"(d[OFF + 16]), "+f"(d[OFF + 17]), "+f"(d[OFF + 18]), "+f"(d[OFF + 19]), "+f"(d[OFF + 20]), "+f"(d[OFF + 21]), "+f"(d[OFF + 22]), "+f"(d[OFF + 23])
            : "r"(a0), "r"(a1), "r"(a2), "r"(a3), "l"(descB), "n"(1));
    }
};
template <int OFF, int NA> struct WG<32, OFF, true, NA> {
    static __device__ __forceinline__ void mma(float (&d)[NA], uint32_t a0, uint32_t a1, uint32_t a2, uint32_t a3, uint64_t descB) {
        asm volatile(
            "{\n"
            ".reg .pred p;\n"
            "setp.ne.b32 p, %21, 0;\n"
            "wgmma.mma_async.sync.aligned.m64n32k16.f32.bf16.bf16 "
            "{%0, %1, %2, %3, %4, %5, %6, %7, %8, %9, %10, %11, %12, %13, %14, %15}, "
            "{%16, %17, %18, %19}, %20, p, 1, 1, 0;\n"
            "}\n"
            : "+f"(d[OFF + 0]), "+f"(d[OFF + 1]), "+f"(d[OFF + 2]), "+f"(d[OFF + 3]), "+f"(d[OFF + 4]), "+f"(d[OFF + 5]), "+f"(d[OFF + 6]), "+f"(d[OFF + 7]), "+f"(d[OFF + 8]), "+f"(d[OFF + 9]), "+f"(d[OFF + 10]), "+f"(d[OFF + 11]), "+f"(d[OFF + 12]), "+f"(d[OFF + 13]), "+f"(d[OFF + 14]), "+f"(d[OFF + 15])
            : "r"(a0), "r"(a1), "r"(a2), "r"(a3), "l"(descB), "n"(1));
    }
};

__host__ __device__ constexpr int gate_time(int d) { return d == 0 ? DLY_POLL : DLY_P1 + (d - 1) * DLY_PS; }
__device__ __forceinline__ void unit_pos(uint32_t u, uint32_t& q, uint32_t& fg) {
    static_assert(W1_FG == 64 && W2_FG == 48, "unit order");
    const uint32_t r = u - NQ * W1_FG, q2 = (r * 1366) >> 16;
    q = u < NQ * W1_FG ? u >> 6 : q2;
    fg = u < NQ * W1_FG ? u & 63 : W1_FG + r - q2 * 48;
}
template <class T> __device__ __forceinline__ T* add_off(T* p, uint32_t bytes) {
    uint64_t r;
    asm("{\n.reg .b64 o;\ncvt.u64.u32 o, %2;\nadd.u64 %0, %1, o;\n}\n" : "=l"(r) : "l"(p), "r"(bytes));
    return (T*)r;
}
__device__ __forceinline__ uint32_t unit_src(uint32_t q, uint32_t fg) { return q * (32 * kN * 4) + fg * 128; }
__device__ __forceinline__ uint32_t lane_src(int lane) { return (lane >> 3) * (2 * kN * 4) + (lane & 7) * 16; }
__device__ __forceinline__ uint32_t unit_dst(uint32_t q, uint32_t fg) {
    return ((fg >> 2) * KSTEPS + (q >> 1)) * 8192 + (fg & 3) * 2048 + (q & 1) * 512;
}
__device__ __forceinline__ uint32_t lane_dst(int lane) { return ((lane >> 2) & 1) * 1024 + (lane & 3) * 64 + (lane >> 3) * 16; }
__device__ __forceinline__ uint32_t lane_unit(int lane) {
    return ((lane >> 3) & 1) * 256 + (((lane >> 4) ^ (lane >> 3)) & 1) * 64 + (lane & 3) * 16 + ((lane >> 2) & 1) * 8;
}
__device__ __forceinline__ constexpr int unit_row(int i) { return 16 * (i >> 2) + 8 * ((i >> 1) & 1) + (i & 1); }
__device__ __forceinline__ void load_unit(uint4 (&v)[8], const int* p) {
#pragma unroll
    for (int i = 0; i < 8; i++) v[i] = ldg_stream(p + (size_t)unit_row(i) * kN);
}
__device__ __forceinline__ uint32_t bytes4(uint32_t v0, uint32_t v1, uint32_t v2, uint32_t v3) {
    return prmt(prmt(v0, v1, 0x0040), prmt(v2, v3, 0x0040), 0x5410);
}
__device__ __forceinline__ void pk_gather(uint32_t (&e)[4], uint32_t (&o)[4], const uint4 (&v)[8]) {
    e[0] = bytes4(v[0].x, v[2].x, v[4].x, v[6].x); o[0] = bytes4(v[1].x, v[3].x, v[5].x, v[7].x);
    e[1] = bytes4(v[0].y, v[2].y, v[4].y, v[6].y); o[1] = bytes4(v[1].y, v[3].y, v[5].y, v[7].y);
    e[2] = bytes4(v[0].z, v[2].z, v[4].z, v[6].z); o[2] = bytes4(v[1].z, v[3].z, v[5].z, v[7].z);
    e[3] = bytes4(v[0].w, v[2].w, v[4].w, v[6].w); o[3] = bytes4(v[1].w, v[3].w, v[5].w, v[7].w);
}

__device__ __forceinline__ void tile0_of(int c, int& fp, int& m0) {
    if (c < 18) { fp = c >= 9; m0 = min((c - 9 * fp) * N0, kM - N0); }
    else { fp = 2 + ((c - 18) >> 3); m0 = ((c - 18) & 7) * N0; }
}
__device__ __forceinline__ void tile1_of(int c, int& fp, int& m0) {
    if (c < 6) { fp = 2 + c; m0 = kM - N1; }
    else { fp = 8 + (c - 6) / 10; m0 = min(((c - 6) % 10) * N1, kM - N1); }
}

__device__ __forceinline__ void ll_fetch(u64 (&c)[4], const char* p) {
    asm volatile("ld.relaxed.gpu.global.b64 %0, [%4];\nld.relaxed.gpu.global.b64 %1, [%4 + 128];\n"
                 "ld.relaxed.gpu.global.b64 %2, [%4 + 512];\nld.relaxed.gpu.global.b64 %3, [%4 + 640];"
                 : "=l"(c[0]), "=l"(c[1]), "=l"(c[2]), "=l"(c[3]) : "l"(p) : "memory");
}
__device__ __forceinline__ void ll_copy(uint32_t dst, const char* src, uint32_t bar) {
    asm volatile("{\n.reg .pred p;\nelect.sync _|p, 0xffffffff;\n"
                 "@p cp.async.bulk.shared::cluster.global.mbarrier::complete_tx::bytes [%0], [%1], 1024, [%2];\n}\n"
                 ::"r"(dst), "l"(src), "r"(bar) : "memory");
}
__device__ __forceinline__ void ll_read(u64 (&c)[4], uint32_t a) {
    asm volatile("ld.volatile.shared.b64 %0, [%4];\nld.volatile.shared.b64 %1, [%4 + 128];\n"
                 "ld.volatile.shared.b64 %2, [%4 + 512];\nld.volatile.shared.b64 %3, [%4 + 640];"
                 : "=l"(c[0]), "=l"(c[1]), "=l"(c[2]), "=l"(c[3]) : "r"(a) : "memory");
}
template <int OFF>
__device__ __forceinline__ void ll_check(u64 (&c)[4], uint32_t a, const char* p, uint32_t tag) {
    asm volatile(
        "{\n.reg .pred p, q;\n.reg .b32 l, h0, h1, h2, h3, x, i, o;\n.reg .b64 g;\n"
        "mov.u32 i, 0;\n"
        "L_%=:\n"
        "mov.b64 {l, h0}, %0;\nmov.b64 {l, h1}, %1;\nmov.b64 {l, h2}, %2;\nmov.b64 {l, h3}, %3;\n"
        "lop3.b32 x, %6, h0, h1, 0x7e;\n"
        "lop3.b32 x, x, %6, h2, 0xf6;\n"
        "lop3.b32 x, x, %6, h3, 0xf6;\n"
        "setp.ne.u32 p, x, 0;\n"
        "vote.sync.any.pred p, p, 0xffffffff;\n"
        "@!p bra D_%=;\n"
        "and.b32 o, %4, 1023;\ncvt.u64.u32 g, o;\nadd.u64 g, g, %5;\n"
        "sub.u32 o, %6, 16;\n"
        "setp.eq.u32 q, h0, o;\nsetp.eq.or.u32 q, h1, o, q;\nsetp.eq.or.u32 q, h2, o, q;\nsetp.eq.or.u32 q, h3, o, q;\n"
        "setp.ge.or.u32 q, i, %8, q;\n"
        "vote.sync.any.pred q, q, 0xffffffff;\n"
        "@!q ld.volatile.shared.b64 %0, [%4 + %9];\n@!q ld.volatile.shared.b64 %1, [%4 + %9 + 128];\n"
        "@!q ld.volatile.shared.b64 %2, [%4 + %9 + 512];\n@!q ld.volatile.shared.b64 %3, [%4 + %9 + 640];\n"
        "@q ld.relaxed.gpu.global.b64 %0, [g];\n@q ld.relaxed.gpu.global.b64 %1, [g + 128];\n"
        "@q ld.relaxed.gpu.global.b64 %2, [g + 512];\n@q ld.relaxed.gpu.global.b64 %3, [g + 640];\n"
        "add.u32 i, i, 1;\n"
        "setp.lt.u32 p, i, %7;\n"
        "@p bra L_%=;\n"
        "D_%=:\n}\n"
        : "+l"(c[0]), "+l"(c[1]), "+l"(c[2]), "+l"(c[3])
        : "r"(a), "l"(p), "r"(tag), "n"(SPIN_LIMIT >> 4), "n"(NSPIN), "n"(OFF) : "memory");
}
__device__ __forceinline__ void ll_poll(u64 (&c)[4], const char* p, uint32_t tag) {
    unsigned it = 0;
    while (__any_sync(0xffffffffu, (((uint32_t)(c[0] >> 32) ^ tag) | ((uint32_t)(c[1] >> 32) ^ tag) |
                                    ((uint32_t)(c[2] >> 32) ^ tag) | ((uint32_t)(c[3] >> 32) ^ tag)) != 0) &&
           ++it < (SPIN_LIMIT >> 4))
        ll_fetch(c, p);
}
__device__ __forceinline__ void decode_alu(uint32_t& r0, uint32_t& r1, uint32_t& r2, uint32_t& r3, uint32_t w,
                                           const uint32_t (&lt)[8]) {
    const uint32_t s0 = w & 0x77777777u, s1 = s0 >> 16, w4 = w * 16;
    const uint32_t m0 = prmt(w4, w, 0xd9c8), m1 = prmt(w4, w, 0xfbea);
    const uint32_t l0 = (prmt(lt[0], lt[1], s0) & ~m0) | (prmt(lt[2], lt[3], s0) & m0);
    const uint32_t h0 = (prmt(lt[4], lt[5], s0) & ~m0) | (prmt(lt[6], lt[7], s0) & m0);
    const uint32_t l1 = (prmt(lt[0], lt[1], s1) & ~m1) | (prmt(lt[2], lt[3], s1) & m1);
    const uint32_t h1 = (prmt(lt[4], lt[5], s1) & ~m1) | (prmt(lt[6], lt[7], s1) & m1);
    r0 = prmt(l0, h0, 0x5140); r1 = prmt(l0, h0, 0x7362);
    r2 = prmt(l1, h1, 0x5140); r3 = prmt(l1, h1, 0x7362);
}
__device__ __forceinline__ void decode(uint32_t (&a)[16], const u64 (&c)[4], uint32_t tblv, const uint32_t (&lt)[8],
                                       const uint32_t (&mu)[4]) {
#pragma unroll
    for (int i = 0; i < 4; i++) {
        const int b = (i >> 1) * 8 + (i & 1);
        if (i < 4 - NALU) {
#pragma unroll
            for (int j = 0; j < 4; j++) a[b + 2 * j] = lds32(dp4a_u((uint32_t)c[i], mu[j], tblv));
        } else {
            decode_alu(a[b], a[b + 2], a[b + 4], a[b + 6], (uint32_t)c[i], lt);
        }
    }
}

__host__ __device__ constexpr int slot_of(int j) { return j < 16 ? j % 6 : (int)(0x2651032651032610ull >> (4 * (j - 16))) & 7; }
constexpr int STGA = 4, STGB = 3;
__host__ __device__ constexpr int slot_addr(int t, int s) {
    return t && (s < 2 || s == 6) ? (s == 6 ? 1 : 2 * s) * N1 * 128 : SLOT_OFF + s * SLOT_BYTES;
}
__host__ __device__ constexpr int stg_slot(int w) { return w ? STGB : STGA; }
__host__ __device__ constexpr int stg_uses(int w) {
    int n = stg_slot(w) == 4 || stg_slot(w) == 5;
    for (int i = 0; i < NSL; i++) n += slot_of(i) == stg_slot(w);
    return n;
}
__host__ __device__ constexpr bool reused(int j) {
    for (int i = j + 1; i < NSL; i++) if (slot_of(i) == slot_of(j)) return true;
    return j < 16 || slot_of(j) == STGA || slot_of(j) == STGB;
}
constexpr int STG_C0 = slot_addr(0, 6) - 2 * E0 * 128, STG_C1 = slot_addr(0, 4);
__host__ __device__ constexpr int loads_before(int j) {
    int n = 0;
    for (int i = 0; i < j; i++) n += slot_of(i) == slot_of(j);
    return n;
}
__host__ __device__ constexpr int uses_before(int j) {
    return loads_before(j) + (j >= 16 && (slot_of(j) == 4 || slot_of(j) == 5));
}
__host__ __device__ constexpr uint64_t prod_tbl(int j0) {
    uint64_t t = 0;
    for (int j = j0; j < j0 + 16; j++) t |= (uint64_t)(slot_of(j) | (((uses_before(j) + 1) & 1) << 3)) << (4 * (j - j0));
    return t;
}
__host__ __device__ constexpr uint64_t addr_tbl(int t) {
    uint64_t r = 0;
    for (int s = 0; s < NSLOTS; s++) r |= (uint64_t)(slot_addr(t, s) / 1024) << (8 * s);
    return r;
}
__host__ __device__ constexpr int dec_upto(int j) { return j < 14 ? j + 1 + (j >= RAMP1) + (j >= RAMP2) : j + 2 + (j >= RAMP3); }
__host__ __device__ constexpr bool ramp_first(int d) {
    return d == RAMP1 + 1 || d == RAMP2 + 2 || d == RAMP3 + 2;
}
__host__ __device__ constexpr bool read_early(int d) {
    return d > RLATE && d < NSL && !ramp_first(d - 2) && !ramp_first(d - 3) && d != 18 && d != 20 && d != 21;
}
__host__ __device__ constexpr bool get_early(int d) { return ramp_first(d); }

__device__ __forceinline__ void fence_a(uint32_t (&a)[16]) {
#pragma unroll
    for (int i = 0; i < 16; i++) asm volatile("" : "+r"(a[i])::"memory");
}
template <int J, int N, int COL>
__device__ __forceinline__ void mma_slice(float (&acc)[N0 / 2], uint32_t (&a)[4][16]) {
    constexpr int off = (slot_addr(J / KSTEPS, slot_of(J)) + COL * 128) / 16, b = J % 4;
    constexpr uint64_t d0 = make_desc(SMEM_BASE);
    WG<N, COL / 2, (J % KSTEPS) != 0, N0 / 2>::mma(acc, a[b][0], a[b][1], a[b][2], a[b][3], d0 + off);
    WG<N, COL / 2, true, N0 / 2>::mma(acc, a[b][4], a[b][5], a[b][6], a[b][7], d0 + (off + 2));
    WG<N, COL / 2, true, N0 / 2>::mma(acc, a[b][8], a[b][9], a[b][10], a[b][11], d0 + (off + 4));
    WG<N, COL / 2, true, N0 / 2>::mma(acc, a[b][12], a[b][13], a[b][14], a[b][15], d0 + (off + 6));
}
template <int N> __device__ __forceinline__ void rename_acc(float (&acc)[N0 / 2]) {
#pragma unroll
    for (int i = 0; i < N / 2; i++) asm volatile("mov.b32 %0, %1;" : "=f"(acc[i]) : "f"(acc[i]) : "memory");
}
template <int N, int COL, bool FENCE>
__device__ __forceinline__ void stage_out(float (&acc)[N0 / 2], uint32_t sa, const float s0, const float s1) {
#pragma unroll
    for (int i = COL / 2; i < (COL + N) / 2; i++) asm volatile("" : "+f"(acc[i])::"memory");
#pragma unroll
    for (int j = COL / 8; j + 1 < (COL + N) / 8; j += 2) {
        const uint32_t r0 = pack_bf16x2(acc[4 * j + 0] * s0, acc[4 * j + 1] * s0);
        const uint32_t r1 = pack_bf16x2(acc[4 * j + 2] * s1, acc[4 * j + 3] * s1);
        const uint32_t r2 = pack_bf16x2(acc[4 * j + 4] * s0, acc[4 * j + 5] * s0);
        const uint32_t r3 = pack_bf16x2(acc[4 * j + 6] * s1, acc[4 * j + 7] * s1);
        asm volatile("stmatrix.sync.aligned.m8n8.x4.trans.shared.b16 [%0], {%1, %2, %3, %4};"
                     ::"r"(sa + j * 1024), "r"(r0), "r"(r1), "r"(r2), "r"(r3) : "memory");
    }
    if constexpr ((N / 8) & 1) {
        constexpr int j = (COL + N) / 8 - 1;
        const uint32_t r0 = pack_bf16x2(acc[4 * j + 0] * s0, acc[4 * j + 1] * s0);
        const uint32_t r1 = pack_bf16x2(acc[4 * j + 2] * s1, acc[4 * j + 3] * s1);
        asm volatile("stmatrix.sync.aligned.m8n8.x2.trans.shared.b16 [%0], {%1, %2};"
                     ::"r"(sa + j * 1024), "r"(r0), "r"(r1) : "memory");
    }
    if constexpr (FENCE) asm volatile("fence.proxy.async.shared::cta;" ::: "memory");
}

struct Maps { CUtensorMap m[4 + NCH]; };

__global__ void __cluster_dims__(2, 1, 1) __launch_bounds__(NUM_THREADS, 1)
nf4_gemm_kernel(const int* __restrict__ qw, u64* __restrict__ ll, unsigned* __restrict__ epoch,
                const __nv_bfloat16* __restrict__ lut, const __nv_bfloat16* __restrict__ scales,
                const __grid_constant__ Maps tm) {
    extern __shared__ __align__(1024) uint8_t smem_raw[];
    const uint32_t t_start = clock32();
    const int lane = threadIdx.x & 31;
    if (threadIdx.x < 32)
        asm volatile("prefetch.global.L2 [%0];" ::"l"(add_off(qw, unit_src(blockIdx.x / W1_FG, blockIdx.x % W1_FG) + lane * (kN * 4))) : "memory");
    const int warp = __shfl_sync(0xffffffffu, threadIdx.x >> 5, 0);
    const uint32_t sb = smem_u32(smem_raw);
    const uint32_t bar_full = sb + BAR_OFF;
    const uint32_t bar_empty = bar_full + NSLOTS * 8;
    const uint32_t bar_tbl = bar_empty + NSLOTS * 8;
    const uint32_t bar_code = bar_tbl + 8;
    const uint32_t bar_stg = bar_code + 8;
    const int crank = blockIdx.x & 1, cluster = blockIdx.x >> 1;

    if (warp == 1) {
        if (lane == 0) {
            for (int i = 0; i < 2 * (2 + NCH); i++) mbar_init(bar_stg + i * 8, 128);
            asm volatile("fence.mbarrier_init.release.cluster;" ::: "memory");
        }
        __syncwarp();
    }
    if (warp != 8) cluster_arrive_relaxed();
    if (warp < 8) {
        const int wg = warp >> 2;
        const uint32_t tagl = ld_ca_u32(epoch + lane);
        const uint32_t lv = ldg_u16(reinterpret_cast<const unsigned short*>(lut) + (lane & 15));
        int fp0, fp1, mm;
        tile0_of(cluster, fp0, mm);
        tile1_of(cluster, fp1, mm);
        const int ft0 = fp0 * 2 + crank, ft1 = fp1 * 2 + crank;
        const unsigned short* sc16 = reinterpret_cast<const unsigned short*>(scales) + warp * 16 + (lane >> 2);
        uint32_t sc0 = ldg_u16(sc16 + ft0 * FT), sc0h = ldg_u16(sc16 + ft0 * FT + 8);
        uint32_t sc1 = ldg_u16(sc16 + ft1 * FT), sc1h = ldg_u16(sc16 + ft1 * FT + 8);
        {
            constexpr int EPS = 128 / TBLC;
#pragma unroll
            for (int k = 0; k < 32 / EPS; k++) {
                const int e = warp * 32 + k * EPS + lane / (TBLC / 4);
                const uint32_t v = __shfl_sync(0xffffffffu, lv, e & 15) | (__shfl_sync(0xffffffffu, lv, e >> 4) << 16);
                asm volatile("st.shared.v4.u32 [%0], {%1, %1, %1, %1};"
                             ::"r"(sb + TBL_OFF + warp * (TBLC * 128) + k * 512 + lane * 16), "r"(v) : "memory");
            }
        }
        asm volatile("setmaxnreg.inc.sync.aligned.u32 %0;" ::"n"(CREGS));
        cluster_wait();
        mbar_arrive(bar_tbl);
        TS(132);
        sc0 |= sc0h << 16;
        sc1 |= sc1h << 16;
        const char* ll0 = keep(reinterpret_cast<const char*>(ll) + (ft0 * (KSTEPS * 8192) + warp * 1024 + lane), 0);
        const char* ll1 = keep(reinterpret_cast<const char*>(ll) + (ft1 * (KSTEPS * 8192) + warp * 1024 + lane), 0);
        const uint32_t cbuf = sb + COD_OFF + warp * 1024;
        const uint32_t tblv = keep(sb + TBL_OFF + (lane % TBLC) * 4, lane);
        const uint32_t cempty = keep(lane < 2 ? mapa(bar_empty, lane) : 0, lane);
        const uint32_t sa0 = keep(sb + (((lane >> 4) * 8 + (lane & 7)) * 128) +
                                  ((((warp & 3) * 2 + ((lane >> 3) & 1)) ^ (lane & 7)) << 4), lane);
        uint32_t lt[8];
        {
            const uint32_t p01 = __shfl_sync(0xffffffffu, lv, 4 * lane) | (__shfl_sync(0xffffffffu, lv, 4 * lane + 1) << 16);
            const uint32_t p23 = __shfl_sync(0xffffffffu, lv, 4 * lane + 2) | (__shfl_sync(0xffffffffu, lv, 4 * lane + 3) << 16);
            const uint32_t pl = prmt(p01, p23, lane & 4 ? 0x7531 : 0x6420);
#pragma unroll
            for (int i = 0; i < 8; i++) lt[i] = __shfl_sync(0xffffffffu, pl, i & 1 ? i : i + (lane & 24));
        }
        uint32_t mu[4];
#pragma unroll
        for (int j = 0; j < 4; j++) mu[j] = keep(((uint32_t)(TBLC * 4) << (8 * j)) + lane, 0);
        uint32_t a[4][16];
        float acc[N0 / 2];

        auto src = [&](auto dc) {
            constexpr int D = decltype(dc)::value;
            return (D < KSTEPS ? ll0 : ll1) + (D % KSTEPS) * 8192;
        };
        const uint32_t tag = __shfl_sync(0xffffffffu, tagl, 0);
        u64 c[4];
        const uint32_t aw = keep(cbuf + lane_unit(lane), lane);
        auto fetch = [&](auto dc) {
            constexpr int D = decltype(dc)::value;
            if constexpr (D < NGATE) delay_until(t_start, gate_time(D));
            if constexpr (D < NSL) ll_copy(cbuf + (D & 1) * 8192, src(dc), bar_code);
        };
        auto get = [&](auto dc) {
            constexpr int D = decltype(dc)::value;
            if constexpr (D + 1 <= FLATE) fetch(IC<D + 1>{});
            if constexpr (!read_early(D)) ll_read(c, aw + (D & 1) * 8192);
            ll_check<(D & 1) * 8192>(c, aw, src(dc), tag + D % KSTEPS);
            if constexpr (D + 2 >= NGATE) fetch(IC<D + 2>{});
        };
        auto dec = [&](auto dc) {
            constexpr int D = decltype(dc)::value;
            decode(a[D % 4], c, tblv, lt, mu);
            if constexpr (D + 2 > FLATE && D + 2 < NGATE) fetch(IC<D + 2>{});
            if constexpr (read_early(D + 1)) ll_read(c, aw + ((D + 1) & 1) * 8192);
            if constexpr (get_early(D + 1)) get(IC<D + 1>{});
        };
        auto wait_full = [&](auto jc) {
            constexpr int J = decltype(jc)::value;
            mbar_wait(bar_full + slot_of(J) * 8, loads_before(J) & 1);
        };
        auto release = [&](auto jc) {
            constexpr int J = decltype(jc)::value;
            if constexpr (reused(J)) mbar_arrive_pair(cempty + slot_of(J) * 8, cempty);
        };
        auto step = [&](auto jc) {
            constexpr int J = decltype(jc)::value, D = dec_upto(J - 1) + 1;
            fence_a(a[J % 4]);
            wgmma_fence();
            mma_slice<J, (J < KSTEPS ? N0 : N1), 0>(acc, a);
            wgmma_commit();
            TS(J);
            if constexpr (!get_early(D)) get(IC<D>{});
            if constexpr (J >= NEARLY) wait_full(IC<J + 1>{});
            wgmma_wait<1>();
            if constexpr (J != 0 && J != 18) release(IC<J - 1>{});
            dec(IC<D>{});
            if constexpr (dec_upto(J) > D) { get(IC<D + 1>{}); dec(IC<D + 1>{}); }
            if constexpr (J < NEARLY) wait_full(IC<J + 1>{});
        };
        static_assert(FLATE >= 1 && FLATE < NGATE && RLATE >= FLATE && RLATE < RAMP1 && RAMP1 + 2 < RAMP2 && RAMP2 < 14 &&
                      RAMP3 > 20 && RAMP3 < 28, "code schedule");
        static_assert(slot_of(10) == 4 && slot_of(11) == 5 && uses_before(11) == 1 && STG_C1 + 2 * E1 * 128 <= STG_C0, "staging");

        mbar_wait(bar_tbl, 0);
        TS(133);
        delay_until(t_start, gate_time(0));
        ll_fetch(c, src(IC<0>{}) + (aw & 1023));
        fetch(IC<1>{});
        ll_poll(c, src(IC<0>{}) + (aw & 1023), tag);
        dec(IC<0>{});
        TS(134);
        wait_full(IC<0>{});
        TS(137);
        static_for<0, 14>(step);
        {
            const float s0 = __uint_as_float(sc0 << 16), s1 = __uint_as_float(sc0 & 0xffff0000u);
            const uint32_t sa = sa0 + STG_C0 + wg * (E0 * 128), sc = sa0 + STG_C1 - E0 * 128 + wg * (E1 * 128);
            auto group = [&](auto jc, auto nc, auto cc) {
                fence_a(a[decltype(jc)::value % 4]);
                wgmma_fence();
                mma_slice<decltype(jc)::value, decltype(nc)::value, decltype(cc)::value>(acc, a);
                wgmma_commit();
            };
            wait_full(IC<15>{});
            TS(140);
            wgmma_wait<0>();
            rename_acc<N0>(acc);
            group(IC<14>{}, IC<E0>{}, IC<0>{});
            release(IC<13>{});
            get(IC<17>{});
            mbar_wait(bar_empty + 5 * 8, 1);
            group(IC<15>{}, IC<E0>{}, IC<0>{});
            TS(14);
            dec(IC<17>{});
            TS(141);
            group(IC<14>{}, IC<E1>{}, IC<E0>{});
            TS(15);
            wgmma_wait<1>();
            stage_out<EI, 0, false>(acc, sa, s0, s1);
            group(IC<15>{}, IC<E1>{}, IC<E0>{});
            TS(142);
            wait_full(IC<16>{});
            wgmma_wait<1>();
            release(IC<14>{});
            TS(143);
            stage_out<E0 - EI, EI, true>(acc, sa, s0, s1);
            mbar_arrive(bar_stg + wg * 8);
            TS(144);
            group(IC<16>{}, IC<S0>{}, IC<0>{});
            wait_full(IC<17>{});
            wgmma_wait<1>();
            release(IC<15>{});
            TS(16);
            stage_out<EI, E0, false>(acc, sc, s0, s1);
            group(IC<17>{}, IC<S0>{}, IC<0>{});
            TS(128);
            stage_out<E1 - EI, E0 + EI, true>(acc, sc, s0, s1);
            mbar_arrive(bar_stg + 16 + wg * 8);
            TS(129);
            group(IC<16>{}, IC<S1>{}, IC<S0>{});
            get(IC<18>{}); dec(IC<18>{});
            group(IC<17>{}, IC<S1>{}, IC<S0>{});
            TS(17);
            get(IC<19>{});
            wait_full(IC<18>{});
            wgmma_wait<1>();
            release(IC<16>{});
            dec(IC<19>{});
            TS(145);
            wgmma_wait<0>();
            rename_acc<N1>(acc);
            release(IC<17>{});
            TS(146);
        }
        static_for<18, NSL - 4>(step);
        {
            constexpr int J0 = NSL - 4;
            const float s0 = __uint_as_float(sc1 << 16), s1 = __uint_as_float(sc1 & 0xffff0000u);
            const uint32_t sa = sa0 + (wg ? slot_addr(1, STGB) : slot_addr(1, STGA));
            wait_full(IC<J0 + 1>{}); wait_full(IC<J0 + 2>{});
            fence_a(a[0]); fence_a(a[1]); fence_a(a[2]);
            TS(160);
            wgmma_wait<0>();
            rename_acc<N1>(acc);
            wgmma_fence();
            mma_slice<J0, chunk_n(0), 0>(acc, a);
            TS(J0);
            release(IC<J0 - 1>{});
            get(IC<NSL - 1>{}); dec(IC<NSL - 1>{});
            asm volatile("{\n.reg .pred p;\nelect.sync _|p, 0xffffffff;\n"
                         "@p mbarrier.arrive.expect_tx.shared::cta.b64 _, [%0], %1;\n}\n" ::"r"(bar_code), "n"((NSL - 1) * 1024) : "memory");
            wgmma_fence();
            mma_slice<J0 + 1, chunk_n(0), 0>(acc, a);
            mma_slice<J0 + 2, chunk_n(0), 0>(acc, a);
            wait_full(IC<NSL - 1>{});
            fence_a(a[3]);
            wgmma_fence();
            mma_slice<J0 + 3, chunk_n(0), 0>(acc, a);
            wgmma_commit();
            static_for<1, NCH + 1>([&](auto cc) {
                constexpr int C = decltype(cc)::value;
                if constexpr (C < NCH) {
                    wgmma_fence();
                    mma_slice<J0, chunk_n(C), chunk_col(C)>(acc, a);
                    wgmma_commit();
                    if constexpr (C == 1)
                        mbar_wait(bar_empty + (wg ? STGB : STGA) * 8, (wg ? stg_uses(1) - 1 : stg_uses(0) - 1) & 1);
                    wgmma_wait<1>();
                } else {
                    wgmma_wait<0>();
                    TS(130);
                }
                stage_out<chunk_n(C - 1), chunk_col(C - 1), true>(acc, sa, s0, s1);
                mbar_arrive(bar_stg + (1 + C) * 16 + wg * 8);
                if constexpr (C < NCH) {
                    wgmma_fence();
                    static_for<J0 + 1, NSL>([&](auto jc) { mma_slice<decltype(jc)::value, chunk_n(C), chunk_col(C)>(acc, a); });
                    wgmma_commit();
                    if constexpr (C < 4) TS(J0 + C);
                }
            });
            TS(131);
        }
    } else {
      if (warp >= 9) {
        {
            const int pw = warp - 9;
            int u = pw * NUM_CTAS + blockIdx.x;
            uint32_t q = u / W1_FG, fg = u % W1_FG;
            const int* qwk = keep(add_off(qw, lane_src(lane)), lane);
            u64* llk = keep(add_off(ll, lane_dst(lane)), lane);
            const unsigned* ep = epoch + lane;
            asm volatile("setmaxnreg.dec.sync.aligned.u32 %0;" ::"n"(504 - 2 * CREGS));
            const uint32_t tag = ld_ca_u32(ep);
            if (pw > 0) delay_until(t_start, DLY_R0 + pw * DLY_R);
            uint4 v[8];
            load_unit(v, add_off(qwk, unit_src(q, fg)));
#pragma unroll 1
            for (;;) {
                u64* dst = add_off(llk, unit_dst(q, fg));
                const uint32_t sl = q >> 1;
                static_assert(RSTOP % NUM_AUX == 0, "pack rounds");
                u += u < (RSTOP - 1) * NUM_CTAS ? NUM_AUX * NUM_CTAS : pw == 2 ? NUM_UNITS : 2 * NUM_CTAS;
                unit_pos(min(u, NUM_UNITS - 1), q, fg);
                const int* p = add_off(qwk, unit_src(q, fg));
                uint32_t e[4], o[4], w[4];
                pk_gather(e, o, v);
#pragma unroll
                for (int k = 0; k < 4; k++)
                    asm("lop3.b32 %0, %1, %2, 0x0f0f0f0f, 0xe4;" : "=r"(w[k]) : "r"(e[k]), "r"(o[k] << 4));
                ll_store2(dst, w[0], w[1], tag + sl);
                ll_store2((u64*)((uint64_t)dst ^ 320), w[2], w[3], tag + sl);
                if (u >= NUM_UNITS) break;
                load_unit(v, p);
            }
        }
        const CUtensorMap* maps = keep(&tm.m[3] + lane, 0);
        named_bar_arrive<4, 128>();
        cluster_wait();
        int fp, m0;
        if (warp == 11) {
            tile0_of(cluster, fp, m0);
            const int f0 = (fp * 2 + crank) * FT;
#pragma unroll 1
            for (int ch = 0; ch < 2; ch++) {
                const uint32_t src = sb + (ch ? STG_C1 : STG_C0);
                const int rows = ch ? E1 : E0;
                int h = 0;
#pragma unroll 1
                for (unsigned it = 0; it < 16 * SPIN_LIMIT && !mbar_test(bar_stg + ch * 16 + h * 8, 0); it++) { h ^= 1; __nanosleep(20); }
#pragma unroll 1
                for (int k = 0; k < 2; k++, h ^= 1) {
                    mbar_wait(bar_stg + ch * 16 + h * 8, 0);
#pragma unroll 1
                    for (int r = 0; r < rows; r += 8) {
                        asm volatile("{\n.reg .pred p;\nelect.sync _|p, 0xffffffff;\n"
                                     "@p cp.async.bulk.tensor.2d.global.shared::cta.bulk_group [%0, {%2, %3}], [%1];\n"
                                     "cp.async.bulk.commit_group;\ncp.async.bulk.wait_group.read 1;\n}\n"
                                     ::"l"(maps), "r"(src + (h * rows + r) * 128), "r"(f0 + h * 64), "r"(m0 + ch * E0 + r)
                                     : "memory");
                    }
                }
                asm volatile("cp.async.bulk.wait_group.read 0;" ::: "memory");
                __syncwarp();
                if (lane < 2) mbar_arrive_cluster_n(mapa(bar_empty + (5 - ch) * 8, lane), 8);
                TSG(604 + ch * 2);
            }
        } else {
            const int wg = warp - 9;
            tile1_of(cluster, fp, m0);
            const int f0 = (fp * 2 + crank) * FT + wg * 64;
            const uint32_t src = sb + (wg ? slot_addr(1, STGB) : slot_addr(1, STGA));
            int r0 = 0;
#pragma unroll 1
            for (int ch = 0; ch < NCH; ch++) {
                mbar_wait(bar_stg + (2 + ch) * 16 + wg * 8, 0);
                asm volatile("{\n.reg .pred p;\nelect.sync _|p, 0xffffffff;\n"
                             "@p cp.async.bulk.tensor.2d.global.shared::cta.bulk_group [%0, {%2, %3}], [%1];\n}\n"
                             ::"l"(maps + 1 + ch), "r"(src + r0 * 128), "r"(f0), "r"(m0 + r0) : "memory");
                r0 += ((CHK >> (4 * ch)) & 15) * 8;
            }
            asm volatile("cp.async.bulk.commit_group;\ncp.async.bulk.wait_group.read 0;" ::: "memory");
            TSG(600 + wg * 2);
        }
      } else {
        asm volatile("setmaxnreg.dec.sync.aligned.u32 %0;" ::"n"(504 - 2 * CREGS));
        if ((sb & 0xFFFFFF) != SMEM_BASE) __trap();
        if (lane == 0) {
            for (int s = 0; s < NSLOTS; s++) {
                mbar_init(bar_full + s * 8, 1);
                mbar_init(bar_empty + s * 8, 16);
            }
            mbar_init(bar_tbl, 256);
            mbar_init(bar_code, 8);
            asm volatile("fence.mbarrier_init.release.cluster;" ::: "memory");
        }
        __syncwarp();
        cluster_arrive_relaxed();
        const CUtensorMap* maps = keep(&tm.m[0] + lane, 0);
        unsigned* epk = keep(epoch + lane, 0);
        if (lane == 0) prefetch_map(maps + crank);
        TSG(512);
        int fp, m0;
        tile0_of(cluster, fp, m0);
        cluster_wait();
#pragma unroll 1
        for (int t = 0; t < 2; t++) {
            const int lo = t == 0 ? 120 : 104, row = m0 + crank * lo;
            const CUtensorMap* map = maps + (t ? 2 : crank);
            const uint32_t bytes = (t ? N1 : N0) * 128, dst = sb + crank * lo * 128;
            uint64_t tbl = t ? prod_tbl(16) : prod_tbl(0);
            const uint64_t adr = t ? addr_tbl(1) : addr_tbl(0);
#pragma unroll 1
            for (int ks = 0; ks < KSTEPS; ks++, tbl >>= 4) {
                const uint32_t slot = (uint32_t)tbl & 7;
                if (t == 0 && ks > 0 && ks < 6) delay_until(t_start, DLY_X0 + ks * DLY_XS);
                mbar_wait(bar_empty + slot * 8, ((uint32_t)tbl >> 3) & 1);
                asm volatile(
                    "{\n.reg .pred p;\nelect.sync _|p, 0xffffffff;\n"
                    "@p mbarrier.arrive.expect_tx.shared::cta.b64 _, [%2], %5;\n"
                    "@p cp.async.bulk.tensor.2d.shared::cluster.global.mbarrier::complete_tx::bytes.multicast::cluster"
                    " [%0], [%1, {%3, %4}], [%2], %6;\n}\n"
                    ::"r"(dst + (((uint32_t)(adr >> (8 * slot)) & 255) << 10)), "l"(map), "r"(bar_full + slot * 8), "r"(ks * BK), "r"(row), "r"(bytes),
                    "h"((uint16_t)3) : "memory");
                TSG(514 + (t * 18 + ks) * 2);
            }
            tile1_of(cluster, fp, m0);
            if (t == 0 && lane >= 2 && lane < 4 + NCH) prefetch_map(maps + lane);
        }
        named_bar_sync<4, 128>();
        const uint32_t tag = ld_ca_u32(epk + lane);
        unsigned old = 0;
        if (lane == 0) old = atomicAdd(epk + 32, tag != 0 ? 1u : 0u);
        if (__shfl_sync(0xffffffffu, old, 0) == NUM_CTAS - 1) {
            if (lane == 0) epk[32] = 0;
            epk[lane] = tag == 0xfffffff0u ? 16 : tag + 16;
        }
        mbar_wait(bar_code, 0);
      }
    }
}

__global__ void generic_kernel(const __nv_bfloat16* __restrict__ x, const int* __restrict__ qw,
                               const __nv_bfloat16* __restrict__ lut, const __nv_bfloat16* __restrict__ scales,
                               __nv_bfloat16* __restrict__ out, int M, int N, int K, int G) {
    const int n = blockIdx.x * blockDim.x + threadIdx.x;
    const int m = blockIdx.y;
    if (n >= N) return;
    float acc = 0.f;
    for (int k = 0; k < K; k++) {
        const float l = __bfloat162float(lut[qw[(size_t)k * N + n] & 15]);
        const float s = __bfloat162float(scales[(size_t)(k / G) * N + n]);
        const float w = __bfloat162float(__float2bfloat16_rn(l * s));
        acc += __bfloat162float(x[(size_t)m * K + k]) * w;
    }
    out[(size_t)m * N + n] = __float2bfloat16_rn(acc);
}

typedef CUresult (*PFN_encodeTiled)(CUtensorMap*, CUtensorMapDataType, cuuint32_t, void*, const cuuint64_t*,
                                    const cuuint64_t*, const cuuint32_t*, const cuuint32_t*, CUtensorMapInterleave,
                                    CUtensorMapSwizzle, CUtensorMapL2promotion, CUtensorMapFloatOOBfill);

bool make_map_2d(PFN_encodeTiled fn, CUtensorMap* map, void* base, uint64_t inner, uint64_t outer, uint32_t box_inner,
                 uint32_t box_outer) {
    cuuint64_t dims[2] = {inner, outer};
    cuuint64_t strides[1] = {inner * 2};
    cuuint32_t box[2] = {box_inner, box_outer};
    cuuint32_t estr[2] = {1, 1};
    return fn(map, CU_TENSOR_MAP_DATA_TYPE_BFLOAT16, 2, base, dims, strides, box, estr, CU_TENSOR_MAP_INTERLEAVE_NONE,
              CU_TENSOR_MAP_SWIZZLE_128B, CU_TENSOR_MAP_L2_PROMOTION_L2_128B,
              CU_TENSOR_MAP_FLOAT_OOB_FILL_NONE) == CUDA_SUCCESS;
}

}

extern "C" void kernel_launch(void* const* d_in, const int* in_sizes, int n_in, void* d_out, int out_size) {
    const __nv_bfloat16* x = (const __nv_bfloat16*)d_in[0];
    const int* qw = (const int*)d_in[1];
    const __nv_bfloat16* lut = (const __nv_bfloat16*)d_in[2];
    const __nv_bfloat16* scales = (const __nv_bfloat16*)d_in[3];
    __nv_bfloat16* out = (__nv_bfloat16*)d_out;

    const double Kd = sqrt((double)in_sizes[0] * (double)in_sizes[1] / (double)out_size);
    const int K = (int)(Kd + 0.5);
    const int M = in_sizes[0] / K, N = in_sizes[1] / K;
    const int ng = in_sizes[3] / N;
    const int G = K / ng;

    bool fast = (M == kM && N == kN && K == kK && ng == 1 && in_sizes[2] >= 16);
    PFN_encodeTiled enc = nullptr;
    Maps tm;
    void *ll = nullptr, *epoch = nullptr;
    if (fast) {
        cudaDriverEntryPointQueryResult qres;
        void* fp = nullptr;
        if (cudaGetDriverEntryPoint("cuTensorMapEncodeTiled", &fp, cudaEnableDefault, &qres) != cudaSuccess || !fp) fast = false;
        enc = (PFN_encodeTiled)fp;
    }
    if (fast) {
        fast = make_map_2d(enc, &tm.m[0], (void*)x, kK, kM, BK, 120) &&
               make_map_2d(enc, &tm.m[1], (void*)x, kK, kM, BK, 112) &&
               make_map_2d(enc, &tm.m[2], (void*)x, kK, kM, BK, 104) &&
               make_map_2d(enc, &tm.m[3], (void*)out, kN, kM, 64, 8) &&
               cudaGetSymbolAddress(&ll, g_ll) == cudaSuccess && cudaGetSymbolAddress(&epoch, g_epoch) == cudaSuccess;
    }
    for (int c = 0; c < NCH && fast; c++) fast = make_map_2d(enc, &tm.m[4 + c], (void*)out, kN, kM, 64, chunk_n(c));
    cudaLaunchConfig_t cfg = {};
    cfg.gridDim = dim3(NUM_CTAS);
    cfg.blockDim = dim3(NUM_THREADS);
    cfg.dynamicSmemBytes = SMEM_TOTAL;
    cfg.stream = cudaStreamPerThread;
    if (fast) {
        int nclusters = 0;
        fast = cudaFuncSetAttribute(nf4_gemm_kernel, cudaFuncAttributeMaxDynamicSharedMemorySize, SMEM_TOTAL) == cudaSuccess &&
               cudaOccupancyMaxActiveClusters(&nclusters, nf4_gemm_kernel, &cfg) == cudaSuccess &&
               nclusters >= NUM_CTAS / 2;
    }
    if (!fast) {
        generic_kernel<<<dim3((N + 127) / 128, M), 128>>>(x, qw, lut, scales, out, M, N, K, G);
        return;
    }
    cudaLaunchKernelEx(&cfg, nf4_gemm_kernel, qw, (u64*)ll, (unsigned*)epoch, lut, scales, tm);
}
```

```cpp
#include <cuda_runtime.h>
#include <cuda_bf16.h>
#include <cuda.h>
#include <stdint.h>
#include <stdio.h>
#include <math.h>

namespace {

constexpr int kM = 2048, kN = 3584, kK = 1024;
constexpr int FT = 128;
constexpr int N0 = 232, N1 = 208;
constexpr int BK = 64, KSTEPS = kK / BK;
constexpr int NSL = 2 * KSTEPS;
constexpr int NSLOTS = 7;
constexpr int SLOT_BYTES = N0 * 128;
constexpr int SLOT_OFF = 3 * N1 * 128 - 2 * SLOT_BYTES;
#define TBLC 16
constexpr int TBL_OFF = SLOT_OFF + 6 * SLOT_BYTES;
constexpr int COD_OFF = TBL_OFF + TBLC * 1024;
constexpr int BAR_OFF = COD_OFF + 2 * 8192;
constexpr int SMEM_TOTAL = BAR_OFF + 256;
constexpr int NUM_THREADS = 384;
constexpr int NUM_CTAS = 132;
constexpr int NUM_AUX = 3;
constexpr int CREGS = 224;
constexpr int NQ = kK / 32, NUM_UNITS = NQ * (kN / 32);
constexpr int W1_FG = 64, W2_FG = kN / 32 - W1_FG;
#define DLY_R0 200
#define DLY_R 400
#define DLY_X0 1000
#define DLY_XS 900
#define DLY_POLL 2600
#define DLY_P1 3250
#define DLY_PS 700
#define NGATE 8
#define FLATE 3
#define RLATE 4
#define NEARLY 4
#define RAMP1 9
#define RAMP2 12
#define RAMP3 22
#define NSPIN 24
#define NALU 2
#define RSTOP 18
#define JW 5
#define RAMP4 25
#define HALF 1
#define EI 64
constexpr int E0 = 120, E1 = N0 - E0, S0 = 112, S1 = N1 - S0;
#define CHK 0x4688
__host__ __device__ constexpr int chunk_n(int c) { return ((CHK >> (4 * c)) & 15) * 8; }
__host__ __device__ constexpr int chunk_col(int c) { return c ? chunk_col(c - 1) + chunk_n(c - 1) : 0; }
constexpr int NCH = CHK > 0xfffff ? 6 : CHK > 0xffff ? 5 : CHK > 0xfff ? 4 : 3;
static_assert(chunk_col(NCH) == N1 && S0 <= E0, "chunks");
constexpr unsigned SPIN_LIMIT = 1u << 20;

__device__ __align__(1024) unsigned long long g_ll[(size_t)(kN / FT) * NQ * FT * 4];
__device__ __align__(256) unsigned int g_epoch[64] = {16, 16, 16, 16, 16, 16, 16, 16, 16, 16, 16, 16, 16, 16, 16, 16,
                                                      16, 16, 16, 16, 16, 16, 16, 16, 16, 16, 16, 16, 16, 16, 16, 16};

#define TS(idx) do {} while (0)
#define TSW(idx) do {} while (0)
#define TSG(idx) do {} while (0)

template <int I> struct IC { static constexpr int value = I; };
template <int B, int E, class F> __device__ __forceinline__ void static_for(F&& f) {
    if constexpr (B < E) { f(IC<B>{}); static_for<B + 1, E>(f); }
}

__device__ __forceinline__ uint32_t smem_u32(const void* p) { return (uint32_t)__cvta_generic_to_shared(p); }
__device__ __forceinline__ uint32_t keep(uint32_t v, int lane) {
    asm volatile("shfl.sync.idx.b32 %0, %0, %1, 0x1f, 0xffffffff;" : "+r"(v) : "r"(lane));
    return v;
}
template <class T> __device__ __forceinline__ T* keep(T* p, int lane) {
    const uint64_t v = (uint64_t)p;
    return (T*)(((uint64_t)keep((uint32_t)(v >> 32), lane) << 32) | keep((uint32_t)v, lane));
}
__device__ __forceinline__ void mbar_init(uint32_t bar, uint32_t count) {
    asm volatile("mbarrier.init.shared::cta.b64 [%0], %1;" ::"r"(bar), "r"(count) : "memory");
}
__device__ __forceinline__ uint32_t clock32() { uint64_t c; asm volatile("mov.u64 %0, %%clock64;" : "=l"(c)); return (uint32_t)c; }
__device__ __forceinline__ void mbar_arrive(uint32_t bar) {
    asm volatile("mbarrier.arrive.shared::cta.b64 _, [%0];" ::"r"(bar) : "memory");
}
__device__ __forceinline__ uint32_t mapa(uint32_t a, uint32_t rank) {
    uint32_t r;
    asm("mapa.shared::cluster.u32 %0, %1, %2;" : "=r"(r) : "r"(a), "r"(rank));
    return r;
}
__device__ __forceinline__ void mbar_arrive_pair(uint32_t cbar, uint32_t base) {
    asm volatile("{\n.reg .pred p;\nsetp.ne.u32 p, %1, 0;\n@p mbarrier.arrive.shared::cluster.b64 _, [%0];\n}\n"
                 ::"r"(cbar), "r"(base) : "memory");
}
__device__ __forceinline__ void mbar_arrive_cluster_n(uint32_t cbar, uint32_t n) {
    asm volatile("mbarrier.arrive.shared::cluster.b64 _, [%0], %1;" ::"r"(cbar), "r"(n) : "memory");
}
__device__ __forceinline__ void delay_until(uint32_t t0, int clks) {
    while (__any_sync(0xffffffffu, (int)(clock32() - t0) < clks)) {}
}
__device__ __forceinline__ bool mbar_test(uint32_t bar, uint32_t parity) {
    uint32_t ok;
    asm volatile("{\n.reg .pred p;\nmbarrier.test_wait.parity.shared::cta.b64 p, [%1], %2;\nvote.sync.all.pred p, p, 0xffffffff;\nselp.u32 %0, 1, 0, p;\n}\n"
                 : "=r"(ok) : "r"(bar), "r"(parity) : "memory");
    return ok != 0;
}
__device__ __forceinline__ void mbar_wait(uint32_t bar, uint32_t parity) {
    asm volatile(
        "{\n.reg .pred p;\n.reg .u32 i;\n"
        "mbarrier.try_wait.parity.shared::cta.b64 p, [%0], %1;\n"
        "@p bra D_%=;\n"
        "mov.u32 i, 0;\n"
        "L_%=:\n"
        "mbarrier.try_wait.parity.shared::cta.b64 p, [%0], %1;\n"
        "@p bra D_%=;\n"
        "add.u32 i, i, 1;\n"
        "setp.lt.u32 p, i, %2;\n"
        "@p bra L_%=;\n"
        "D_%=:\n}\n"
        ::"r"(bar), "r"(parity), "n"(SPIN_LIMIT) : "memory");
}
__device__ __forceinline__ void prefetch_map(const CUtensorMap* map) {
    asm volatile("prefetch.tensormap [%0];" ::"l"(map) : "memory");
}
constexpr uint32_t SMEM_BASE = 1024;
__host__ __device__ constexpr uint64_t make_desc(uint32_t saddr) {
    return (uint64_t)((saddr & 0x3FFFF) >> 4) | ((uint64_t)1 << 16) | ((uint64_t)(1024 >> 4) << 32) | ((uint64_t)1 << 62);
}
__device__ __forceinline__ void wgmma_fence() { asm volatile("wgmma.fence.sync.aligned;" ::: "memory"); }
__device__ __forceinline__ void wgmma_commit() { asm volatile("wgmma.commit_group.sync.aligned;" ::: "memory"); }
template <int N> __device__ __forceinline__ void wgmma_wait() {
    asm volatile("wgmma.wait_group.sync.aligned %0;" ::"n"(N) : "memory");
}
__device__ __forceinline__ uint32_t pack_bf16x2(float lo, float hi) {
    uint32_t r;
    asm("cvt.rn.bf16x2.f32 %0, %1, %2;" : "=r"(r) : "f"(hi), "f"(lo));
    return r;
}
__device__ __forceinline__ uint32_t lds32(uint32_t addr) {
    uint32_t v;
    asm("ld.shared.u32 %0, [%1];" : "=r"(v) : "r"(addr));
    return v;
}
__device__ __forceinline__ uint32_t dp4a_u(uint32_t a, uint32_t b, uint32_t c) {
    uint32_t d;
    asm("dp4a.u32.u32 %0, %1, %2, %3;" : "=r"(d) : "r"(a), "r"(b), "r"(c));
    return d;
}
__device__ __forceinline__ uint32_t prmt(uint32_t a, uint32_t b, uint32_t s) {
    uint32_t d;
    asm("prmt.b32 %0, %1, %2, %3;" : "=r"(d) : "r"(a), "r"(b), "r"(s));
    return d;
}
template <int ID, int NT> __device__ __forceinline__ void named_bar_sync() {
    asm volatile("bar.sync %0, %1;" ::"n"(ID), "n"(NT) : "memory");
}
template <int ID, int NT> __device__ __forceinline__ void named_bar_arrive() {
    asm volatile("bar.arrive %0, %1;" ::"n"(ID), "n"(NT) : "memory");
}
__device__ __forceinline__ void cluster_arrive_relaxed() { asm volatile("barrier.cluster.arrive.relaxed.aligned;" ::: "memory"); }
__device__ __forceinline__ void cluster_wait() { asm volatile("barrier.cluster.wait.acquire.aligned;" ::: "memory"); }
__device__ __forceinline__ uint4 ldg_stream(const int* p) {
    uint4 v;
    asm volatile("ld.global.L1::no_allocate.L2::128B.v4.u32 {%0, %1, %2, %3}, [%4];"
                 : "=r"(v.x), "=r"(v.y), "=r"(v.z), "=r"(v.w) : "l"(p));
    return v;
}
__device__ __forceinline__ uint32_t ldg_u16(const unsigned short* p) {
    uint32_t v;
    asm volatile("ld.global.nc.u16 %0, [%1];" : "=r"(v) : "l"(p));
    return v;
}
__device__ __forceinline__ unsigned ld_ca_u32(const unsigned* p) {
    unsigned v;
    asm volatile("ld.global.ca.u32 %0, [%1];" : "=r"(v) : "l"(p) : "memory");
    return v;
}
typedef unsigned long long u64;
__device__ __forceinline__ void ll_store2(u64* p, uint32_t w0, uint32_t w1, uint32_t tag) {
    asm volatile("{\n.reg .b64 a, b;\nmov.b64 a, {%1, %3};\nmov.b64 b, {%2, %3};\n"
                 "st.relaxed.gpu.global.v2.b64 [%0], {a, b};\n}\n" ::"l"(p), "r"(w0), "r"(w1), "r"(tag) : "memory");
}

template <int N, int OFF, bool ACC, int NA> struct WG;
template <int OFF, int NA> struct WG<232, OFF, false, NA> {
    static __device__ __forceinline__ void mma(float (&d)[NA], uint32_t a0, uint32_t a1, uint32_t a2, uint32_t a3, uint64_t descB) {
        asm volatile(
            "{\n"
            ".reg .pred p;\n"
            "setp.ne.b32 p, %121, 0;\n"
            "wgmma.mma_async.sync.aligned.m64n232k16.f32.bf16.bf16 "
            "{%0, %1, %2, %3, %4, %5, %6, %7, %8, %9, %10, %11, %12, %13, %14, %15, %16, %17, %18, %19, %20, %21, %22, %23, %24, %25, %26, %27, %28, %29, %30, %31, %32, %33, %34, %35, %36, %37, %38, %39, %40, %41, %42, %43, %44, %45, %46, %47, %48, %49, %50, %51, %52, %53, %54, %55, %56, %57, %58, %59, %60, %61, %62, %63, %64, %65, %66, %67, %68, %69, %70, %71, %72, %73, %74, %75, %76, %77, %78, %79, %80, %81, %82, %83, %84, %85, %86, %87, %88, %89, %90, %91, %92, %93, %94, %95, %96, %97, %98, %99, %100, %101, %102, %103, %104, %105, %106, %107, %108, %109, %110, %111, %112, %113, %114, %115}, "
            "{%116, %117, %118, %119}, %120, p, 1, 1, 0;\n"
            "}\n"
            : "=f"(d[OFF + 0]), "=f"(d[OFF + 1]), "=f"(d[OFF + 2]), "=f"(d[OFF + 3]), "=f"(d[OFF + 4]), "=f"(d[OFF + 5]), "=f"(d[OFF + 6]), "=f"(d[OFF + 7]), "=f"(d[OFF + 8]), "=f"(d[OFF + 9]), "=f"(d[OFF + 10]), "=f"(d[OFF + 11]), "=f"(d[OFF + 12]), "=f"(d[OFF + 13]), "=f"(d[OFF + 14]), "=f"(d[OFF + 15]), "=f"(d[OFF + 16]), "=f"(d[OFF + 17]), "=f"(d[OFF + 18]), "=f"(d[OFF + 19]), "=f"(d[OFF + 20]), "=f"(d[OFF + 21]), "=f"(d[OFF + 22]), "=f"(d[OFF + 23]), "=f"(d[OFF + 24]), "=f"(d[OFF + 25]), "=f"(d[OFF + 26]), "=f"(d[OFF + 27]), "=f"(d[OFF + 28]), "=f"(d[OFF + 29]), "=f"(d[OFF + 30]), "=f"(d[OFF + 31]), "=f"(d[OFF + 32]), "=f"(d[OFF + 33]), "=f"(d[OFF + 34]), "=f"(d[OFF + 35]), "=f"(d[OFF + 36]), "=f"(d[OFF + 37]), "=f"(d[OFF + 38]), "=f"(d[OFF + 39]), "=f"(d[OFF + 40]), "=f"(d[OFF + 41]), "=f"(d[OFF + 42]), "=f"(d[OFF + 43]), "=f"(d[OFF + 44]), "=f"(d[OFF + 45]), "=f"(d[OFF + 46]), "=f"(d[OFF + 47]), "=f"(d[OFF + 48]), "=f"(d[OFF + 49]), "=f"(d[OFF + 50]), "=f"(d[OFF + 51]), "=f"(d[OFF + 52]), "=f"(d[OFF + 53]), "=f"(d[OFF + 54]), "=f"(d[OFF + 55]), "=f"(d[OFF + 56]), "=f"(d[OFF + 57]), "=f"(d[OFF + 58]), "=f"(d[OFF + 59]), "=f"(d[OFF + 60]), "=f"(d[OFF + 61]), "=f"(d[OFF + 62]), "=f"(d[OFF + 63]), "=f"(d[OFF + 64]), "=f"(d[OFF + 65]), "=f"(d[OFF + 66]), "=f"(d[OFF + 67]), "=f"(d[OFF + 68]), "=f"(d[OFF + 69]), "=f"(d[OFF + 70]), "=f"(d[OFF + 71]), "=f"(d[OFF + 72]), "=f"(d[OFF + 73]), "=f"(d[OFF + 74]), "=f"(d[OFF + 75]), "=f"(d[OFF + 76]), "=f"(d[OFF + 77]), "=f"(d[OFF + 78]), "=f"(d[OFF + 79]), "=f"(d[OFF + 80]), "=f"(d[OFF + 81]), "=f"(d[OFF + 82]), "=f"(d[OFF + 83]), "=f"(d[OFF + 84]), "=f"(d[OFF + 85]), "=f"(d[OFF + 86]), "=f"(d[OFF + 87]), "=f"(d[OFF + 88]), "=f"(d[OFF + 89]), "=f"(d[OFF + 90]), "=f"(d[OFF + 91]), "=f"(d[OFF + 92]), "=f"(d[OFF + 93]), "=f"(d[OFF + 94]), "=f"(d[OFF + 95]), "=f"(d[OFF + 96]), "=f"(d[OFF + 97]), "=f"(d[OFF + 98]), "=f"(d[OFF + 99]), "=f"(d[OFF + 100]), "=f"(d[OFF + 101]), "=f"(d[OFF + 102]), "=f"(d[OFF + 103]), "=f"(d[OFF + 104]), "=f"(d[OFF + 105]), "=f"(d[OFF + 106]), "=f"(d[OFF + 107]), "=f"(d[OFF + 108]), "=f"(d[OFF + 109]), "=f"(d[OFF + 110]), "=f"(d[OFF + 111]), "=f"(d[OFF + 112]), "=f"(d[OFF + 113]), "=f"(d[OFF + 114]), "=f"(d[OFF + 115])
            : "r"(a0), "r"(a1), "r"(a2), "r"(a3), "l"(descB), "n"(0));
    }
};
template <int OFF, int NA> struct WG<232, OFF, true, NA> {
    static __device__ __forceinline__ void mma(float (&d)[NA], uint32_t a0, uint32_t a1, uint32_t a2, uint32_t a3, uint64_t descB) {
        asm volatile(
            "{\n"
            ".reg .pred p;\n"
            "setp.ne.b32 p, %121, 0;\n"
            "wgmma.mma_async.sync.aligned.m64n232k16.f32.bf16.bf16 "
            "{%0, %1, %2, %3, %4, %5, %6, %7, %8, %9, %10, %11, %12, %13, %14, %15, %16, %17, %18, %19, %20, %21, %22, %23, %24, %25, %26, %27, %28, %29, %30, %31, %32, %33, %34, %35, %36, %37, %38, %39, %40, %41, %42, %43, %44, %45, %46, %47, %48, %49, %50, %51, %52, %53, %54, %55, %56, %57, %58, %59, %60, %61, %62, %63, %64, %65, %66, %67, %68, %69, %70, %71, %72, %73, %74, %75, %76, %77, %78, %79, %80, %81, %82, %83, %84, %85, %86, %87, %88, %89, %90, %91, %92, %93, %94, %95, %96, %97, %98, %99, %100, %101, %102, %103, %104, %105, %106, %107, %108, %109, %110, %111, %112, %113, %114, %115}, "
            "{%116, %117, %118, %119}, %120, p, 1, 1, 0;\n"
            "}\n"
            : "+f"(d[OFF + 0]), "+f"(d[OFF + 1]), "+f"(d[OFF + 2]), "+f"(d[OFF + 3]), "+f"(d[OFF + 4]), "+f"(d[OFF + 5]), "+f"(d[OFF + 6]), "+f"(d[OFF + 7]), "+f"(d[OFF + 8]), "+f"(d[OFF + 9]), "+f"(d[OFF + 10]), "+f"(d[OFF + 11]), "+f"(d[OFF + 12]), "+f"(d[OFF + 13]), "+f"(d[OFF + 14]), "+f"(d[OFF + 15]), "+f"(d[OFF + 16]), "+f"(d[OFF + 17]), "+f"(d[OFF + 18]), "+f"(d[OFF + 19]), "+f"(d[OFF + 20]), "+f"(d[OFF + 21]), "+f"(d[OFF + 22]), "+f"(d[OFF + 23]), "+f"(d[OFF + 24]), "+f"(d[OFF + 25]), "+f"(d[OFF + 26]), "+f"(d[OFF + 27]), "+f"(d[OFF + 28]), "+f"(d[OFF + 29]), "+f"(d[OFF + 30]), "+f"(d[OFF + 31]), "+f"(d[OFF + 32]), "+f"(d[OFF + 33]), "+f"(d[OFF + 34]), "+f"(d[OFF + 35]), "+f"(d[OFF + 36]), "+f"(d[OFF + 37]), "+f"(d[OFF + 38]), "+f"(d[OFF + 39]), "+f"(d[OFF + 40]), "+f"(d[OFF + 41]), "+f"(d[OFF + 42]), "+f"(d[OFF + 43]), "+f"(d[OFF + 44]), "+f"(d[OFF + 45]), "+f"(d[OFF + 46]), "+f"(d[OFF + 47]), "+f"(d[OFF + 48]), "+f"(d[OFF + 49]), "+f"(d[OFF + 50]), "+f"(d[OFF + 51]), "+f"(d[OFF + 52]), "+f"(d[OFF + 53]), "+f"(d[OFF + 54]), "+f"(d[OFF + 55]), "+f"(d[OFF + 56]), "+f"(d[OFF + 57]), "+f"(d[OFF + 58]), "+f"(d[OFF + 59]), "+f"(d[OFF + 60]), "+f"(d[OFF + 61]), "+f"(d[OFF + 62]), "+f"(d[OFF + 63]), "+f"(d[OFF + 64]), "+f"(d[OFF + 65]), "+f"(d[OFF + 66]), "+f"(d[OFF + 67]), "+f"(d[OFF + 68]), "+f"(d[OFF + 69]), "+f"(d[OFF + 70]), "+f"(d[OFF + 71]), "+f"(d[OFF + 72]), "+f"(d[OFF + 73]), "+f"(d[OFF + 74]), "+f"(d[OFF + 75]), "+f"(d[OFF + 76]), "+f"(d[OFF + 77]), "+f"(d[OFF + 78]), "+f"(d[OFF + 79]), "+f"(d[OFF + 80]), "+f"(d[OFF + 81]), "+f"(d[OFF + 82]), "+f"(d[OFF + 83]), "+f"(d[OFF + 84]), "+f"(d[OFF + 85]), "+f"(d[OFF + 86]), "+f"(d[OFF + 87]), "+f"(d[OFF + 88]), "+f"(d[OFF + 89]), "+f"(d[OFF + 90]), "+f"(d[OFF + 91]), "+f"(d[OFF + 92]), "+f"(d[OFF + 93]), "+f"(d[OFF + 94]), "+f"(d[OFF + 95]), "+f"(d[OFF + 96]), "+f"(d[OFF + 97]), "+f"(d[OFF + 98]), "+f"(d[OFF + 99]), "+f"(d[OFF + 100]), "+f"(d[OFF + 101]), "+f"(d[OFF + 102]), "+f"(d[OFF + 103]), "+f"(d[OFF + 104]), "+f"(d[OFF + 105]), "+f"(d[OFF + 106]), "+f"(d[OFF + 107]), "+f"(d[OFF + 108]), "+f"(d[OFF + 109]), "+f"(d[OFF + 110]), "+f"(d[OFF + 111]), "+f"(d[OFF + 112]), "+f"(d[OFF + 113]), "+f"(d[OFF + 114]), "+f"(d[OFF + 115])
            : "r"(a0), "r"(a1), "r"(a2), "r"(a3), "l"(descB), "n"(1));
    }
};
template <int OFF, int NA> struct WG<208, OFF, false, NA> {
    static __device__ __forceinline__ void mma(float (&d)[NA], uint32_t a0, uint32_t a1, uint32_t a2, uint32_t a3, uint64_t descB) {
        asm volatile(
            "{\n"
            ".reg .pred p;\n"
            "setp.ne.b32 p, %109, 0;\n"
            "wgmma.mma_async.sync.aligned.m64n208k16.f32.bf16.bf16 "
            "{%0, %1, %2, %3, %4, %5, %6, %7, %8, %9, %10, %11, %12, %13, %14, %15, %16, %17, %18, %19, %20, %21, %22, %23, %24, %25, %26, %27, %28, %29, %30, %31, %32, %33, %34, %35, %36, %37, %38, %39, %40, %41, %42, %43, %44, %45, %46, %47, %48, %49, %50, %51, %52, %53, %54, %55, %56, %57, %58, %59, %60, %61, %62, %63, %64, %65, %66, %67, %68, %69, %70, %71, %72, %73, %74, %75, %76, %77, %78, %79, %80, %81, %82, %83, %84, %85, %86, %87, %88, %89, %90, %91, %92, %93, %94, %95, %96, %97, %98, %99, %100, %101, %102, %103}, "
            "{%104, %105, %106, %107}, %108, p, 1, 1, 0;\n"
            "}\n"
            : "=f"(d[OFF + 0]), "=f"(d[OFF + 1]), "=f"(d[OFF + 2]), "=f"(d[OFF + 3]), "=f"(d[OFF + 4]), "=f"(d[OFF + 5]), "=f"(d[OFF + 6]), "=f"(d[OFF + 7]), "=f"(d[OFF + 8]), "=f"(d[OFF + 9]), "=f"(d[OFF + 10]), "=f"(d[OFF + 11]), "=f"(d[OFF + 12]), "=f"(d[OFF + 13]), "=f"(d[OFF + 14]), "=f"(d[OFF + 15]), "=f"(d[OFF + 16]), "=f"(d[OFF + 17]), "=f"(d[OFF + 18]), "=f"(d[OFF + 19]), "=f"(d[OFF + 20]), "=f"(d[OFF + 21]), "=f"(d[OFF + 22]), "=f"(d[OFF + 23]), "=f"(d[OFF + 24]), "=f"(d[OFF + 25]), "=f"(d[OFF + 26]), "=f"(d[OFF + 27]), "=f"(d[OFF + 28]), "=f"(d[OFF + 29]), "=f"(d[OFF + 30]), "=f"(d[OFF + 31]), "=f"(d[OFF + 32]), "=f"(d[OFF + 33]), "=f"(d[OFF + 34]), "=f"(d[OFF + 35]), "=f"(d[OFF + 36]), "=f"(d[OFF + 37]), "=f"(d[OFF + 38]), "=f"(d[OFF + 39]), "=f"(d[OFF + 40]), "=f"(d[OFF + 41]), "=f"(d[OFF + 42]), "=f"(d[OFF + 43]), "=f"(d[OFF + 44]), "=f"(d[OFF + 45]), "=f"(d[OFF + 46]), "=f"(d[OFF + 47]), "=f"(d[OFF + 48]), "=f"(d[OFF + 49]), "=f"(d[OFF + 50]), "=f"(d[OFF + 51]), "=f"(d[OFF + 52]), "=f"(d[OFF + 53]), "=f"(d[OFF + 54]), "=f"(d[OFF + 55]), "=f"(d[OFF + 56]), "=f"(d[OFF + 57]), "=f"(d[OFF + 58]), "=f"(d[OFF + 59]), "=f"(d[OFF + 60]), "=f"(d[OFF + 61]), "=f"(d[OFF + 62]), "=f"(d[OFF + 63]), "=f"(d[OFF + 64]), "=f"(d[OFF + 65]), "=f"(d[OFF + 66]), "=f"(d[OFF + 67]), "=f"(d[OFF + 68]), "=f"(d[OFF + 69]), "=f"(d[OFF + 70]), "=f"(d[OFF + 71]), "=f"(d[OFF + 72]), "=f"(d[OFF + 73]), "=f"(d[OFF + 74]), "=f"(d[OFF + 75]), "=f"(d[OFF + 76]), "=f"(d[OFF + 77]), "=f"(d[OFF + 78]), "=f"(d[OFF + 79]), "=f"(d[OFF + 80]), "=f"(d[OFF + 81]), "=f"(d[OFF + 82]), "=f"(d[OFF + 83]), "=f"(d[OFF + 84]), "=f"(d[OFF + 85]), "=f"(d[OFF + 86]), "=f"(d[OFF + 87]), "=f"(d[OFF + 88]), "=f"(d[OFF + 89]), "=f"(d[OFF + 90]), "=f"(d[OFF + 91]), "=f"(d[OFF + 92]), "=f"(d[OFF + 93]), "=f"(d[OFF + 94]), "=f"(d[OFF + 95]), "=f"(d[OFF + 96]), "=f"(d[OFF + 97]), "=f"(d[OFF + 98]), "=f"(d[OFF + 99]), "=f"(d[OFF + 100]), "=f"(d[OFF + 101]), "=f"(d[OFF + 102]), "=f"(d[OFF + 103])
            : "r"(a0), "r"(a1), "r"(a2), "r"(a3), "l"(descB), "n"(0));
    }
};
template <int OFF, int NA> struct WG<208, OFF, true, NA> {
    static __device__ __forceinline__ void mma(float (&d)[NA], uint32_t a0, uint32_t a1, uint32_t a2, uint32_t a3, uint64_t descB) {
        asm volatile(
            "{\n"
            ".reg .pred p;\n"
            "setp.ne.b32 p, %109, 0;\n"
            "wgmma.mma_async.sync.aligned.m64n208k16.f32.bf16.bf16 "
            "{%0, %1, %2, %3, %4, %5, %6, %7, %8, %9, %10, %11, %12, %13, %14, %15, %16, %17, %18, %19, %20, %21, %22, %23, %24, %25, %26, %27, %28, %29, %30, %31, %32, %33, %34, %35, %36, %37, %38, %39, %40, %41, %42, %43, %44, %45, %46, %47, %48, %49, %50, %51, %52, %53, %54, %55, %56, %57, %58, %59, %60, %61, %62, %63, %64, %65, %66, %67, %68, %69, %70, %71, %72, %73, %74, %75, %76, %77, %78, %79, %80, %81, %82, %83, %84, %85, %86, %87, %88, %89, %90, %91, %92, %93, %94, %95, %96, %97, %98, %99, %100, %101, %102, %103}, "
            "{%104, %105, %106, %107}, %108, p, 1, 1, 0;\n"
            "}\n"
            : "+f"(d[OFF + 0]), "+f"(d[OFF + 1]), "+f"(d[OFF + 2]), "+f"(d[OFF + 3]), "+f"(d[OFF + 4]), "+f"(d[OFF + 5]), "+f"(d[OFF + 6]), "+f"(d[OFF + 7]), "+f"(d[OFF + 8]), "+f"(d[OFF + 9]), "+f"(d[OFF + 10]), "+f"(d[OFF + 11]), "+f"(d[OFF + 12]), "+f"(d[OFF + 13]), "+f"(d[OFF + 14]), "+f"(d[OFF + 15]), "+f"(d[OFF + 16]), "+f"(d[OFF + 17]), "+f"(d[OFF + 18]), "+f"(d[OFF + 19]), "+f"(d[OFF + 20]), "+f"(d[OFF + 21]), "+f"(d[OFF + 22]), "+f"(d[OFF + 23]), "+f"(d[OFF + 24]), "+f"(d[OFF + 25]), "+f"(d[OFF + 26]), "+f"(d[OFF + 27]), "+f"(d[OFF + 28]), "+f"(d[OFF + 29]), "+f"(d[OFF + 30]), "+f"(d[OFF + 31]), "+f"(d[OFF + 32]), "+f"(d[OFF + 33]), "+f"(d[OFF + 34]), "+f"(d[OFF + 35]), "+f"(d[OFF + 36]), "+f"(d[OFF + 37]), "+f"(d[OFF + 38]), "+f"(d[OFF + 39]), "+f"(d[OFF + 40]), "+f"(d[OFF + 41]), "+f"(d[OFF + 42]), "+f"(d[OFF + 43]), "+f"(d[OFF + 44]), "+f"(d[OFF + 45]), "+f"(d[OFF + 46]), "+f"(d[OFF + 47]), "+f"(d[OFF + 48]), "+f"(d[OFF + 49]), "+f"(d[OFF + 50]), "+f"(d[OFF + 51]), "+f"(d[OFF + 52]), "+f"(d[OFF + 53]), "+f"(d[OFF + 54]), "+f"(d[OFF + 55]), "+f"(d[OFF + 56]), "+f"(d[OFF + 57]), "+f"(d[OFF + 58]), "+f"(d[OFF + 59]), "+f"(d[OFF + 60]), "+f"(d[OFF + 61]), "+f"(d[OFF + 62]), "+f"(d[OFF + 63]), "+f"(d[OFF + 64]), "+f"(d[OFF + 65]), "+f"(d[OFF + 66]), "+f"(d[OFF + 67]), "+f"(d[OFF + 68]), "+f"(d[OFF + 69]), "+f"(d[OFF + 70]), "+f"(d[OFF + 71]), "+f"(d[OFF + 72]), "+f"(d[OFF + 73]), "+f"(d[OFF + 74]), "+f"(d[OFF + 75]), "+f"(d[OFF + 76]), "+f"(d[OFF + 77]), "+f"(d[OFF + 78]), "+f"(d[OFF + 79]), "+f"(d[OFF + 80]), "+f"(d[OFF + 81]), "+f"(d[OFF + 82]), "+f"(d[OFF + 83]), "+f"(d[OFF + 84]), "+f"(d[OFF + 85]), "+f"(d[OFF + 86]), "+f"(d[OFF + 87]), "+f"(d[OFF + 88]), "+f"(d[OFF + 89]), "+f"(d[OFF + 90]), "+f"(d[OFF + 91]), "+f"(d[OFF + 92]), "+f"(d[OFF + 93]), "+f"(d[OFF + 94]), "+f"(d[OFF + 95]), "+f"(d[OFF + 96]), "+f"(d[OFF + 97]), "+f"(d[OFF + 98]), "+f"(d[OFF + 99]), "+f"(d[OFF + 100]), "+f"(d[OFF + 101]), "+f"(d[OFF + 102]), "+f"(d[OFF + 103])
            : "r"(a0), "r"(a1), "r"(a2), "r"(a3), "l"(descB), "n"(1));
    }
};
template <int OFF, int NA> struct WG<120, OFF, false, NA> {
    static __device__ __forceinline__ void mma(float (&d)[NA], uint32_t a0, uint32_t a1, uint32_t a2, uint32_t a3, uint64_t descB) {
        asm volatile(
            "{\n"
            ".reg .pred p;\n"
            "setp.ne.b32 p, %65, 0;\n"
            "wgmma.mma_async.sync.aligned.m64n120k16.f32.bf16.bf16 "
            "{%0, %1, %2, %3, %4, %5, %6, %7, %8, %9, %10, %11, %12, %13, %14, %15, %16, %17, %18, %19, %20, %21, %22, %23, %24, %25, %26, %27, %28, %29, %30, %31, %32, %33, %34, %35, %36, %37, %38, %39, %40, %41, %42, %43, %44, %45, %46, %47, %48, %49, %50, %51, %52, %53, %54, %55, %56, %57, %58, %59}, "
            "{%60, %61, %62, %63}, %64, p, 1, 1, 0;\n"
            "}\n"
            : "=f"(d[OFF + 0]), "=f"(d[OFF + 1]), "=f"(d[OFF + 2]), "=f"(d[OFF + 3]), "=f"(d[OFF + 4]), "=f"(d[OFF + 5]), "=f"(d[OFF + 6]), "=f"(d[OFF + 7]), "=f"(d[OFF + 8]), "=f"(d[OFF + 9]), "=f"(d[OFF + 10]), "=f"(d[OFF + 11]), "=f"(d[OFF + 12]), "=f"(d[OFF + 13]), "=f"(d[OFF + 14]), "=f"(d[OFF + 15]), "=f"(d[OFF + 16]), "=f"(d[OFF + 17]), "=f"(d[OFF + 18]), "=f"(d[OFF + 19]), "=f"(d[OFF + 20]), "=f"(d[OFF + 21]), "=f"(d[OFF + 22]), "=f"(d[OFF + 23]), "=f"(d[OFF + 24]), "=f"(d[OFF + 25]), "=f"(d[OFF + 26]), "=f"(d[OFF + 27]), "=f"(d[OFF + 28]), "=f"(d[OFF + 29]), "=f"(d[OFF + 30]), "=f"(d[OFF + 31]), "=f"(d[OFF + 32]), "=f"(d[OFF + 33]), "=f"(d[OFF + 34]), "=f"(d[OFF + 35]), "=f"(d[OFF + 36]), "=f"(d[OFF + 37]), "=f"(d[OFF + 38]), "=f"(d[OFF + 39]), "=f"(d[OFF + 40]), "=f"(d[OFF + 41]), "=f"(d[OFF + 42]), "=f"(d[OFF + 43]), "=f"(d[OFF + 44]), "=f"(d[OFF + 45]), "=f"(d[OFF + 46]), "=f"(d[OFF + 47]), "=f"(d[OFF + 48]), "=f"(d[OFF + 49]), "=f"(d[OFF + 50]), "=f"(d[OFF + 51]), "=f"(d[OFF + 52]), "=f"(d[OFF + 53]), "=f"(d[OFF + 54]), "=f"(d[OFF + 55]), "=f"(d[OFF + 56]), "=f"(d[OFF + 57]), "=f"(d[OFF + 58]), "=f"(d[OFF + 59])
            : "r"(a0), "r"(a1), "r"(a2), "r"(a3), "l"(descB), "n"(0));
    }
};
template <int OFF, int NA> struct WG<120, OFF, true, NA> {
    static __device__ __forceinline__ void mma(float (&d)[NA], uint32_t a0, uint32_t a1, uint32_t a2, uint32_t a3, uint64_t descB) {
        asm volatile(
            "{\n"
            ".reg .pred p;\n"
            "setp.ne.b32 p, %65, 0;\n"
            "wgmma.mma_async.sync.aligned.m64n120k16.f32.bf16.bf16 "
            "{%0, %1, %2, %3, %4, %5, %6, %7, %8, %9, %10, %11, %12, %13, %14, %15, %16, %17, %18, %19, %20, %21, %22, %23, %24, %25, %26, %27, %28, %29, %30, %31, %32, %33, %34, %35, %36, %37, %38, %39, %40, %41, %42, %43, %44, %45, %46, %47, %48, %49, %50, %51, %52, %53, %54, %55, %56, %57, %58, %59}, "
            "{%60, %61, %62, %63}, %64, p, 1, 1, 0;\n"
            "}\n"
            : "+f"(d[OFF + 0]), "+f"(d[OFF + 1]), "+f"(d[OFF + 2]), "+f"(d[OFF + 3]), "+f"(d[OFF + 4]), "+f"(d[OFF + 5]), "+f"(d[OFF + 6]), "+f"(d[OFF + 7]), "+f"(d[OFF + 8]), "+f"(d[OFF + 9]), "+f"(d[OFF + 10]), "+f"(d[OFF + 11]), "+f"(d[OFF + 12]), "+f"(d[OFF + 13]), "+f"(d[OFF + 14]), "+f"(d[OFF + 15]), "+f"(d[OFF + 16]), "+f"(d[OFF + 17]), "+f"(d[OFF + 18]), "+f"(d[OFF + 19]), "+f"(d[OFF + 20]), "+f"(d[OFF + 21]), "+f"(d[OFF + 22]), "+f"(d[OFF + 23]), "+f"(d[OFF + 24]), "+f"(d[OFF + 25]), "+f"(d[OFF + 26]), "+f"(d[OFF + 27]), "+f"(d[OFF + 28]), "+f"(d[OFF + 29]), "+f"(d[OFF + 30]), "+f"(d[OFF + 31]), "+f"(d[OFF + 32]), "+f"(d[OFF + 33]), "+f"(d[OFF + 34]), "+f"(d[OFF + 35]), "+f"(d[OFF + 36]), "+f"(d[OFF + 37]), "+f"(d[OFF + 38]), "+f"(d[OFF + 39]), "+f"(d[OFF + 40]), "+f"(d[OFF + 41]), "+f"(d[OFF + 42]), "+f"(d[OFF + 43]), "+f"(d[OFF + 44]), "+f"(d[OFF + 45]), "+f"(d[OFF + 46]), "+f"(d[OFF + 47]), "+f"(d[OFF + 48]), "+f"(d[OFF + 49]), "+f"(d[OFF + 50]), "+f"(d[OFF + 51]), "+f"(d[OFF + 52]), "+f"(d[OFF + 53]), "+f"(d[OFF + 54]), "+f"(d[OFF + 55]), "+f"(d[OFF + 56]), "+f"(d[OFF + 57]), "+f"(d[OFF + 58]), "+f"(d[OFF + 59])
            : "r"(a0), "r"(a1), "r"(a2), "r"(a3), "l"(descB), "n"(1));
    }
};
template <int OFF, int NA> struct WG<112, OFF, false, NA> {
    static __device__ __forceinline__ void mma(float (&d)[NA], uint32_t a0, uint32_t a1, uint32_t a2, uint32_t a3, uint64_t descB) {
        asm volatile(
            "{\n"
            ".reg .pred p;\n"
            "setp.ne.b32 p, %61, 0;\n"
            "wgmma.mma_async.sync.aligned.m64n112k16.f32.bf16.bf16 "
            "{%0, %1, %2, %3, %4, %5, %6, %7, %8, %9, %10, %11, %12, %13, %14, %15, %16, %17, %18, %19, %20, %21, %22, %23, %24, %25, %26, %27, %28, %29, %30, %31, %32, %33, %34, %35, %36, %37, %38, %39, %40, %41, %42, %43, %44, %45, %46, %47, %48, %49, %50, %51, %52, %53, %54, %55}, "
            "{%56, %57, %58, %59}, %60, p, 1, 1, 0;\n"
            "}\n"
            : "=f"(d[OFF + 0]), "=f"(d[OFF + 1]), "=f"(d[OFF + 2]), "=f"(d[OFF + 3]), "=f"(d[OFF + 4]), "=f"(d[OFF + 5]), "=f"(d[OFF + 6]), "=f"(d[OFF + 7]), "=f"(d[OFF + 8]), "=f"(d[OFF + 9]), "=f"(d[OFF + 10]), "=f"(d[OFF + 11]), "=f"(d[OFF + 12]), "=f"(d[OFF + 13]), "=f"(d[OFF + 14]), "=f"(d[OFF + 15]), "=f"(d[OFF + 16]), "=f"(d[OFF + 17]), "=f"(d[OFF + 18]), "=f"(d[OFF + 19]), "=f"(d[OFF + 20]), "=f"(d[OFF + 21]), "=f"(d[OFF + 22]), "=f"(d[OFF + 23]), "=f"(d[OFF + 24]), "=f"(d[OFF + 25]), "=f"(d[OFF + 26]), "=f"(d[OFF + 27]), "=f"(d[OFF + 28]), "=f"(d[OFF + 29]), "=f"(d[OFF + 30]), "=f"(d[OFF + 31]), "=f"(d[OFF + 32]), "=f"(d[OFF + 33]), "=f"(d[OFF + 34]), "=f"(d[OFF + 35]), "=f"(d[OFF + 36]), "=f"(d[OFF + 37]), "=f"(d[OFF + 38]), "=f"(d[OFF + 39]), "=f"(d[OFF + 40]), "=f"(d[OFF + 41]), "=f"(d[OFF + 42]), "=f"(d[OFF + 43]), "=f"(d[OFF + 44]), "=f"(d[OFF + 45]), "=f"(d[OFF + 46]), "=f"(d[OFF + 47]), "=f"(d[OFF + 48]), "=f"(d[OFF + 49]), "=f"(d[OFF + 50]), "=f"(d[OFF + 51]), "=f"(d[OFF + 52]), "=f"(d[OFF + 53]), "=f"(d[OFF + 54]), "=f"(d[OFF + 55])
            : "r"(a0), "r"(a1), "r"(a2), "r"(a3), "l"(descB), "n"(0));
    }
};
template <int OFF, int NA> struct WG<112, OFF, true, NA> {
    static __device__ __forceinline__ void mma(float (&d)[NA], uint32_t a0, uint32_t a1, uint32_t a2, uint32_t a3, uint64_t descB) {
        asm volatile(
            "{\n"
            ".reg .pred p;\n"
            "setp.ne.b32 p, %61, 0;\n"
            "wgmma.mma_async.sync.aligned.m64n112k16.f32.bf16.bf16 "
            "{%0, %1, %2, %3, %4, %5, %6, %7, %8, %9, %10, %11, %12, %13, %14, %15, %16, %17, %18, %19, %20, %21, %22, %23, %24, %25, %26, %27, %28, %29, %30, %31, %32, %33, %34, %35, %36, %37, %38, %39, %40, %41, %42, %43, %44, %45, %46, %47, %48, %49, %50, %51, %52, %53, %54, %55}, "
            "{%56, %57, %58, %59}, %60, p, 1, 1, 0;\n"
            "}\n"
            : "+f"(d[OFF + 0]), "+f"(d[OFF + 1]), "+f"(d[OFF + 2]), "+f"(d[OFF + 3]), "+f"(d[OFF + 4]), "+f"(d[OFF + 5]), "+f"(d[OFF + 6]), "+f"(d[OFF + 7]), "+f"(d[OFF + 8]), "+f"(d[OFF + 9]), "+f"(d[OFF + 10]), "+f"(d[OFF + 11]), "+f"(d[OFF + 12]), "+f"(d[OFF + 13]), "+f"(d[OFF + 14]), "+f"(d[OFF + 15]), "+f"(d[OFF + 16]), "+f"(d[OFF + 17]), "+f"(d[OFF + 18]), "+f"(d[OFF + 19]), "+f"(d[OFF + 20]), "+f"(d[OFF + 21]), "+f"(d[OFF + 22]), "+f"(d[OFF + 23]), "+f"(d[OFF + 24]), "+f"(d[OFF + 25]), "+f"(d[OFF + 26]), "+f"(d[OFF + 27]), "+f"(d[OFF + 28]), "+f"(d[OFF + 29]), "+f"(d[OFF + 30]), "+f"(d[OFF + 31]), "+f"(d[OFF + 32]), "+f"(d[OFF + 33]), "+f"(d[OFF + 34]), "+f"(d[OFF + 35]), "+f"(d[OFF + 36]), "+f"(d[OFF + 37]), "+f"(d[OFF + 38]), "+f"(d[OFF + 39]), "+f"(d[OFF + 40]), "+f"(d[OFF + 41]), "+f"(d[OFF + 42]), "+f"(d[OFF + 43]), "+f"(d[OFF + 44]), "+f"(d[OFF + 45]), "+f"(d[OFF + 46]), "+f"(d[OFF + 47]), "+f"(d[OFF + 48]), "+f"(d[OFF + 49]), "+f"(d[OFF + 50]), "+f"(d[OFF + 51]), "+f"(d[OFF + 52]), "+f"(d[OFF + 53]), "+f"(d[OFF + 54]), "+f"(d[OFF + 55])
            : "r"(a0), "r"(a1), "r"(a2), "r"(a3), "l"(descB), "n"(1));
    }
};
template <int OFF, int NA> struct WG<96, OFF, false, NA> {
    static __device__ __forceinline__ void mma(float (&d)[NA], uint32_t a0, uint32_t a1, uint32_t a2, uint32_t a3, uint64_t descB) {
        asm volatile(
            "{\n"
            ".reg .pred p;\n"
            "setp.ne.b32 p, %53, 0;\n"
            "wgmma.mma_async.sync.aligned.m64n96k16.f32.bf16.bf16 "
            "{%0, %1, %2, %3, %4, %5, %6, %7, %8, %9, %10, %11, %12, %13, %14, %15, %16, %17, %18, %19, %20, %21, %22, %23, %24, %25, %26, %27, %28, %29, %30, %31, %32, %33, %34, %35, %36, %37, %38, %39, %40, %41, %42, %43, %44, %45, %46, %47}, "
            "{%48, %49, %50, %51}, %52, p, 1, 1, 0;\n"
            "}\n"
            : "=f"(d[OFF + 0]), "=f"(d[OFF + 1]), "=f"(d[OFF + 2]), "=f"(d[OFF + 3]), "=f"(d[OFF + 4]), "=f"(d[OFF + 5]), "=f"(d[OFF + 6]), "=f"(d[OFF + 7]), "=f"(d[OFF + 8]), "=f"(d[OFF + 9]), "=f"(d[OFF + 10]), "=f"(d[OFF + 11]), "=f"(d[OFF + 12]), "=f"(d[OFF + 13]), "=f"(d[OFF + 14]), "=f"(d[OFF + 15]), "=f"(d[OFF + 16]), "=f"(d[OFF + 17]), "=f"(d[OFF + 18]), "=f"(d[OFF + 19]), "=f"(d[OFF + 20]), "=f"(d[OFF + 21]), "=f"(d[OFF + 22]), "=f"(d[OFF + 23]), "=f"(d[OFF + 24]), "=f"(d[OFF + 25]), "=f"(d[OFF + 26]), "=f"(d[OFF + 27]), "=f"(d[OFF + 28]), "=f"(d[OFF + 29]), "=f"(d[OFF + 30]), "=f"(d[OFF + 31]), "=f"(d[OFF + 32]), "=f"(d[OFF + 33]), "=f"(d[OFF + 34]), "=f"(d[OFF + 35]), "=f"(d[OFF + 36]), "=f"(d[OFF + 37]), "=f"(d[OFF + 38]), "=f"(d[OFF + 39]), "=f"(d[OFF + 40]), "=f"(d[OFF + 41]), "=f"(d[OFF + 42]), "=f"(d[OFF + 43]), "=f"(d[OFF + 44]), "=f"(d[OFF + 45]), "=f"(d[OFF + 46]), "=f"(d[OFF + 47])
            : "r"(a0), "r"(a1), "r"(a2), "r"(a3), "l"(descB), "n"(0));
    }
};
template <int OFF, int NA> struct WG<96, OFF, true, NA> {
    static __device__ __forceinline__ void mma(float (&d)[NA], uint32_t a0, uint32_t a1, uint32_t a2, uint32_t a3, uint64_t descB) {
        asm volatile(
            "{\n"
            ".reg .pred p;\n"
            "setp.ne.b32 p, %53, 0;\n"
            "wgmma.mma_async.sync.aligned.m64n96k16.f32.bf16.bf16 "
            "{%0, %1, %2, %3, %4, %5, %6, %7, %8, %9, %10, %11, %12, %13, %14, %15, %16, %17, %18, %19, %20, %21, %22, %23, %24, %25, %26, %27, %28, %29, %30, %31, %32, %33, %34, %35, %36, %37, %38, %39, %40, %41, %42, %43, %44, %45, %46, %47}, "
            "{%48, %49, %50, %51}, %52, p, 1, 1, 0;\n"
            "}\n"
            : "+f"(d[OFF + 0]), "+f"(d[OFF + 1]), "+f"(d[OFF + 2]), "+f"(d[OFF + 3]), "+f"(d[OFF + 4]), "+f"(d[OFF + 5]), "+f"(d[OFF + 6]), "+f"(d[OFF + 7]), "+f"(d[OFF + 8]), "+f"(d[OFF + 9]), "+f"(d[OFF + 10]), "+f"(d[OFF + 11]), "+f"(d[OFF + 12]), "+f"(d[OFF + 13]), "+f"(d[OFF + 14]), "+f"(d[OFF + 15]), "+f"(d[OFF + 16]), "+f"(d[OFF + 17]), "+f"(d[OFF + 18]), "+f"(d[OFF + 19]), "+f"(d[OFF + 20]), "+f"(d[OFF + 21]), "+f"(d[OFF + 22]), "+f"(d[OFF + 23]), "+f"(d[OFF + 24]), "+f"(d[OFF + 25]), "+f"(d[OFF + 26]), "+f"(d[OFF + 27]), "+f"(d[OFF + 28]), "+f"(d[OFF + 29]), "+f"(d[OFF + 30]), "+f"(d[OFF + 31]), "+f"(d[OFF + 32]), "+f"(d[OFF + 33]), "+f"(d[OFF + 34]), "+f"(d[OFF + 35]), "+f"(d[OFF + 36]), "+f"(d[OFF + 37]), "+f"(d[OFF + 38]), "+f"(d[OFF + 39]), "+f"(d[OFF + 40]), "+f"(d[OFF + 41]), "+f"(d[OFF + 42]), "+f"(d[OFF + 43]), "+f"(d[OFF + 44]), "+f"(d[OFF + 45]), "+f"(d[OFF + 46]), "+f"(d[OFF + 47])
            : "r"(a0), "r"(a1), "r"(a2), "r"(a3), "l"(descB), "n"(1));
    }
};
template <int OFF, int NA> struct WG<64, OFF, true, NA> {
    static __device__ __forceinline__ void mma(float (&d)[NA], uint32_t a0, uint32_t a1, uint32_t a2, uint32_t a3, uint64_t descB) {
        asm volatile(
            "{\n"
            ".reg .pred p;\n"
            "setp.ne.b32 p, %37, 0;\n"
            "wgmma.mma_async.sync.aligned.m64n64k16.f32.bf16.bf16 "
            "{%0, %1, %2, %3, %4, %5, %6, %7, %8, %9, %10, %11, %12, %13, %14, %15, %16, %17, %18, %19, %20, %21, %22, %23, %24, %25, %26, %27, %28, %29, %30, %31}, "
            "{%32, %33, %34, %35}, %36, p, 1, 1, 0;\n"
            "}\n"
            : "+f"(d[OFF + 0]), "+f"(d[OFF + 1]), "+f"(d[OFF + 2]), "+f"(d[OFF + 3]), "+f"(d[OFF + 4]), "+f"(d[OFF + 5]), "+f"(d[OFF + 6]), "+f"(d[OFF + 7]), "+f"(d[OFF + 8]), "+f"(d[OFF + 9]), "+f"(d[OFF + 10]), "+f"(d[OFF + 11]), "+f"(d[OFF + 12]), "+f"(d[OFF + 13]), "+f"(d[OFF + 14]), "+f"(d[OFF + 15]), "+f"(d[OFF + 16]), "+f"(d[OFF + 17]), "+f"(d[OFF + 18]), "+f"(d[OFF + 19]), "+f"(d[OFF + 20]), "+f"(d[OFF + 21]), "+f"(d[OFF + 22]), "+f"(d[OFF + 23]), "+f"(d[OFF + 24]), "+f"(d[OFF + 25]), "+f"(d[OFF + 26]), "+f"(d[OFF + 27]), "+f"(d[OFF + 28]), "+f"(d[OFF + 29]), "+f"(d[OFF + 30]), "+f"(d[OFF + 31])
            : "r"(a0), "r"(a1), "r"(a2), "r"(a3), "l"(descB), "n"(1));
    }
};
template <int OFF, int NA> struct WG<48, OFF, true, NA> {
    static __device__ __forceinline__ void mma(float (&d)[NA], uint32_t a0, uint32_t a1, uint32_t a2, uint32_t a3, uint64_t descB) {
        asm volatile(
            "{\n"
            ".reg .pred p;\n"
            "setp.ne.b32 p, %29, 0;\n"
            "wgmma.mma_async.sync.aligned.m64n48k16.f32.bf16.bf16 "
            "{%0, %1, %2, %3, %4, %5, %6, %7, %8, %9, %10, %11, %12, %13, %14, %15, %16, %17, %18, %19, %20, %21, %22, %23}, "
            "{%24, %25, %26, %27}, %28, p, 1, 1, 0;\n"
            "}\n"
            : "+f"(d[OFF + 0]), "+f"(d[OFF + 1]), "+f"(d[OFF + 2]), "+f"(d[OFF + 3]), "+f"(d[OFF + 4]), "+f"(d[OFF + 5]), "+f"(d[OFF + 6]), "+f"(d[OFF + 7]), "+f"(d[OFF + 8]), "+f"(d[OFF + 9]), "+f"(d[OFF + 10]), "+f"(d[OFF + 11]), "+f"(d[OFF + 12]), "+f"(d[OFF + 13]), "+f"(d[OFF + 14]), "+f"(d[OFF + 15]), "+f"(d[OFF + 16]), "+f"(d[OFF + 17]), "+f"(d[OFF + 18]), "+f"(d[OFF + 19]), "+f"(d[OFF + 20]), "+f"(d[OFF + 21]), "+f"(d[OFF + 22]), "+f"(d[OFF + 23])
            : "r"(a0), "r"(a1), "r"(a2), "r"(a3), "l"(descB), "n"(1));
    }
};
template <int OFF, int NA> struct WG<32, OFF, true, NA> {
    static __device__ __forceinline__ void mma(float (&d)[NA], uint32_t a0, uint32_t a1, uint32_t a2, uint32_t a3, uint64_t descB) {
        asm volatile(
            "{\n"
            ".reg .pred p;\n"
            "setp.ne.b32 p, %21, 0;\n"
            "wgmma.mma_async.sync.aligned.m64n32k16.f32.bf16.bf16 "
            "{%0, %1, %2, %3, %4, %5, %6, %7, %8, %9, %10, %11, %12, %13, %14, %15}, "
            "{%16, %17, %18, %19}, %20, p, 1, 1, 0;\n"
            "}\n"
            : "+f"(d[OFF + 0]), "+f"(d[OFF + 1]), "+f"(d[OFF + 2]), "+f"(d[OFF + 3]), "+f"(d[OFF + 4]), "+f"(d[OFF + 5]), "+f"(d[OFF + 6]), "+f"(d[OFF + 7]), "+f"(d[OFF + 8]), "+f"(d[OFF + 9]), "+f"(d[OFF + 10]), "+f"(d[OFF + 11]), "+f"(d[OFF + 12]), "+f"(d[OFF + 13]), "+f"(d[OFF + 14]), "+f"(d[OFF + 15])
            : "r"(a0), "r"(a1), "r"(a2), "r"(a3), "l"(descB), "n"(1));
    }
};

__host__ __device__ constexpr int gate_time(int d) { return d == 0 ? DLY_POLL : DLY_P1 + (d - 1) * DLY_PS; }
__device__ __forceinline__ void unit_pos(uint32_t u, uint32_t& q, uint32_t& fg) {
    static_assert(W1_FG == 64 && W2_FG == 48, "unit order");
    const uint32_t r = u - NQ * W1_FG, q2 = (r * 1366) >> 16;
    q = u < NQ * W1_FG ? u >> 6 : q2;
    fg = u < NQ * W1_FG ? u & 63 : W1_FG + r - q2 * 48;
}
template <class T> __device__ __forceinline__ T* add_off(T* p, uint32_t bytes) {
    uint64_t r;
    asm("{\n.reg .b64 o;\ncvt.u64.u32 o, %2;\nadd.u64 %0, %1, o;\n}\n" : "=l"(r) : "l"(p), "r"(bytes));
    return (T*)r;
}
__device__ __forceinline__ uint32_t unit_src(uint32_t q, uint32_t fg) { return q * (32 * kN * 4) + fg * 128; }
__device__ __forceinline__ uint32_t lane_src(int lane) { return (lane >> 3) * (2 * kN * 4) + (lane & 7) * 16; }
__device__ __forceinline__ uint32_t unit_dst(uint32_t q, uint32_t fg) {
    return ((fg >> 2) * KSTEPS + (q >> 1)) * 8192 + (fg & 3) * 2048 + (q & 1) * 512;
}
__device__ __forceinline__ uint32_t lane_dst(int lane) { return ((lane >> 2) & 1) * 1024 + (lane & 3) * 64 + (lane >> 3) * 16; }
__device__ __forceinline__ uint32_t lane_unit(int lane) {
    return ((lane >> 3) & 1) * 256 + (((lane >> 4) ^ (lane >> 3)) & 1) * 64 + (lane & 3) * 16 + ((lane >> 2) & 1) * 8;
}
__device__ __forceinline__ constexpr int unit_row(int i) { return 16 * (i >> 2) + 8 * ((i >> 1) & 1) + (i & 1); }
__device__ __forceinline__ void load_unit(uint4 (&v)[8], const int* p) {
#pragma unroll
    for (int i = 0; i < 8; i++) v[i] = ldg_stream(p + (size_t)unit_row(i) * kN);
}
__device__ __forceinline__ uint32_t bytes4(uint32_t v0, uint32_t v1, uint32_t v2, uint32_t v3) {
    return prmt(prmt(v0, v1, 0x0040), prmt(v2, v3, 0x0040), 0x5410);
}
__device__ __forceinline__ void pk_gather(uint32_t (&e)[4], uint32_t (&o)[4], const uint4 (&v)[8]) {
    e[0] = bytes4(v[0].x, v[2].x, v[4].x, v[6].x); o[0] = bytes4(v[1].x, v[3].x, v[5].x, v[7].x);
    e[1] = bytes4(v[0].y, v[2].y, v[4].y, v[6].y); o[1] = bytes4(v[1].y, v[3].y, v[5].y, v[7].y);
    e[2] = bytes4(v[0].z, v[2].z, v[4].z, v[6].z); o[2] = bytes4(v[1].z, v[3].z, v[5].z, v[7].z);
    e[3] = bytes4(v[0].w, v[2].w, v[4].w, v[6].w); o[3] = bytes4(v[1].w, v[3].w, v[5].w, v[7].w);
}

__device__ __forceinline__ void tile0_of(int c, int& fp, int& m0) {
    const int t = c - 4, k = ((t - 32) * 37) >> 8;
    fp = t < 0 ? 0 : t < 32 ? t & 7 : t < 60 ? t - 31 - 7 * k : t - 54;
    m0 = (t < 0 ? 4 + c : t < 32 ? t >> 3 : 4 + k) * N0;
}
__device__ __forceinline__ void tile1_of(int c, int& fp, int& m0) {
    if (c < 6) { fp = c; m0 = 8 * N0; }
    else { fp = 8 + (c - 6) / 10; m0 = ((c - 6) % 10) * N1; }
}

__device__ __forceinline__ void ll_fetch(u64 (&c)[4], const char* p) {
    asm volatile("ld.relaxed.gpu.global.b64 %0, [%4];\nld.relaxed.gpu.global.b64 %1, [%4 + 128];\n"
                 "ld.relaxed.gpu.global.b64 %2, [%4 + 512];\nld.relaxed.gpu.global.b64 %3, [%4 + 640];"
                 : "=l"(c[0]), "=l"(c[1]), "=l"(c[2]), "=l"(c[3]) : "l"(p) : "memory");
}
__device__ __forceinline__ void ll_copy(uint32_t dst, const char* src, uint32_t bar) {
    asm volatile("{\n.reg .pred p;\nelect.sync _|p, 0xffffffff;\n"
                 "@p cp.async.bulk.shared::cluster.global.mbarrier::complete_tx::bytes [%0], [%1], 1024, [%2];\n}\n"
                 ::"r"(dst), "l"(src), "r"(bar) : "memory");
}
__device__ __forceinline__ void ll_read(u64 (&c)[4], uint32_t a) {
    asm volatile("ld.volatile.shared.b64 %0, [%4];\nld.volatile.shared.b64 %1, [%4 + 128];\n"
                 "ld.volatile.shared.b64 %2, [%4 + 512];\nld.volatile.shared.b64 %3, [%4 + 640];"
                 : "=l"(c[0]), "=l"(c[1]), "=l"(c[2]), "=l"(c[3]) : "r"(a) : "memory");
}
template <int OFF>
__device__ __forceinline__ void ll_check(u64 (&c)[4], uint32_t a, const char* p, uint32_t tag) {
    asm volatile(
        "{\n.reg .pred p, q;\n.reg .b32 l, h0, h1, h2, h3, x, i, o;\n.reg .b64 g;\n"
        "mov.u32 i, 0;\n"
        "L_%=:\n"
        "mov.b64 {l, h0}, %0;\nmov.b64 {l, h1}, %1;\nmov.b64 {l, h2}, %2;\nmov.b64 {l, h3}, %3;\n"
        "lop3.b32 x, %6, h0, h1, 0x7e;\n"
        "lop3.b32 x, x, %6, h2, 0xf6;\n"
        "lop3.b32 x, x, %6, h3, 0xf6;\n"
        "setp.ne.u32 p, x, 0;\n"
        "vote.sync.any.pred p, p, 0xffffffff;\n"
        "@!p bra D_%=;\n"
        "and.b32 o, %4, 1023;\ncvt.u64.u32 g, o;\nadd.u64 g, g, %5;\n"
        "sub.u32 o, %6, 16;\n"
        "setp.eq.u32 q, h0, o;\nsetp.eq.or.u32 q, h1, o, q;\nsetp.eq.or.u32 q, h2, o, q;\nsetp.eq.or.u32 q, h3, o, q;\n"
        "setp.ge.or.u32 q, i, %8, q;\n"
        "vote.sync.any.pred q, q, 0xffffffff;\n"
        "@!q ld.volatile.shared.b64 %0, [%4 + %9];\n@!q ld.volatile.shared.b64 %1, [%4 + %9 + 128];\n"
        "@!q ld.volatile.shared.b64 %2, [%4 + %9 + 512];\n@!q ld.volatile.shared.b64 %3, [%4 + %9 + 640];\n"
        "@q ld.relaxed.gpu.global.b64 %0, [g];\n@q ld.relaxed.gpu.global.b64 %1, [g + 128];\n"
        "@q ld.relaxed.gpu.global.b64 %2, [g + 512];\n@q ld.relaxed.gpu.global.b64 %3, [g + 640];\n"
        "add.u32 i, i, 1;\n"
        "setp.lt.u32 p, i, %7;\n"
        "@p bra L_%=;\n"
        "D_%=:\n}\n"
        : "+l"(c[0]), "+l"(c[1]), "+l"(c[2]), "+l"(c[3])
        : "r"(a), "l"(p), "r"(tag), "n"(SPIN_LIMIT >> 4), "n"(NSPIN), "n"(OFF) : "memory");
}
__device__ __forceinline__ void ll_poll(u64 (&c)[4], const char* p, uint32_t tag) {
    unsigned it = 0;
    while (__any_sync(0xffffffffu, (((uint32_t)(c[0] >> 32) ^ tag) | ((uint32_t)(c[1] >> 32) ^ tag) |
                                    ((uint32_t)(c[2] >> 32) ^ tag) | ((uint32_t)(c[3] >> 32) ^ tag)) != 0) &&
           ++it < (SPIN_LIMIT >> 4))
        ll_fetch(c, p);
}
__device__ __forceinline__ void decode_alu(uint32_t& r0, uint32_t& r1, uint32_t& r2, uint32_t& r3, uint32_t w,
                                           const uint32_t (&lt)[8]) {
    const uint32_t s0 = w & 0x77777777u, s1 = s0 >> 16, w4 = w * 16;
    const uint32_t m0 = prmt(w4, w, 0xd9c8), m1 = prmt(w4, w, 0xfbea);
    const uint32_t l0 = (prmt(lt[0], lt[1], s0) & ~m0) | (prmt(lt[2], lt[3], s0) & m0);
    const uint32_t h0 = (prmt(lt[4], lt[5], s0) & ~m0) | (prmt(lt[6], lt[7], s0) & m0);
    const uint32_t l1 = (prmt(lt[0], lt[1], s1) & ~m1) | (prmt(lt[2], lt[3], s1) & m1);
    const uint32_t h1 = (prmt(lt[4], lt[5], s1) & ~m1) | (prmt(lt[6], lt[7], s1) & m1);
    r0 = prmt(l0, h0, 0x5140); r1 = prmt(l0, h0, 0x7362);
    r2 = prmt(l1, h1, 0x5140); r3 = prmt(l1, h1, 0x7362);
}
template <int I0, int DI>
__device__ __forceinline__ void decode(uint32_t (&a)[16], const u64 (&c)[4], uint32_t tblv, const uint32_t (&lt)[8],
                                       const uint32_t (&mu)[4]) {
#pragma unroll
    for (int i = I0; i < 4; i += DI) {
        const int b = (i >> 1) * 8 + (i & 1);
        if (i < 4 - NALU) {
#pragma unroll
            for (int j = 0; j < 4; j++) a[b + 2 * j] = lds32(dp4a_u((uint32_t)c[i], mu[j], tblv));
        } else {
            decode_alu(a[b], a[b + 2], a[b + 4], a[b + 6], (uint32_t)c[i], lt);
        }
    }
}

__host__ __device__ constexpr int slot_of(int j) { return j < 16 ? j % 6 : (int)(0x2651032651032610ull >> (4 * (j - 16))) & 7; }
constexpr int STGA = 4, STGB = 3;
__host__ __device__ constexpr int slot_addr(int t, int s) {
    return t && (s < 2 || s == 6) ? (s == 6 ? 1 : 2 * s) * N1 * 128 : SLOT_OFF + s * SLOT_BYTES;
}
__host__ __device__ constexpr int stg_slot(int w) { return w ? STGB : STGA; }
__host__ __device__ constexpr int stg_uses(int w) {
    int n = stg_slot(w) == 4 || stg_slot(w) == 5;
    for (int i = 0; i < NSL; i++) n += slot_of(i) == stg_slot(w);
    return n;
}
__host__ __device__ constexpr bool reused(int j) {
    for (int i = j + 1; i < NSL; i++) if (slot_of(i) == slot_of(j)) return true;
    return j < 16 || slot_of(j) == STGA || slot_of(j) == STGB;
}
constexpr int STG_C0 = slot_addr(0, 6) - 2 * E0 * 128, STG_C1 = slot_addr(0, 4);
__host__ __device__ constexpr int loads_before(int j) {
    int n = 0;
    for (int i = 0; i < j; i++) n += slot_of(i) == slot_of(j);
    return n;
}
__host__ __device__ constexpr int uses_before(int j) {
    return loads_before(j) + (j >= 16 && (slot_of(j) == 4 || slot_of(j) == 5));
}
__host__ __device__ constexpr uint64_t prod_tbl(int j0) {
    uint64_t t = 0;
    for (int j = j0; j < j0 + 16; j++) t |= (uint64_t)(slot_of(j) | (((uses_before(j) + 1) & 1) << 3)) << (4 * (j - j0));
    return t;
}
__host__ __device__ constexpr uint64_t addr_tbl(int t) {
    uint64_t r = 0;
    for (int s = 0; s < NSLOTS; s++) r |= (uint64_t)(slot_addr(t, s) / 1024) << (8 * s);
    return r;
}
__host__ __device__ constexpr int dec_upto(int j) {
    return j < 14 ? j + 1 + (j >= RAMP1) + (j >= RAMP2) : j + 2 + (j >= RAMP3) + (JW == 5 && j >= RAMP4);
}
__host__ __device__ constexpr bool ramp_first(int d) {
    return d == RAMP1 + 1 || d == RAMP2 + 2 || d == RAMP3 + 2 || (JW == 5 && d == RAMP4 + 3);
}
__host__ __device__ constexpr int abuf(int j) { return JW == 5 && j >= RAMP4 + 4 ? (j == RAMP4 + 4 ? 4 : (j - 1) % 4) : j % 4; }
__host__ __device__ constexpr bool read_early(int d) {
    return d > RLATE && d < NSL && !ramp_first(d - 2) && !ramp_first(d - 3) && d != 18 && d != 20 && d != 21;
}
__host__ __device__ constexpr bool get_early(int d) { return ramp_first(d); }

__device__ __forceinline__ void fence_a(uint32_t (&a)[16]) {
#pragma unroll
    for (int i = 0; i < 16; i++) asm volatile("" : "+r"(a[i])::"memory");
}
template <int J, int N, int COL>
__device__ __forceinline__ void mma_slice(float (&acc)[N0 / 2], uint32_t (&a)[JW][16]) {
    constexpr int off = (slot_addr(J / KSTEPS, slot_of(J)) + COL * 128) / 16, b = abuf(J);
    constexpr uint64_t d0 = make_desc(SMEM_BASE);
    WG<N, COL / 2, (J % KSTEPS) != 0, N0 / 2>::mma(acc, a[b][0], a[b][1], a[b][2], a[b][3], d0 + off);
    WG<N, COL / 2, true, N0 / 2>::mma(acc, a[b][4], a[b][5], a[b][6], a[b][7], d0 + (off + 2));
    WG<N, COL / 2, true, N0 / 2>::mma(acc, a[b][8], a[b][9], a[b][10], a[b][11], d0 + (off + 4));
    WG<N, COL / 2, true, N0 / 2>::mma(acc, a[b][12], a[b][13], a[b][14], a[b][15], d0 + (off + 6));
}
template <int N> __device__ __forceinline__ void rename_acc(float (&acc)[N0 / 2]) {
#pragma unroll
    for (int i = 0; i < N / 2; i++) asm volatile("mov.b32 %0, %1;" : "=f"(acc[i]) : "f"(acc[i]) : "memory");
}
template <int N, int COL, bool FENCE>
__device__ __forceinline__ void stage_out(float (&acc)[N0 / 2], uint32_t sa, const float s0, const float s1) {
#pragma unroll
    for (int i = COL / 2; i < (COL + N) / 2; i++) asm volatile("" : "+f"(acc[i])::"memory");
#pragma unroll
    for (int j = COL / 8; j + 1 < (COL + N) / 8; j += 2) {
        const uint32_t r0 = pack_bf16x2(acc[4 * j + 0] * s0, acc[4 * j + 1] * s0);
        const uint32_t r1 = pack_bf16x2(acc[4 * j + 2] * s1, acc[4 * j + 3] * s1);
        const uint32_t r2 = pack_bf16x2(acc[4 * j + 4] * s0, acc[4 * j + 5] * s0);
        const uint32_t r3 = pack_bf16x2(acc[4 * j + 6] * s1, acc[4 * j + 7] * s1);
        asm volatile("stmatrix.sync.aligned.m8n8.x4.trans.shared.b16 [%0], {%1, %2, %3, %4};"
                     ::"r"(sa + j * 1024), "r"(r0), "r"(r1), "r"(r2), "r"(r3) : "memory");
    }
    if constexpr ((N / 8) & 1) {
        constexpr int j = (COL + N) / 8 - 1;
        const uint32_t r0 = pack_bf16x2(acc[4 * j + 0] * s0, acc[4 * j + 1] * s0);
        const uint32_t r1 = pack_bf16x2(acc[4 * j + 2] * s1, acc[4 * j + 3] * s1);
        asm volatile("stmatrix.sync.aligned.m8n8.x2.trans.shared.b16 [%0], {%1, %2};"
                     ::"r"(sa + j * 1024), "r"(r0), "r"(r1) : "memory");
    }
    if constexpr (FENCE) asm volatile("fence.proxy.async.shared::cta;" ::: "memory");
}

struct Maps { CUtensorMap m[4 + NCH]; };

__global__ void __cluster_dims__(2, 1, 1) __launch_bounds__(NUM_THREADS, 1)
nf4_gemm_kernel(const int* __restrict__ qw, u64* __restrict__ ll, unsigned* __restrict__ epoch,
                const __nv_bfloat16* __restrict__ lut, const __nv_bfloat16* __restrict__ scales,
                const __grid_constant__ Maps tm) {
    extern __shared__ __align__(1024) uint8_t smem_raw[];
    const uint32_t t_start = clock32();
    const int lane = threadIdx.x & 31;
    if (threadIdx.x < 32)
        asm volatile("prefetch.global.L2 [%0];" ::"l"(add_off(qw, unit_src(blockIdx.x / W1_FG, blockIdx.x % W1_FG) + lane * (kN * 4))) : "memory");
    const int warp = __shfl_sync(0xffffffffu, threadIdx.x >> 5, 0);
    const uint32_t sb = smem_u32(smem_raw);
    const uint32_t bar_full = sb + BAR_OFF;
    const uint32_t bar_empty = bar_full + NSLOTS * 8;
    const uint32_t bar_tbl = bar_empty + NSLOTS * 8;
    const uint32_t bar_code = bar_tbl + 8;
    const uint32_t bar_stg = bar_code + 8;

    if (warp == 1) {
        if (lane == 0) {
            for (int i = 0; i < 2 * (2 + NCH); i++) mbar_init(bar_stg + i * 8, 128);
            asm volatile("fence.mbarrier_init.release.cluster;" ::: "memory");
        }
        __syncwarp();
    }
    if (warp != 8) cluster_arrive_relaxed();
    const int crank = blockIdx.x & 1, cluster = blockIdx.x >> 1;
    if (warp < 8) {
        const int wg = warp >> 2;
        const uint32_t tagl = ld_ca_u32(epoch + lane);
        const uint32_t lv = ldg_u16(reinterpret_cast<const unsigned short*>(lut) + (lane & 15));
        int fp0, fp1, mm;
        tile0_of(cluster, fp0, mm);
        tile1_of(cluster, fp1, mm);
        const int ft0 = fp0 * 2 + crank, ft1 = fp1 * 2 + crank;
        const unsigned short* sc16 = reinterpret_cast<const unsigned short*>(scales) + warp * 16 + (lane >> 2);
        uint32_t sc0 = ldg_u16(sc16 + ft0 * FT), sc0h = ldg_u16(sc16 + ft0 * FT + 8);
        uint32_t sc1 = ldg_u16(sc16 + ft1 * FT), sc1h = ldg_u16(sc16 + ft1 * FT + 8);
        {
            constexpr int EPS = 128 / TBLC;
#pragma unroll
            for (int k = 0; k < 32 / EPS; k++) {
                const int e = warp * 32 + k * EPS + lane / (TBLC / 4);
                const uint32_t v = __shfl_sync(0xffffffffu, lv, e & 15) | (__shfl_sync(0xffffffffu, lv, e >> 4) << 16);
                asm volatile("st.shared.v4.u32 [%0], {%1, %1, %1, %1};"
                             ::"r"(sb + TBL_OFF + warp * (TBLC * 128) + k * 512 + lane * 16), "r"(v) : "memory");
            }
        }
        asm volatile("setmaxnreg.inc.sync.aligned.u32 %0;" ::"n"(CREGS));
        cluster_wait();
        mbar_arrive(bar_tbl);
        TS(132);
        sc0 |= sc0h << 16;
        sc1 |= sc1h << 16;
        const char* ll0 = keep(reinterpret_cast<const char*>(ll) + (ft0 * (KSTEPS * 8192) + warp * 1024 + lane), 0);
        const char* ll1 = keep(reinterpret_cast<const char*>(ll) + (ft1 * (KSTEPS * 8192) + warp * 1024 + lane), 0);
        const uint32_t cbuf = sb + COD_OFF + warp * 1024;
        const uint32_t tblv = keep(sb + TBL_OFF + (lane % TBLC) * 4, lane);
        const uint32_t cempty = keep(lane < 2 ? mapa(bar_empty, lane) : 0, lane);
        const uint32_t sa0 = keep(sb + (((lane >> 4) * 8 + (lane & 7)) * 128) +
                                  ((((warp & 3) * 2 + ((lane >> 3) & 1)) ^ (lane & 7)) << 4), lane);
        uint32_t lt[8];
        {
            const uint32_t p01 = __shfl_sync(0xffffffffu, lv, 4 * lane) | (__shfl_sync(0xffffffffu, lv, 4 * lane + 1) << 16);
            const uint32_t p23 = __shfl_sync(0xffffffffu, lv, 4 * lane + 2) | (__shfl_sync(0xffffffffu, lv, 4 * lane + 3) << 16);
            const uint32_t pl = prmt(p01, p23, lane & 4 ? 0x7531 : 0x6420);
#pragma unroll
            for (int i = 0; i < 8; i++) lt[i] = __shfl_sync(0xffffffffu, pl, i & 1 ? i : i + (lane & 24));
        }
        uint32_t mu[4];
#pragma unroll
        for (int j = 0; j < 4; j++) mu[j] = keep(((uint32_t)(TBLC * 4) << (8 * j)) + lane, 0);
        uint32_t a[JW][16];
        float acc[N0 / 2];

        auto src = [&](auto dc) {
            constexpr int D = decltype(dc)::value;
            return (D < KSTEPS ? ll0 : ll1) + (D % KSTEPS) * 8192;
        };
        const uint32_t tag = __shfl_sync(0xffffffffu, tagl, 0);
        u64 c[4], ch[4];
        const uint32_t aw = keep(cbuf + lane_unit(lane), lane);
        auto fetch = [&](auto dc) {
            constexpr int D = decltype(dc)::value;
            if constexpr (D < NGATE) delay_until(t_start, gate_time(D));
            if constexpr (D < NSL) ll_copy(cbuf + (D & 1) * 8192, src(dc), bar_code);
        };
        auto get = [&](auto dc) {
            constexpr int D = decltype(dc)::value;
            if constexpr (D + 1 <= FLATE) fetch(IC<D + 1>{});
            if constexpr (!read_early(D)) ll_read(c, aw + (D & 1) * 8192);
            ll_check<(D & 1) * 8192>(c, aw, src(dc), tag + D % KSTEPS);
            if constexpr (D + 2 >= NGATE) fetch(IC<D + 2>{});
        };
        auto dec = [&](auto dc) {
            constexpr int D = decltype(dc)::value;
            if constexpr (HALF && ramp_first(D - 1)) {
                decode<0, 2>(a[abuf(D)], c, tblv, lt, mu);
                ch[1] = (uint32_t)c[1]; ch[3] = (uint32_t)c[3];
            } else {
                if constexpr (HALF && ramp_first(D - 2)) decode<1, 2>(a[abuf(D - 1)], ch, tblv, lt, mu);
                decode<0, 1>(a[abuf(D)], c, tblv, lt, mu);
            }
            if constexpr (D + 2 > FLATE && D + 2 < NGATE) fetch(IC<D + 2>{});
            if constexpr (read_early(D + 1)) ll_read(c, aw + ((D + 1) & 1) * 8192);
            if constexpr (get_early(D + 1)) get(IC<D + 1>{});
        };
        auto wait_full = [&](auto jc) {
            constexpr int J = decltype(jc)::value;
            mbar_wait(bar_full + slot_of(J) * 8, loads_before(J) & 1);
        };
        auto release = [&](auto jc) {
            constexpr int J = decltype(jc)::value;
            if constexpr (reused(J)) mbar_arrive_pair(cempty + slot_of(J) * 8, cempty);
        };
        auto step = [&](auto jc) {
            constexpr int J = decltype(jc)::value, D = dec_upto(J - 1) + 1;
            fence_a(a[abuf(J)]);
            wgmma_fence();
            mma_slice<J, (J < KSTEPS ? N0 : N1), 0>(acc, a);
            wgmma_commit();
            TS(J);
            if constexpr (!get_early(D)) get(IC<D>{});
            if constexpr (J >= NEARLY) wait_full(IC<J + 1>{});
            wgmma_wait<1>();
            if constexpr (J != 0 && J != 18) release(IC<J - 1>{});
            dec(IC<D>{});
            if constexpr (dec_upto(J) > D) { get(IC<D + 1>{}); dec(IC<D + 1>{}); }
            if constexpr (J < NEARLY) wait_full(IC<J + 1>{});
        };
        static_assert(FLATE >= 1 && FLATE < NGATE && RLATE >= FLATE && RLATE < RAMP1 && RAMP1 + 2 < RAMP2 && RAMP2 < 14 &&
                      RAMP3 > 20 && RAMP3 < 28 && (!HALF || (RAMP2 < 13 && (JW == 4 ? RAMP3 < 27 : RAMP4 < 26))), "code schedule");
        static_assert(slot_of(10) == 4 && slot_of(11) == 5 && uses_before(11) == 1 && STG_C1 + 2 * E1 * 128 <= STG_C0, "staging");

        mbar_wait(bar_tbl, 0);
        TS(133);
        delay_until(t_start, gate_time(0));
        ll_fetch(c, src(IC<0>{}) + (aw & 1023));
        fetch(IC<1>{});
        ll_poll(c, src(IC<0>{}) + (aw & 1023), tag);
        dec(IC<0>{});
        TS(134);
        wait_full(IC<0>{});
        TS(137);
        static_for<0, 14>(step);
        {
            const float s0 = __uint_as_float(sc0 << 16), s1 = __uint_as_float(sc0 & 0xffff0000u);
            const uint32_t sa = sa0 + STG_C0 + wg * (E0 * 128), sc = sa0 + STG_C1 - E0 * 128 + wg * (E1 * 128);
            auto group = [&](auto jc, auto nc, auto cc) {
                fence_a(a[decltype(jc)::value % 4]);
                wgmma_fence();
                mma_slice<decltype(jc)::value, decltype(nc)::value, decltype(cc)::value>(acc, a);
                wgmma_commit();
            };
            wait_full(IC<15>{});
            TS(140);
            wgmma_wait<0>();
            rename_acc<N0>(acc);
            group(IC<14>{}, IC<E0>{}, IC<0>{});
            release(IC<13>{});
            get(IC<17>{});
            mbar_wait(bar_empty + 5 * 8, 1);
            group(IC<15>{}, IC<E0>{}, IC<0>{});
            TS(14);
            dec(IC<17>{});
            TS(141);
            group(IC<14>{}, IC<E1>{}, IC<E0>{});
            TS(15);
            wgmma_wait<1>();
            stage_out<EI, 0, false>(acc, sa, s0, s1);
            group(IC<15>{}, IC<E1>{}, IC<E0>{});
            TS(142);
            wait_full(IC<16>{});
            wgmma_wait<1>();
            release(IC<14>{});
            TS(143);
            stage_out<E0 - EI, EI, true>(acc, sa, s0, s1);
            mbar_arrive(bar_stg + wg * 8);
            TS(144);
            group(IC<16>{}, IC<S0>{}, IC<0>{});
            wait_full(IC<17>{});
            wgmma_wait<1>();
            release(IC<15>{});
            TS(16);
            stage_out<EI, E0, false>(acc, sc, s0, s1);
            group(IC<17>{}, IC<S0>{}, IC<0>{});
            TS(128);
            stage_out<E1 - EI, E0 + EI, true>(acc, sc, s0, s1);
            mbar_arrive(bar_stg + 16 + wg * 8);
            TS(129);
            group(IC<16>{}, IC<S1>{}, IC<S0>{});
            get(IC<18>{}); dec(IC<18>{});
            group(IC<17>{}, IC<S1>{}, IC<S0>{});
            TS(17);
            get(IC<19>{});
            wait_full(IC<18>{});
            wgmma_wait<1>();
            release(IC<16>{});
            dec(IC<19>{});
            TS(145);
            wgmma_wait<0>();
            rename_acc<N1>(acc);
            release(IC<17>{});
            TS(146);
        }
        static_for<18, NSL - JW>(step);
        {
            constexpr int J0 = NSL - JW;
            const float s0 = __uint_as_float(sc1 << 16), s1 = __uint_as_float(sc1 & 0xffff0000u);
            const uint32_t sa = sa0 + (wg ? slot_addr(1, STGB) : slot_addr(1, STGA));
            static_for<J0 + 1, NSL - 1>(wait_full);
            static_for<J0, NSL - 1>([&](auto jc) { fence_a(a[abuf(decltype(jc)::value)]); });
            TS(160);
            wgmma_wait<0>();
            rename_acc<N1>(acc);
            wgmma_fence();
            mma_slice<J0, chunk_n(0), 0>(acc, a);
            TS(J0);
            release(IC<J0 - 1>{});
            get(IC<NSL - 1>{}); dec(IC<NSL - 1>{});
            asm volatile("{\n.reg .pred p;\nelect.sync _|p, 0xffffffff;\n"
                         "@p mbarrier.arrive.expect_tx.shared::cta.b64 _, [%0], %1;\n}\n" ::"r"(bar_code), "n"((NSL - 1) * 1024) : "memory");
            wgmma_fence();
            static_for<J0 + 1, NSL - 1>([&](auto jc) { mma_slice<decltype(jc)::value, chunk_n(0), 0>(acc, a); });
            wait_full(IC<NSL - 1>{});
            fence_a(a[abuf(NSL - 1)]);
            wgmma_fence();
            mma_slice<NSL - 1, chunk_n(0), 0>(acc, a);
            wgmma_commit();
            static_for<1, NCH + 1>([&](auto cc) {
                constexpr int C = decltype(cc)::value;
                if constexpr (C < NCH) {
                    wgmma_fence();
                    mma_slice<J0, chunk_n(C), chunk_col(C)>(acc, a);
                    wgmma_commit();
                    if constexpr (C == 1)
                        mbar_wait(bar_empty + (wg ? STGB : STGA) * 8, (wg ? stg_uses(1) - 1 : stg_uses(0) - 1) & 1);
                    wgmma_wait<1>();
                } else {
                    wgmma_wait<0>();
                    TS(130);
                }
                stage_out<chunk_n(C - 1), chunk_col(C - 1), true>(acc, sa, s0, s1);
                mbar_arrive(bar_stg + (1 + C) * 16 + wg * 8);
                if constexpr (C < NCH) {
                    wgmma_fence();
                    static_for<J0 + 1, NSL>([&](auto jc) { mma_slice<decltype(jc)::value, chunk_n(C), chunk_col(C)>(acc, a); });
                    wgmma_commit();
                    if constexpr (C < 4) TS(J0 + C);
                }
            });
            TS(131);
        }
    } else {
      if (warp >= 9) {
        {
            const int pw = warp - 9;
            int u = pw * NUM_CTAS + blockIdx.x;
            uint32_t q = u / W1_FG, fg = u % W1_FG;
            const int* qwk = keep(add_off(qw, lane_src(lane)), lane);
            u64* llk = keep(add_off(ll, lane_dst(lane)), lane);
            const unsigned* ep = epoch + lane;
            asm volatile("setmaxnreg.dec.sync.aligned.u32 %0;" ::"n"(504 - 2 * CREGS));
            const uint32_t tag = ld_ca_u32(ep);
            if (pw > 0) delay_until(t_start, DLY_R0 + pw * DLY_R);
            uint4 v[8];
            load_unit(v, add_off(qwk, unit_src(q, fg)));
#pragma unroll 1
            for (;;) {
                u64* dst = add_off(llk, unit_dst(q, fg));
                const uint32_t sl = q >> 1;
                static_assert(RSTOP % NUM_AUX == 0, "pack rounds");
                u += u < (RSTOP - 1) * NUM_CTAS ? NUM_AUX * NUM_CTAS : pw == 2 ? NUM_UNITS : 2 * NUM_CTAS;
                unit_pos(min(u, NUM_UNITS - 1), q, fg);
                const int* p = add_off(qwk, unit_src(q, fg));
                uint32_t e[4], o[4], w[4];
                pk_gather(e, o, v);
#pragma unroll
                for (int k = 0; k < 4; k++)
                    asm("lop3.b32 %0, %1, %2, 0x0f0f0f0f, 0xe4;" : "=r"(w[k]) : "r"(e[k]), "r"(o[k] << 4));
                ll_store2(dst, w[0], w[1], tag + sl);
                ll_store2((u64*)((uint64_t)dst ^ 320), w[2], w[3], tag + sl);
                if (u >= NUM_UNITS) break;
                load_unit(v, p);
            }
        }
        const CUtensorMap* maps = keep(&tm.m[3] + lane, 0);
        named_bar_arrive<4, 128>();
        cluster_wait();
        int fp, m0;
        if (warp == 11) {
            tile0_of(cluster, fp, m0);
            const int f0 = (fp * 2 + crank) * FT;
#pragma unroll 1
            for (int ch = 0; ch < 2; ch++) {
                const uint32_t src = sb + (ch ? STG_C1 : STG_C0);
                const int rows = ch ? E1 : E0;
                int h = 0;
#pragma unroll 1
                for (unsigned it = 0; it < 16 * SPIN_LIMIT && !mbar_test(bar_stg + ch * 16 + h * 8, 0); it++) { h ^= 1; __nanosleep(20); }
#pragma unroll 1
                for (int k = 0; k < 2; k++, h ^= 1) {
                    mbar_wait(bar_stg + ch * 16 + h * 8, 0);
#pragma unroll 1
                    for (int r = 0; r < rows; r += 8) {
                        asm volatile("{\n.reg .pred p;\nelect.sync _|p, 0xffffffff;\n"
                                     "@p cp.async.bulk.tensor.2d.global.shared::cta.bulk_group [%0, {%2, %3}], [%1];\n"
                                     "cp.async.bulk.commit_group;\ncp.async.bulk.wait_group.read 1;\n}\n"
                                     ::"l"(maps), "r"(src + (h * rows + r) * 128), "r"(f0 + h * 64), "r"(m0 + ch * E0 + r)
                                     : "memory");
                    }
                }
                asm volatile("cp.async.bulk.wait_group.read 0;" ::: "memory");
                __syncwarp();
                if (lane < 2) mbar_arrive_cluster_n(mapa(bar_empty + (5 - ch) * 8, lane), 8);
                TSG(604 + ch * 2);
            }
        } else {
            const int wg = warp - 9;
            tile1_of(cluster, fp, m0);
            const int f0 = (fp * 2 + crank) * FT + wg * 64;
            const uint32_t src = sb + (wg ? slot_addr(1, STGB) : slot_addr(1, STGA));
            int r0 = 0;
#pragma unroll 1
            for (int ch = 0; ch < NCH; ch++) {
                mbar_wait(bar_stg + (2 + ch) * 16 + wg * 8, 0);
                asm volatile("{\n.reg .pred p;\nelect.sync _|p, 0xffffffff;\n"
                             "@p cp.async.bulk.tensor.2d.global.shared::cta.bulk_group [%0, {%2, %3}], [%1];\n}\n"
                             ::"l"(maps + 1 + ch), "r"(src + r0 * 128), "r"(f0), "r"(m0 + r0) : "memory");
                r0 += ((CHK >> (4 * ch)) & 15) * 8;
            }
            asm volatile("cp.async.bulk.commit_group;\ncp.async.bulk.wait_group.read 0;" ::: "memory");
            TSG(600 + wg * 2);
        }
      } else {
        asm volatile("setmaxnreg.dec.sync.aligned.u32 %0;" ::"n"(504 - 2 * CREGS));
        if ((sb & 0xFFFFFF) != SMEM_BASE) __trap();
        if (lane == 0) {
            for (int s = 0; s < NSLOTS; s++) {
                mbar_init(bar_full + s * 8, 1);
                mbar_init(bar_empty + s * 8, 16);
            }
            mbar_init(bar_tbl, 256);
            mbar_init(bar_code, 8);
            asm volatile("fence.mbarrier_init.release.cluster;" ::: "memory");
        }
        __syncwarp();
        cluster_arrive_relaxed();
        const CUtensorMap* maps = keep(&tm.m[0] + lane, 0);
        unsigned* epk = keep(epoch + lane, 0);
        if (lane == 0) prefetch_map(maps + crank);
        TSG(512);
        int fp, m0;
        tile0_of(cluster, fp, m0);
        cluster_wait();
#pragma unroll 1
        for (int t = 0; t < 2; t++) {
            const int lo = t == 0 ? 120 : 104, row = m0 + crank * lo;
            const CUtensorMap* map = maps + (t ? 2 : crank);
            const uint32_t bytes = (t ? N1 : N0) * 128, dst = sb + crank * lo * 128;
            uint64_t tbl = t ? prod_tbl(16) : prod_tbl(0);
            const uint64_t adr = t ? addr_tbl(1) : addr_tbl(0);
#pragma unroll 1
            for (int ks = 0; ks < KSTEPS; ks++, tbl >>= 4) {
                const uint32_t slot = (uint32_t)tbl & 7;
                if (t == 0 && ks > 0 && ks < 6) delay_until(t_start, DLY_X0 + ks * DLY_XS);
                mbar_wait(bar_empty + slot * 8, ((uint32_t)tbl >> 3) & 1);
                asm volatile(
                    "{\n.reg .pred p;\nelect.sync _|p, 0xffffffff;\n"
                    "@p mbarrier.arrive.expect_tx.shared::cta.b64 _, [%2], %5;\n"
                    "@p cp.async.bulk.tensor.2d.shared::cluster.global.mbarrier::complete_tx::bytes.multicast::cluster"
                    " [%0], [%1, {%3, %4}], [%2], %6;\n}\n"
                    ::"r"(dst + (((uint32_t)(adr >> (8 * slot)) & 255) << 10)), "l"(map), "r"(bar_full + slot * 8), "r"(ks * BK), "r"(row), "r"(bytes),
                    "h"((uint16_t)3) : "memory");
                TSG(514 + (t * 18 + ks) * 2);
            }
            tile1_of(cluster, fp, m0);
            if (t == 0 && lane >= 2 && lane < 4 + NCH) prefetch_map(maps + lane);
        }
        named_bar_sync<4, 128>();
        const uint32_t tag = ld_ca_u32(epk + lane);
        unsigned old = 0;
        if (lane == 0) old = atomicAdd(epk + 32, tag != 0 ? 1u : 0u);
        if (__shfl_sync(0xffffffffu, old, 0) == NUM_CTAS - 1) {
            if (lane == 0) epk[32] = 0;
            epk[lane] = tag == 0xfffffff0u ? 16 : tag + 16;
        }
        mbar_wait(bar_code, 0);
      }
    }
}

__global__ void generic_kernel(const __nv_bfloat16* __restrict__ x, const int* __restrict__ qw,
                               const __nv_bfloat16* __restrict__ lut, const __nv_bfloat16* __restrict__ scales,
                               __nv_bfloat16* __restrict__ out, int M, int N, int K, int G) {
    const int n = blockIdx.x * blockDim.x + threadIdx.x;
    const int m = blockIdx.y;
    if (n >= N) return;
    float acc = 0.f;
    for (int k = 0; k < K; k++) {
        const float l = __bfloat162float(lut[qw[(size_t)k * N + n] & 15]);
        const float s = __bfloat162float(scales[(size_t)(k / G) * N + n]);
        const float w = __bfloat162float(__float2bfloat16_rn(l * s));
        acc += __bfloat162float(x[(size_t)m * K + k]) * w;
    }
    out[(size_t)m * N + n] = __float2bfloat16_rn(acc);
}

typedef CUresult (*PFN_encodeTiled)(CUtensorMap*, CUtensorMapDataType, cuuint32_t, void*, const cuuint64_t*,
                                    const cuuint64_t*, const cuuint32_t*, const cuuint32_t*, CUtensorMapInterleave,
                                    CUtensorMapSwizzle, CUtensorMapL2promotion, CUtensorMapFloatOOBfill);

bool make_map_2d(PFN_encodeTiled fn, CUtensorMap* map, void* base, uint64_t inner, uint64_t outer, uint32_t box_inner,
                 uint32_t box_outer) {
    cuuint64_t dims[2] = {inner, outer};
    cuuint64_t strides[1] = {inner * 2};
    cuuint32_t box[2] = {box_inner, box_outer};
    cuuint32_t estr[2] = {1, 1};
    return fn(map, CU_TENSOR_MAP_DATA_TYPE_BFLOAT16, 2, base, dims, strides, box, estr, CU_TENSOR_MAP_INTERLEAVE_NONE,
              CU_TENSOR_MAP_SWIZZLE_128B, CU_TENSOR_MAP_L2_PROMOTION_L2_128B,
              CU_TENSOR_MAP_FLOAT_OOB_FILL_NONE) == CUDA_SUCCESS;
}

}

extern "C" void kernel_launch(void* const* d_in, const int* in_sizes, int n_in, void* d_out, int out_size) {
    const __nv_bfloat16* x = (const __nv_bfloat16*)d_in[0];
    const int* qw = (const int*)d_in[1];
    const __nv_bfloat16* lut = (const __nv_bfloat16*)d_in[2];
    const __nv_bfloat16* scales = (const __nv_bfloat16*)d_in[3];
    __nv_bfloat16* out = (__nv_bfloat16*)d_out;

    const double Kd = sqrt((double)in_sizes[0] * (double)in_sizes[1] / (double)out_size);
    const int K = (int)(Kd + 0.5);
    const int M = in_sizes[0] / K, N = in_sizes[1] / K;
    const int ng = in_sizes[3] / N;
    const int G = K / ng;

    bool fast = (M == kM && N == kN && K == kK && ng == 1 && in_sizes[2] >= 16);
    PFN_encodeTiled enc = nullptr;
    Maps tm;
    void *ll = nullptr, *epoch = nullptr;
    if (fast) {
        cudaDriverEntryPointQueryResult qres;
        void* fp = nullptr;
        if (cudaGetDriverEntryPoint("cuTensorMapEncodeTiled", &fp, cudaEnableDefault, &qres) != cudaSuccess || !fp) fast = false;
        enc = (PFN_encodeTiled)fp;
    }
    if (fast) {
        fast = make_map_2d(enc, &tm.m[0], (void*)x, kK, kM, BK, 120) &&
               make_map_2d(enc, &tm.m[1], (void*)x, kK, kM, BK, 112) &&
               make_map_2d(enc, &tm.m[2], (void*)x, kK, kM, BK, 104) &&
               make_map_2d(enc, &tm.m[3], (void*)out, kN, kM, 64, 8) &&
               cudaGetSymbolAddress(&ll, g_ll) == cudaSuccess && cudaGetSymbolAddress(&epoch, g_epoch) == cudaSuccess;
    }
    for (int c = 0; c < NCH && fast; c++) fast = make_map_2d(enc, &tm.m[4 + c], (void*)out, kN, kM, 64, chunk_n(c));
    cudaLaunchConfig_t cfg = {};
    cfg.gridDim = dim3(NUM_CTAS);
    cfg.blockDim = dim3(NUM_THREADS);
    cfg.dynamicSmemBytes = SMEM_TOTAL;
    cfg.stream = cudaStreamPerThread;
    if (fast) {
        int nclusters = 0;
        fast = cudaFuncSetAttribute(nf4_gemm_kernel, cudaFuncAttributeMaxDynamicSharedMemorySize, SMEM_TOTAL) == cudaSuccess &&
               cudaOccupancyMaxActiveClusters(&nclusters, nf4_gemm_kernel, &cfg) == cudaSuccess &&
               nclusters >= NUM_CTAS / 2;
    }
    if (!fast) {
        generic_kernel<<<dim3((N + 127) / 128, M), 128>>>(x, qw, lut, scales, out, M, N, K, G);
        return;
    }
    cudaLaunchKernelEx(&cfg, nf4_gemm_kernel, qw, (u64*)ll, (unsigned*)epoch, lut, scales, tm);
}
```

```cpp
#include <cuda_runtime.h>
#include <cuda_bf16.h>
#include <cuda.h>
#include <stdint.h>
#include <stdio.h>
#include <math.h>

namespace {

constexpr int kM = 2048, kN = 3584, kK = 1024;
constexpr int FT = 128;
constexpr int N0 = 232, N1 = 208;
constexpr int BK = 64, KSTEPS = kK / BK;
constexpr int NSL = 2 * KSTEPS;
constexpr int NSLOTS = 7;
constexpr int SLOT_BYTES = N0 * 128;
constexpr int SLOT_OFF = 3 * N1 * 128 - 2 * SLOT_BYTES;
constexpr int TBLC = 16;
constexpr int TBL_OFF = SLOT_OFF + 6 * SLOT_BYTES;
constexpr int COD_OFF = TBL_OFF + TBLC * 1024;
constexpr int BAR_OFF = COD_OFF + 2 * 8192;
constexpr int SMEM_TOTAL = BAR_OFF + 256;
constexpr int NUM_THREADS = 384;
constexpr int NUM_CTAS = 132;
constexpr int NUM_AUX = 3;
constexpr int CREGS = 224;
constexpr int NQ = kK / 32, NUM_UNITS = NQ * (kN / 32);
constexpr int W1_FG = 64, W2_FG = kN / 32 - W1_FG;
constexpr int DLY_R0 = 200;
constexpr int DLY_R = 400;
constexpr int DLY_X0 = 1000;
constexpr int DLY_XS = 900;
constexpr int DLY_POLL = 2600;
constexpr int DLY_P1 = 3250;
constexpr int DLY_PS = 700;
constexpr int NGATE = 8;
constexpr int FLATE = 3;
constexpr int RLATE = 4;
constexpr int NEARLY = 4;
constexpr int RAMP1 = 9;
constexpr int RAMP2 = 12;
constexpr int RAMP3 = 22;
constexpr int NSPIN = 24;
constexpr int NALU = 2;
constexpr int RSTOP = 18;
constexpr int JW = 5;
constexpr int RAMP4 = 25;
constexpr int HALF = 1;
constexpr int EI = 64;
constexpr int E0 = 120, E1 = N0 - E0, S0 = 112, S1 = N1 - S0;
constexpr int CHK = 0x4688;
__host__ __device__ constexpr int chunk_n(int c) { return ((CHK >> (4 * c)) & 15) * 8; }
__host__ __device__ constexpr int chunk_col(int c) { return c ? chunk_col(c - 1) + chunk_n(c - 1) : 0; }
constexpr int NCH = CHK > 0xfffff ? 6 : CHK > 0xffff ? 5 : CHK > 0xfff ? 4 : 3;
static_assert(chunk_col(NCH) == N1 && S0 <= E0, "chunks");
constexpr unsigned SPIN_LIMIT = 1u << 20;

__device__ __align__(1024) unsigned long long g_ll[(size_t)(kN / FT) * NQ * FT * 4];
__device__ __align__(256) unsigned int g_epoch[64] = {16, 16, 16, 16, 16, 16, 16, 16, 16, 16, 16, 16, 16, 16, 16, 16,
                                                      16, 16, 16, 16, 16, 16, 16, 16, 16, 16, 16, 16, 16, 16, 16, 16};

template <int I> struct IC { static constexpr int value = I; };
template <int B, int E, class F> __device__ __forceinline__ void static_for(F&& f) {
    if constexpr (B < E) { f(IC<B>{}); static_for<B + 1, E>(f); }
}

__device__ __forceinline__ uint32_t smem_u32(const void* p) { return (uint32_t)__cvta_generic_to_shared(p); }
__device__ __forceinline__ uint32_t keep(uint32_t v, int lane) {
    asm volatile("shfl.sync.idx.b32 %0, %0, %1, 0x1f, 0xffffffff;" : "+r"(v) : "r"(lane));
    return v;
}
template <class T> __device__ __forceinline__ T* keep(T* p, int lane) {
    const uint64_t v = (uint64_t)p;
    return (T*)(((uint64_t)keep((uint32_t)(v >> 32), lane) << 32) | keep((uint32_t)v, lane));
}
__device__ __forceinline__ void mbar_init(uint32_t bar, uint32_t count) {
    asm volatile("mbarrier.init.shared::cta.b64 [%0], %1;" ::"r"(bar), "r"(count) : "memory");
}
__device__ __forceinline__ uint32_t clock32() { uint64_t c; asm volatile("mov.u64 %0, %%clock64;" : "=l"(c)); return (uint32_t)c; }
__device__ __forceinline__ void mbar_arrive(uint32_t bar) {
    asm volatile("mbarrier.arrive.shared::cta.b64 _, [%0];" ::"r"(bar) : "memory");
}
__device__ __forceinline__ uint32_t mapa(uint32_t a, uint32_t rank) {
    uint32_t r;
    asm("mapa.shared::cluster.u32 %0, %1, %2;" : "=r"(r) : "r"(a), "r"(rank));
    return r;
}
__device__ __forceinline__ void mbar_arrive_pair(uint32_t cbar, uint32_t base) {
    asm volatile("{\n.reg .pred p;\nsetp.ne.u32 p, %1, 0;\n@p mbarrier.arrive.shared::cluster.b64 _, [%0];\n}\n"
                 ::"r"(cbar), "r"(base) : "memory");
}
__device__ __forceinline__ void mbar_arrive_cluster_n(uint32_t cbar, uint32_t n) {
    asm volatile("mbarrier.arrive.shared::cluster.b64 _, [%0], %1;" ::"r"(cbar), "r"(n) : "memory");
}
__device__ __forceinline__ void delay_until(uint32_t t0, int clks) {
    while (__any_sync(0xffffffffu, (int)(clock32() - t0) < clks)) {}
}
__device__ __forceinline__ bool mbar_test(uint32_t bar, uint32_t parity) {
    uint32_t ok;
    asm volatile("{\n.reg .pred p;\nmbarrier.test_wait.parity.shared::cta.b64 p, [%1], %2;\nvote.sync.all.pred p, p, 0xffffffff;\nselp.u32 %0, 1, 0, p;\n}\n"
                 : "=r"(ok) : "r"(bar), "r"(parity) : "memory");
    return ok != 0;
}
__device__ __forceinline__ void mbar_wait(uint32_t bar, uint32_t parity) {
    asm volatile(
        "{\n.reg .pred p;\n.reg .u32 i;\n"
        "mbarrier.try_wait.parity.shared::cta.b64 p, [%0], %1;\n"
        "@p bra D_%=;\n"
        "mov.u32 i, 0;\n"
        "L_%=:\n"
        "mbarrier.try_wait.parity.shared::cta.b64 p, [%0], %1;\n"
        "@p bra D_%=;\n"
        "add.u32 i, i, 1;\n"
        "setp.lt.u32 p, i, %2;\n"
        "@p bra L_%=;\n"
        "D_%=:\n}\n"
        ::"r"(bar), "r"(parity), "n"(SPIN_LIMIT) : "memory");
}
__device__ __forceinline__ void prefetch_map(const CUtensorMap* map) {
    asm volatile("prefetch.tensormap [%0];" ::"l"(map) : "memory");
}
constexpr uint32_t SMEM_BASE = 1024;
__host__ __device__ constexpr uint64_t make_desc(uint32_t saddr) {
    return (uint64_t)((saddr & 0x3FFFF) >> 4) | ((uint64_t)1 << 16) | ((uint64_t)(1024 >> 4) << 32) | ((uint64_t)1 << 62);
}
__device__ __forceinline__ void wgmma_fence() { asm volatile("wgmma.fence.sync.aligned;" ::: "memory"); }
__device__ __forceinline__ void wgmma_commit() { asm volatile("wgmma.commit_group.sync.aligned;" ::: "memory"); }
template <int N> __device__ __forceinline__ void wgmma_wait() {
    asm volatile("wgmma.wait_group.sync.aligned %0;" ::"n"(N) : "memory");
}
__device__ __forceinline__ uint32_t pack_bf16x2(float lo, float hi) {
    uint32_t r;
    asm("cvt.rn.bf16x2.f32 %0, %1, %2;" : "=r"(r) : "f"(hi), "f"(lo));
    return r;
}
__device__ __forceinline__ uint32_t lds32(uint32_t addr) {
    uint32_t v;
    asm("ld.shared.u32 %0, [%1];" : "=r"(v) : "r"(addr));
    return v;
}
__device__ __forceinline__ uint32_t dp4a_u(uint32_t a, uint32_t b, uint32_t c) {
    uint32_t d;
    asm("dp4a.u32.u32 %0, %1, %2, %3;" : "=r"(d) : "r"(a), "r"(b), "r"(c));
    return d;
}
__device__ __forceinline__ uint32_t prmt(uint32_t a, uint32_t b, uint32_t s) {
    uint32_t d;
    asm("prmt.b32 %0, %1, %2, %3;" : "=r"(d) : "r"(a), "r"(b), "r"(s));
    return d;
}
template <int ID, int NT> __device__ __forceinline__ void named_bar_sync() {
    asm volatile("bar.sync %0, %1;" ::"n"(ID), "n"(NT) : "memory");
}
template <int ID, int NT> __device__ __forceinline__ void named_bar_arrive() {
    asm volatile("bar.arrive %0, %1;" ::"n"(ID), "n"(NT) : "memory");
}
__device__ __forceinline__ void cluster_arrive_relaxed() { asm volatile("barrier.cluster.arrive.relaxed.aligned;" ::: "memory"); }
__device__ __forceinline__ void cluster_wait() { asm volatile("barrier.cluster.wait.acquire.aligned;" ::: "memory"); }
__device__ __forceinline__ uint4 ldg_stream(const int* p) {
    uint4 v;
    asm volatile("ld.global.L1::no_allocate.L2::128B.v4.u32 {%0, %1, %2, %3}, [%4];"
                 : "=r"(v.x), "=r"(v.y), "=r"(v.z), "=r"(v.w) : "l"(p));
    return v;
}
__device__ __forceinline__ uint32_t ldg_u16(const unsigned short* p) {
    uint32_t v;
    asm volatile("ld.global.nc.u16 %0, [%1];" : "=r"(v) : "l"(p));
    return v;
}
__device__ __forceinline__ unsigned ld_ca_u32(const unsigned* p) {
    unsigned v;
    asm volatile("ld.global.ca.u32 %0, [%1];" : "=r"(v) : "l"(p) : "memory");
    return v;
}
typedef unsigned long long u64;
__device__ __forceinline__ void ll_store2(u64* p, uint32_t w0, uint32_t w1, uint32_t tag) {
    asm volatile("{\n.reg .b64 a, b;\nmov.b64 a, {%1, %3};\nmov.b64 b, {%2, %3};\n"
                 "st.relaxed.gpu.global.v2.b64 [%0], {a, b};\n}\n" ::"l"(p), "r"(w0), "r"(w1), "r"(tag) : "memory");
}

template <int N, int OFF, bool ACC, int NA> struct WG;
template <int OFF, int NA> struct WG<232, OFF, false, NA> {
    static __device__ __forceinline__ void mma(float (&d)[NA], uint32_t a0, uint32_t a1, uint32_t a2, uint32_t a3, uint64_t descB) {
        asm volatile(
            "{\n"
            ".reg .pred p;\n"
            "setp.ne.b32 p, %121, 0;\n"
            "wgmma.mma_async.sync.aligned.m64n232k16.f32.bf16.bf16 "
            "{%0, %1, %2, %3, %4, %5, %6, %7, %8, %9, %10, %11, %12, %13, %14, %15, %16, %17, %18, %19, %20, %21, %22, %23, %24, %25, %26, %27, %28, %29, %30, %31, %32, %33, %34, %35, %36, %37, %38, %39, %40, %41, %42, %43, %44, %45, %46, %47, %48, %49, %50, %51, %52, %53, %54, %55, %56, %57, %58, %59, %60, %61, %62, %63, %64, %65, %66, %67, %68, %69, %70, %71, %72, %73, %74, %75, %76, %77, %78, %79, %80, %81, %82, %83, %84, %85, %86, %87, %88, %89, %90, %91, %92, %93, %94, %95, %96, %97, %98, %99, %100, %101, %102, %103, %104, %105, %106, %107, %108, %109, %110, %111, %112, %113, %114, %115}, "
            "{%116, %117, %118, %119}, %120, p, 1, 1, 0;\n"
            "}\n"
            : "=f"(d[OFF + 0]), "=f"(d[OFF + 1]), "=f"(d[OFF + 2]), "=f"(d[OFF + 3]), "=f"(d[OFF + 4]), "=f"(d[OFF + 5]), "=f"(d[OFF + 6]), "=f"(d[OFF + 7]), "=f"(d[OFF + 8]), "=f"(d[OFF + 9]), "=f"(d[OFF + 10]), "=f"(d[OFF + 11]), "=f"(d[OFF + 12]), "=f"(d[OFF + 13]), "=f"(d[OFF + 14]), "=f"(d[OFF + 15]), "=f"(d[OFF + 16]), "=f"(d[OFF + 17]), "=f"(d[OFF + 18]), "=f"(d[OFF + 19]), "=f"(d[OFF + 20]), "=f"(d[OFF + 21]), "=f"(d[OFF + 22]), "=f"(d[OFF + 23]), "=f"(d[OFF + 24]), "=f"(d[OFF + 25]), "=f"(d[OFF + 26]), "=f"(d[OFF + 27]), "=f"(d[OFF + 28]), "=f"(d[OFF + 29]), "=f"(d[OFF + 30]), "=f"(d[OFF + 31]), "=f"(d[OFF + 32]), "=f"(d[OFF + 33]), "=f"(d[OFF + 34]), "=f"(d[OFF + 35]), "=f"(d[OFF + 36]), "=f"(d[OFF + 37]), "=f"(d[OFF + 38]), "=f"(d[OFF + 39]), "=f"(d[OFF + 40]), "=f"(d[OFF + 41]), "=f"(d[OFF + 42]), "=f"(d[OFF + 43]), "=f"(d[OFF + 44]), "=f"(d[OFF + 45]), "=f"(d[OFF + 46]), "=f"(d[OFF + 47]), "=f"(d[OFF + 48]), "=f"(d[OFF + 49]), "=f"(d[OFF + 50]), "=f"(d[OFF + 51]), "=f"(d[OFF + 52]), "=f"(d[OFF + 53]), "=f"(d[OFF + 54]), "=f"(d[OFF + 55]), "=f"(d[OFF + 56]), "=f"(d[OFF + 57]), "=f"(d[OFF + 58]), "=f"(d[OFF + 59]), "=f"(d[OFF + 60]), "=f"(d[OFF + 61]), "=f"(d[OFF + 62]), "=f"(d[OFF + 63]), "=f"(d[OFF + 64]), "=f"(d[OFF + 65]), "=f"(d[OFF + 66]), "=f"(d[OFF + 67]), "=f"(d[OFF + 68]), "=f"(d[OFF + 69]), "=f"(d[OFF + 70]), "=f"(d[OFF + 71]), "=f"(d[OFF + 72]), "=f"(d[OFF + 73]), "=f"(d[OFF + 74]), "=f"(d[OFF + 75]), "=f"(d[OFF + 76]), "=f"(d[OFF + 77]), "=f"(d[OFF + 78]), "=f"(d[OFF + 79]), "=f"(d[OFF + 80]), "=f"(d[OFF + 81]), "=f"(d[OFF + 82]), "=f"(d[OFF + 83]), "=f"(d[OFF + 84]), "=f"(d[OFF + 85]), "=f"(d[OFF + 86]), "=f"(d[OFF + 87]), "=f"(d[OFF + 88]), "=f"(d[OFF + 89]), "=f"(d[OFF + 90]), "=f"(d[OFF + 91]), "=f"(d[OFF + 92]), "=f"(d[OFF + 93]), "=f"(d[OFF + 94]), "=f"(d[OFF + 95]), "=f"(d[OFF + 96]), "=f"(d[OFF + 97]), "=f"(d[OFF + 98]), "=f"(d[OFF + 99]), "=f"(d[OFF + 100]), "=f"(d[OFF + 101]), "=f"(d[OFF + 102]), "=f"(d[OFF + 103]), "=f"(d[OFF + 104]), "=f"(d[OFF + 105]), "=f"(d[OFF + 106]), "=f"(d[OFF + 107]), "=f"(d[OFF + 108]), "=f"(d[OFF + 109]), "=f"(d[OFF + 110]), "=f"(d[OFF + 111]), "=f"(d[OFF + 112]), "=f"(d[OFF + 113]), "=f"(d[OFF + 114]), "=f"(d[OFF + 115])
            : "r"(a0), "r"(a1), "r"(a2), "r"(a3), "l"(descB), "n"(0));
    }
};
template <int OFF, int NA> struct WG<232, OFF, true, NA> {
    static __device__ __forceinline__ void mma(float (&d)[NA], uint32_t a0, uint32_t a1, uint32_t a2, uint32_t a3, uint64_t descB) {
        asm volatile(
            "{\n"
            ".reg .pred p;\n"
            "setp.ne.b32 p, %121, 0;\n"
            "wgmma.mma_async.sync.aligned.m64n232k16.f32.bf16.bf16 "
            "{%0, %1, %2, %3, %4, %5, %6, %7, %8, %9, %10, %11, %12, %13, %14, %15, %16, %17, %18, %19, %20, %21, %22, %23, %24, %25, %26, %27, %28, %29, %30, %31, %32, %33, %34, %35, %36, %37, %38, %39, %40, %41, %42, %43, %44, %45, %46, %47, %48, %49, %50, %51, %52, %53, %54, %55, %56, %57, %58, %59, %60, %61, %62, %63, %64, %65, %66, %67, %68, %69, %70, %71, %72, %73, %74, %75, %76, %77, %78, %79, %80, %81, %82, %83, %84, %85, %86, %87, %88, %89, %90, %91, %92, %93, %94, %95, %96, %97, %98, %99, %100, %101, %102, %103, %104, %105, %106, %107, %108, %109, %110, %111, %112, %113, %114, %115}, "
            "{%116, %117, %118, %119}, %120, p, 1, 1, 0;\n"
            "}\n"
            : "+f"(d[OFF + 0]), "+f"(d[OFF + 1]), "+f"(d[OFF + 2]), "+f"(d[OFF + 3]), "+f"(d[OFF + 4]), "+f"(d[OFF + 5]), "+f"(d[OFF + 6]), "+f"(d[OFF + 7]), "+f"(d[OFF + 8]), "+f"(d[OFF + 9]), "+f"(d[OFF + 10]), "+f"(d[OFF + 11]), "+f"(d[OFF + 12]), "+f"(d[OFF + 13]), "+f"(d[OFF + 14]), "+f"(d[OFF + 15]), "+f"(d[OFF + 16]), "+f"(d[OFF + 17]), "+f"(d[OFF + 18]), "+f"(d[OFF + 19]), "+f"(d[OFF + 20]), "+f"(d[OFF + 21]), "+f"(d[OFF + 22]), "+f"(d[OFF + 23]), "+f"(d[OFF + 24]), "+f"(d[OFF + 25]), "+f"(d[OFF + 26]), "+f"(d[OFF + 27]), "+f"(d[OFF + 28]), "+f"(d[OFF + 29]), "+f"(d[OFF + 30]), "+f"(d[OFF + 31]), "+f"(d[OFF + 32]), "+f"(d[OFF + 33]), "+f"(d[OFF + 34]), "+f"(d[OFF + 35]), "+f"(d[OFF + 36]), "+f"(d[OFF + 37]), "+f"(d[OFF + 38]), "+f"(d[OFF + 39]), "+f"(d[OFF + 40]), "+f"(d[OFF + 41]), "+f"(d[OFF + 42]), "+f"(d[OFF + 43]), "+f"(d[OFF + 44]), "+f"(d[OFF + 45]), "+f"(d[OFF + 46]), "+f"(d[OFF + 47]), "+f"(d[OFF + 48]), "+f"(d[OFF + 49]), "+f"(d[OFF + 50]), "+f"(d[OFF + 51]), "+f"(d[OFF + 52]), "+f"(d[OFF + 53]), "+f"(d[OFF + 54]), "+f"(d[OFF + 55]), "+f"(d[OFF + 56]), "+f"(d[OFF + 57]), "+f"(d[OFF + 58]), "+f"(d[OFF + 59]), "+f"(d[OFF + 60]), "+f"(d[OFF + 61]), "+f"(d[OFF + 62]), "+f"(d[OFF + 63]), "+f"(d[OFF + 64]), "+f"(d[OFF + 65]), "+f"(d[OFF + 66]), "+f"(d[OFF + 67]), "+f"(d[OFF + 68]), "+f"(d[OFF + 69]), "+f"(d[OFF + 70]), "+f"(d[OFF + 71]), "+f"(d[OFF + 72]), "+f"(d[OFF + 73]), "+f"(d[OFF + 74]), "+f"(d[OFF + 75]), "+f"(d[OFF + 76]), "+f"(d[OFF + 77]), "+f"(d[OFF + 78]), "+f"(d[OFF + 79]), "+f"(d[OFF + 80]), "+f"(d[OFF + 81]), "+f"(d[OFF + 82]), "+f"(d[OFF + 83]), "+f"(d[OFF + 84]), "+f"(d[OFF + 85]), "+f"(d[OFF + 86]), "+f"(d[OFF + 87]), "+f"(d[OFF + 88]), "+f"(d[OFF + 89]), "+f"(d[OFF + 90]), "+f"(d[OFF + 91]), "+f"(d[OFF + 92]), "+f"(d[OFF + 93]), "+f"(d[OFF + 94]), "+f"(d[OFF + 95]), "+f"(d[OFF + 96]), "+f"(d[OFF + 97]), "+f"(d[OFF + 98]), "+f"(d[OFF + 99]), "+f"(d[OFF + 100]), "+f"(d[OFF + 101]), "+f"(d[OFF + 102]), "+f"(d[OFF + 103]), "+f"(d[OFF + 104]), "+f"(d[OFF + 105]), "+f"(d[OFF + 106]), "+f"(d[OFF + 107]), "+f"(d[OFF + 108]), "+f"(d[OFF + 109]), "+f"(d[OFF + 110]), "+f"(d[OFF + 111]), "+f"(d[OFF + 112]), "+f"(d[OFF + 113]), "+f"(d[OFF + 114]), "+f"(d[OFF + 115])
            : "r"(a0), "r"(a1), "r"(a2), "r"(a3), "l"(descB), "n"(1));
    }
};
template <int OFF, int NA> struct WG<208, OFF, false, NA> {
    static __device__ __forceinline__ void mma(float (&d)[NA], uint32_t a0, uint32_t a1, uint32_t a2, uint32_t a3, uint64_t descB) {
        asm volatile(
            "{\n"
            ".reg .pred p;\n"
            "setp.ne.b32 p, %109, 0;\n"
            "wgmma.mma_async.sync.aligned.m64n208k16.f32.bf16.bf16 "
            "{%0, %1, %2, %3, %4, %5, %6, %7, %8, %9, %10, %11, %12, %13, %14, %15, %16, %17, %18, %19, %20, %21, %22, %23, %24, %25, %26, %27, %28, %29, %30, %31, %32, %33, %34, %35, %36, %37, %38, %39, %40, %41, %42, %43, %44, %45, %46, %47, %48, %49, %50, %51, %52, %53, %54, %55, %56, %57, %58, %59, %60, %61, %62, %63, %64, %65, %66, %67, %68, %69, %70, %71, %72, %73, %74, %75, %76, %77, %78, %79, %80, %81, %82, %83, %84, %85, %86, %87, %88, %89, %90, %91, %92, %93, %94, %95, %96, %97, %98, %99, %100, %101, %102, %103}, "
            "{%104, %105, %106, %107}, %108, p, 1, 1, 0;\n"
            "}\n"
            : "=f"(d[OFF + 0]), "=f"(d[OFF + 1]), "=f"(d[OFF + 2]), "=f"(d[OFF + 3]), "=f"(d[OFF + 4]), "=f"(d[OFF + 5]), "=f"(d[OFF + 6]), "=f"(d[OFF + 7]), "=f"(d[OFF + 8]), "=f"(d[OFF + 9]), "=f"(d[OFF + 10]), "=f"(d[OFF + 11]), "=f"(d[OFF + 12]), "=f"(d[OFF + 13]), "=f"(d[OFF + 14]), "=f"(d[OFF + 15]), "=f"(d[OFF + 16]), "=f"(d[OFF + 17]), "=f"(d[OFF + 18]), "=f"(d[OFF + 19]), "=f"(d[OFF + 20]), "=f"(d[OFF + 21]), "=f"(d[OFF + 22]), "=f"(d[OFF + 23]), "=f"(d[OFF + 24]), "=f"(d[OFF + 25]), "=f"(d[OFF + 26]), "=f"(d[OFF + 27]), "=f"(d[OFF + 28]), "=f"(d[OFF + 29]), "=f"(d[OFF + 30]), "=f"(d[OFF + 31]), "=f"(d[OFF + 32]), "=f"(d[OFF + 33]), "=f"(d[OFF + 34]), "=f"(d[OFF + 35]), "=f"(d[OFF + 36]), "=f"(d[OFF + 37]), "=f"(d[OFF + 38]), "=f"(d[OFF + 39]), "=f"(d[OFF + 40]), "=f"(d[OFF + 41]), "=f"(d[OFF + 42]), "=f"(d[OFF + 43]), "=f"(d[OFF + 44]), "=f"(d[OFF + 45]), "=f"(d[OFF + 46]), "=f"(d[OFF + 47]), "=f"(d[OFF + 48]), "=f"(d[OFF + 49]), "=f"(d[OFF + 50]), "=f"(d[OFF + 51]), "=f"(d[OFF + 52]), "=f"(d[OFF + 53]), "=f"(d[OFF + 54]), "=f"(d[OFF + 55]), "=f"(d[OFF + 56]), "=f"(d[OFF + 57]), "=f"(d[OFF + 58]), "=f"(d[OFF + 59]), "=f"(d[OFF + 60]), "=f"(d[OFF + 61]), "=f"(d[OFF + 62]), "=f"(d[OFF + 63]), "=f"(d[OFF + 64]), "=f"(d[OFF + 65]), "=f"(d[OFF + 66]), "=f"(d[OFF + 67]), "=f"(d[OFF + 68]), "=f"(d[OFF + 69]), "=f"(d[OFF + 70]), "=f"(d[OFF + 71]), "=f"(d[OFF + 72]), "=f"(d[OFF + 73]), "=f"(d[OFF + 74]), "=f"(d[OFF + 75]), "=f"(d[OFF + 76]), "=f"(d[OFF + 77]), "=f"(d[OFF + 78]), "=f"(d[OFF + 79]), "=f"(d[OFF + 80]), "=f"(d[OFF + 81]), "=f"(d[OFF + 82]), "=f"(d[OFF + 83]), "=f"(d[OFF + 84]), "=f"(d[OFF + 85]), "=f"(d[OFF + 86]), "=f"(d[OFF + 87]), "=f"(d[OFF + 88]), "=f"(d[OFF + 89]), "=f"(d[OFF + 90]), "=f"(d[OFF + 91]), "=f"(d[OFF + 92]), "=f"(d[OFF + 93]), "=f"(d[OFF + 94]), "=f"(d[OFF + 95]), "=f"(d[OFF + 96]), "=f"(d[OFF + 97]), "=f"(d[OFF + 98]), "=f"(d[OFF + 99]), "=f"(d[OFF + 100]), "=f"(d[OFF + 101]), "=f"(d[OFF + 102]), "=f"(d[OFF + 103])
            : "r"(a0), "r"(a1), "r"(a2), "r"(a3), "l"(descB), "n"(0));
    }
};
template <int OFF, int NA> struct WG<208, OFF, true, NA> {
    static __device__ __forceinline__ void mma(float (&d)[NA], uint32_t a0, uint32_t a1, uint32_t a2, uint32_t a3, uint64_t descB) {
        asm volatile(
            "{\n"
            ".reg .pred p;\n"
            "setp.ne.b32 p, %109, 0;\n"
            "wgmma.mma_async.sync.aligned.m64n208k16.f32.bf16.bf16 "
            "{%0, %1, %2, %3, %4, %5, %6, %7, %8, %9, %10, %11, %12, %13, %14, %15, %16, %17, %18, %19, %20, %21, %22, %23, %24, %25, %26, %27, %28, %29, %30, %31, %32, %33, %34, %35, %36, %37, %38, %39, %40, %41, %42, %43, %44, %45, %46, %47, %48, %49, %50, %51, %52, %53, %54, %55, %56, %57, %58, %59, %60, %61, %62, %63, %64, %65, %66, %67, %68, %69, %70, %71, %72, %73, %74, %75, %76, %77, %78, %79, %80, %81, %82, %83, %84, %85, %86, %87, %88, %89, %90, %91, %92, %93, %94, %95, %96, %97, %98, %99, %100, %101, %102, %103}, "
            "{%104, %105, %106, %107}, %108, p, 1, 1, 0;\n"
            "}\n"
            : "+f"(d[OFF + 0]), "+f"(d[OFF + 1]), "+f"(d[OFF + 2]), "+f"(d[OFF + 3]), "+f"(d[OFF + 4]), "+f"(d[OFF + 5]), "+f"(d[OFF + 6]), "+f"(d[OFF + 7]), "+f"(d[OFF + 8]), "+f"(d[OFF + 9]), "+f"(d[OFF + 10]), "+f"(d[OFF + 11]), "+f"(d[OFF + 12]), "+f"(d[OFF + 13]), "+f"(d[OFF + 14]), "+f"(d[OFF + 15]), "+f"(d[OFF + 16]), "+f"(d[OFF + 17]), "+f"(d[OFF + 18]), "+f"(d[OFF + 19]), "+f"(d[OFF + 20]), "+f"(d[OFF + 21]), "+f"(d[OFF + 22]), "+f"(d[OFF + 23]), "+f"(d[OFF + 24]), "+f"(d[OFF + 25]), "+f"(d[OFF + 26]), "+f"(d[OFF + 27]), "+f"(d[OFF + 28]), "+f"(d[OFF + 29]), "+f"(d[OFF + 30]), "+f"(d[OFF + 31]), "+f"(d[OFF + 32]), "+f"(d[OFF + 33]), "+f"(d[OFF + 34]), "+f"(d[OFF + 35]), "+f"(d[OFF + 36]), "+f"(d[OFF + 37]), "+f"(d[OFF + 38]), "+f"(d[OFF + 39]), "+f"(d[OFF + 40]), "+f"(d[OFF + 41]), "+f"(d[OFF + 42]), "+f"(d[OFF + 43]), "+f"(d[OFF + 44]), "+f"(d[OFF + 45]), "+f"(d[OFF + 46]), "+f"(d[OFF + 47]), "+f"(d[OFF + 48]), "+f"(d[OFF + 49]), "+f"(d[OFF + 50]), "+f"(d[OFF + 51]), "+f"(d[OFF + 52]), "+f"(d[OFF + 53]), "+f"(d[OFF + 54]), "+f"(d[OFF + 55]), "+f"(d[OFF + 56]), "+f"(d[OFF + 57]), "+f"(d[OFF + 58]), "+f"(d[OFF + 59]), "+f"(d[OFF + 60]), "+f"(d[OFF + 61]), "+f"(d[OFF + 62]), "+f"(d[OFF + 63]), "+f"(d[OFF + 64]), "+f"(d[OFF + 65]), "+f"(d[OFF + 66]), "+f"(d[OFF + 67]), "+f"(d[OFF + 68]), "+f"(d[OFF + 69]), "+f"(d[OFF + 70]), "+f"(d[OFF + 71]), "+f"(d[OFF + 72]), "+f"(d[OFF + 73]), "+f"(d[OFF + 74]), "+f"(d[OFF + 75]), "+f"(d[OFF + 76]), "+f"(d[OFF + 77]), "+f"(d[OFF + 78]), "+f"(d[OFF + 79]), "+f"(d[OFF + 80]), "+f"(d[OFF + 81]), "+f"(d[OFF + 82]), "+f"(d[OFF + 83]), "+f"(d[OFF + 84]), "+f"(d[OFF + 85]), "+f"(d[OFF + 86]), "+f"(d[OFF + 87]), "+f"(d[OFF + 88]), "+f"(d[OFF + 89]), "+f"(d[OFF + 90]), "+f"(d[OFF + 91]), "+f"(d[OFF + 92]), "+f"(d[OFF + 93]), "+f"(d[OFF + 94]), "+f"(d[OFF + 95]), "+f"(d[OFF + 96]), "+f"(d[OFF + 97]), "+f"(d[OFF + 98]), "+f"(d[OFF + 99]), "+f"(d[OFF + 100]), "+f"(d[OFF + 101]), "+f"(d[OFF + 102]), "+f"(d[OFF + 103])
            : "r"(a0), "r"(a1), "r"(a2), "r"(a3), "l"(descB), "n"(1));
    }
};
template <int OFF, int NA> struct WG<120, OFF, false, NA> {
    static __device__ __forceinline__ void mma(float (&d)[NA], uint32_t a0, uint32_t a1, uint32_t a2, uint32_t a3, uint64_t descB) {
        asm volatile(
            "{\n"
            ".reg .pred p;\n"
            "setp.ne.b32 p, %65, 0;\n"
            "wgmma.mma_async.sync.aligned.m64n120k16.f32.bf16.bf16 "
            "{%0, %1, %2, %3, %4, %5, %6, %7, %8, %9, %10, %11, %12, %13, %14, %15, %16, %17, %18, %19, %20, %21, %22, %23, %24, %25, %26, %27, %28, %29, %30, %31, %32, %33, %34, %35, %36, %37, %38, %39, %40, %41, %42, %43, %44, %45, %46, %47, %48, %49, %50, %51, %52, %53, %54, %55, %56, %57, %58, %59}, "
            "{%60, %61, %62, %63}, %64, p, 1, 1, 0;\n"
            "}\n"
            : "=f"(d[OFF + 0]), "=f"(d[OFF + 1]), "=f"(d[OFF + 2]), "=f"(d[OFF + 3]), "=f"(d[OFF + 4]), "=f"(d[OFF + 5]), "=f"(d[OFF + 6]), "=f"(d[OFF + 7]), "=f"(d[OFF + 8]), "=f"(d[OFF + 9]), "=f"(d[OFF + 10]), "=f"(d[OFF + 11]), "=f"(d[OFF + 12]), "=f"(d[OFF + 13]), "=f"(d[OFF + 14]), "=f"(d[OFF + 15]), "=f"(d[OFF + 16]), "=f"(d[OFF + 17]), "=f"(d[OFF + 18]), "=f"(d[OFF + 19]), "=f"(d[OFF + 20]), "=f"(d[OFF + 21]), "=f"(d[OFF + 22]), "=f"(d[OFF + 23]), "=f"(d[OFF + 24]), "=f"(d[OFF + 25]), "=f"(d[OFF + 26]), "=f"(d[OFF + 27]), "=f"(d[OFF + 28]), "=f"(d[OFF + 29]), "=f"(d[OFF + 30]), "=f"(d[OFF + 31]), "=f"(d[OFF + 32]), "=f"(d[OFF + 33]), "=f"(d[OFF + 34]), "=f"(d[OFF + 35]), "=f"(d[OFF + 36]), "=f"(d[OFF + 37]), "=f"(d[OFF + 38]), "=f"(d[OFF + 39]), "=f"(d[OFF + 40]), "=f"(d[OFF + 41]), "=f"(d[OFF + 42]), "=f"(d[OFF + 43]), "=f"(d[OFF + 44]), "=f"(d[OFF + 45]), "=f"(d[OFF + 46]), "=f"(d[OFF + 47]), "=f"(d[OFF + 48]), "=f"(d[OFF + 49]), "=f"(d[OFF + 50]), "=f"(d[OFF + 51]), "=f"(d[OFF + 52]), "=f"(d[OFF + 53]), "=f"(d[OFF + 54]), "=f"(d[OFF + 55]), "=f"(d[OFF + 56]), "=f"(d[OFF + 57]), "=f"(d[OFF + 58]), "=f"(d[OFF + 59])
            : "r"(a0), "r"(a1), "r"(a2), "r"(a3), "l"(descB), "n"(0));
    }
};
template <int OFF, int NA> struct WG<120, OFF, true, NA> {
    static __device__ __forceinline__ void mma(float (&d)[NA], uint32_t a0, uint32_t a1, uint32_t a2, uint32_t a3, uint64_t descB) {
        asm volatile(
            "{\n"
            ".reg .pred p;\n"
            "setp.ne.b32 p, %65, 0;\n"
            "wgmma.mma_async.sync.aligned.m64n120k16.f32.bf16.bf16 "
            "{%0, %1, %2, %3, %4, %5, %6, %7, %8, %9, %10, %11, %12, %13, %14, %15, %16, %17, %18, %19, %20, %21, %22, %23, %24, %25, %26, %27, %28, %29, %30, %31, %32, %33, %34, %35, %36, %37, %38, %39, %40, %41, %42, %43, %44, %45, %46, %47, %48, %49, %50, %51, %52, %53, %54, %55, %56, %57, %58, %59}, "
            "{%60, %61, %62, %63}, %64, p, 1, 1, 0;\n"
            "}\n"
            : "+f"(d[OFF + 0]), "+f"(d[OFF + 1]), "+f"(d[OFF + 2]), "+f"(d[OFF + 3]), "+f"(d[OFF + 4]), "+f"(d[OFF + 5]), "+f"(d[OFF + 6]), "+f"(d[OFF + 7]), "+f"(d[OFF + 8]), "+f"(d[OFF + 9]), "+f"(d[OFF + 10]), "+f"(d[OFF + 11]), "+f"(d[OFF + 12]), "+f"(d[OFF + 13]), "+f"(d[OFF + 14]), "+f"(d[OFF + 15]), "+f"(d[OFF + 16]), "+f"(d[OFF + 17]), "+f"(d[OFF + 18]), "+f"(d[OFF + 19]), "+f"(d[OFF + 20]), "+f"(d[OFF + 21]), "+f"(d[OFF + 22]), "+f"(d[OFF + 23]), "+f"(d[OFF + 24]), "+f"(d[OFF + 25]), "+f"(d[OFF + 26]), "+f"(d[OFF + 27]), "+f"(d[OFF + 28]), "+f"(d[OFF + 29]), "+f"(d[OFF + 30]), "+f"(d[OFF + 31]), "+f"(d[OFF + 32]), "+f"(d[OFF + 33]), "+f"(d[OFF + 34]), "+f"(d[OFF + 35]), "+f"(d[OFF + 36]), "+f"(d[OFF + 37]), "+f"(d[OFF + 38]), "+f"(d[OFF + 39]), "+f"(d[OFF + 40]), "+f"(d[OFF + 41]), "+f"(d[OFF + 42]), "+f"(d[OFF + 43]), "+f"(d[OFF + 44]), "+f"(d[OFF + 45]), "+f"(d[OFF + 46]), "+f"(d[OFF + 47]), "+f"(d[OFF + 48]), "+f"(d[OFF + 49]), "+f"(d[OFF + 50]), "+f"(d[OFF + 51]), "+f"(d[OFF + 52]), "+f"(d[OFF + 53]), "+f"(d[OFF + 54]), "+f"(d[OFF + 55]), "+f"(d[OFF + 56]), "+f"(d[OFF + 57]), "+f"(d[OFF + 58]), "+f"(d[OFF + 59])
            : "r"(a0), "r"(a1), "r"(a2), "r"(a3), "l"(descB), "n"(1));
    }
};
template <int OFF, int NA> struct WG<112, OFF, false, NA> {
    static __device__ __forceinline__ void mma(float (&d)[NA], uint32_t a0, uint32_t a1, uint32_t a2, uint32_t a3, uint64_t descB) {
        asm volatile(
            "{\n"
            ".reg .pred p;\n"
            "setp.ne.b32 p, %61, 0;\n"
            "wgmma.mma_async.sync.aligned.m64n112k16.f32.bf16.bf16 "
            "{%0, %1, %2, %3, %4, %5, %6, %7, %8, %9, %10, %11, %12, %13, %14, %15, %16, %17, %18, %19, %20, %21, %22, %23, %24, %25, %26, %27, %28, %29, %30, %31, %32, %33, %34, %35, %36, %37, %38, %39, %40, %41, %42, %43, %44, %45, %46, %47, %48, %49, %50, %51, %52, %53, %54, %55}, "
            "{%56, %57, %58, %59}, %60, p, 1, 1, 0;\n"
            "}\n"
            : "=f"(d[OFF + 0]), "=f"(d[OFF + 1]), "=f"(d[OFF + 2]), "=f"(d[OFF + 3]), "=f"(d[OFF + 4]), "=f"(d[OFF + 5]), "=f"(d[OFF + 6]), "=f"(d[OFF + 7]), "=f"(d[OFF + 8]), "=f"(d[OFF + 9]), "=f"(d[OFF + 10]), "=f"(d[OFF + 11]), "=f"(d[OFF + 12]), "=f"(d[OFF + 13]), "=f"(d[OFF + 14]), "=f"(d[OFF + 15]), "=f"(d[OFF + 16]), "=f"(d[OFF + 17]), "=f"(d[OFF + 18]), "=f"(d[OFF + 19]), "=f"(d[OFF + 20]), "=f"(d[OFF + 21]), "=f"(d[OFF + 22]), "=f"(d[OFF + 23]), "=f"(d[OFF + 24]), "=f"(d[OFF + 25]), "=f"(d[OFF + 26]), "=f"(d[OFF + 27]), "=f"(d[OFF + 28]), "=f"(d[OFF + 29]), "=f"(d[OFF + 30]), "=f"(d[OFF + 31]), "=f"(d[OFF + 32]), "=f"(d[OFF + 33]), "=f"(d[OFF + 34]), "=f"(d[OFF + 35]), "=f"(d[OFF + 36]), "=f"(d[OFF + 37]), "=f"(d[OFF + 38]), "=f"(d[OFF + 39]), "=f"(d[OFF + 40]), "=f"(d[OFF + 41]), "=f"(d[OFF + 42]), "=f"(d[OFF + 43]), "=f"(d[OFF + 44]), "=f"(d[OFF + 45]), "=f"(d[OFF + 46]), "=f"(d[OFF + 47]), "=f"(d[OFF + 48]), "=f"(d[OFF + 49]), "=f"(d[OFF + 50]), "=f"(d[OFF + 51]), "=f"(d[OFF + 52]), "=f"(d[OFF + 53]), "=f"(d[OFF + 54]), "=f"(d[OFF + 55])
            : "r"(a0), "r"(a1), "r"(a2), "r"(a3), "l"(descB), "n"(0));
    }
};
template <int OFF, int NA> struct WG<112, OFF, true, NA> {
    static __device__ __forceinline__ void mma(float (&d)[NA], uint32_t a0, uint32_t a1, uint32_t a2, uint32_t a3, uint64_t descB) {
        asm volatile(
            "{\n"
            ".reg .pred p;\n"
            "setp.ne.b32 p, %61, 0;\n"
            "wgmma.mma_async.sync.aligned.m64n112k16.f32.bf16.bf16 "
            "{%0, %1, %2, %3, %4, %5, %6, %7, %8, %9, %10, %11, %12, %13, %14, %15, %16, %17, %18, %19, %20, %21, %22, %23, %24, %25, %26, %27, %28, %29, %30, %31, %32, %33, %34, %35, %36, %37, %38, %39, %40, %41, %42, %43, %44, %45, %46, %47, %48, %49, %50, %51, %52, %53, %54, %55}, "
            "{%56, %57, %58, %59}, %60, p, 1, 1, 0;\n"
            "}\n"
            : "+f"(d[OFF + 0]), "+f"(d[OFF + 1]), "+f"(d[OFF + 2]), "+f"(d[OFF + 3]), "+f"(d[OFF + 4]), "+f"(d[OFF + 5]), "+f"(d[OFF + 6]), "+f"(d[OFF + 7]), "+f"(d[OFF + 8]), "+f"(d[OFF + 9]), "+f"(d[OFF + 10]), "+f"(d[OFF + 11]), "+f"(d[OFF + 12]), "+f"(d[OFF + 13]), "+f"(d[OFF + 14]), "+f"(d[OFF + 15]), "+f"(d[OFF + 16]), "+f"(d[OFF + 17]), "+f"(d[OFF + 18]), "+f"(d[OFF + 19]), "+f"(d[OFF + 20]), "+f"(d[OFF + 21]), "+f"(d[OFF + 22]), "+f"(d[OFF + 23]), "+f"(d[OFF + 24]), "+f"(d[OFF + 25]), "+f"(d[OFF + 26]), "+f"(d[OFF + 27]), "+f"(d[OFF + 28]), "+f"(d[OFF + 29]), "+f"(d[OFF + 30]), "+f"(d[OFF + 31]), "+f"(d[OFF + 32]), "+f"(d[OFF + 33]), "+f"(d[OFF + 34]), "+f"(d[OFF + 35]), "+f"(d[OFF + 36]), "+f"(d[OFF + 37]), "+f"(d[OFF + 38]), "+f"(d[OFF + 39]), "+f"(d[OFF + 40]), "+f"(d[OFF + 41]), "+f"(d[OFF + 42]), "+f"(d[OFF + 43]), "+f"(d[OFF + 44]), "+f"(d[OFF + 45]), "+f"(d[OFF + 46]), "+f"(d[OFF + 47]), "+f"(d[OFF + 48]), "+f"(d[OFF + 49]), "+f"(d[OFF + 50]), "+f"(d[OFF + 51]), "+f"(d[OFF + 52]), "+f"(d[OFF + 53]), "+f"(d[OFF + 54]), "+f"(d[OFF + 55])
            : "r"(a0), "r"(a1), "r"(a2), "r"(a3), "l"(descB), "n"(1));
    }
};
template <int OFF, int NA> struct WG<96, OFF, false, NA> {
    static __device__ __forceinline__ void mma(float (&d)[NA], uint32_t a0, uint32_t a1, uint32_t a2, uint32_t a3, uint64_t descB) {
        asm volatile(
            "{\n"
            ".reg .pred p;\n"
            "setp.ne.b32 p, %53, 0;\n"
            "wgmma.mma_async.sync.aligned.m64n96k16.f32.bf16.bf16 "
            "{%0, %1, %2, %3, %4, %5, %6, %7, %8, %9, %10, %11, %12, %13, %14, %15, %16, %17, %18, %19, %20, %21, %22, %23, %24, %25, %26, %27, %28, %29, %30, %31, %32, %33, %34, %35, %36, %37, %38, %39, %40, %41, %42, %43, %44, %45, %46, %47}, "
            "{%48, %49, %50, %51}, %52, p, 1, 1, 0;\n"
            "}\n"
            : "=f"(d[OFF + 0]), "=f"(d[OFF + 1]), "=f"(d[OFF + 2]), "=f"(d[OFF + 3]), "=f"(d[OFF + 4]), "=f"(d[OFF + 5]), "=f"(d[OFF + 6]), "=f"(d[OFF + 7]), "=f"(d[OFF + 8]), "=f"(d[OFF + 9]), "=f"(d[OFF + 10]), "=f"(d[OFF + 11]), "=f"(d[OFF + 12]), "=f"(d[OFF + 13]), "=f"(d[OFF + 14]), "=f"(d[OFF + 15]), "=f"(d[OFF + 16]), "=f"(d[OFF + 17]), "=f"(d[OFF + 18]), "=f"(d[OFF + 19]), "=f"(d[OFF + 20]), "=f"(d[OFF + 21]), "=f"(d[OFF + 22]), "=f"(d[OFF + 23]), "=f"(d[OFF + 24]), "=f"(d[OFF + 25]), "=f"(d[OFF + 26]), "=f"(d[OFF + 27]), "=f"(d[OFF + 28]), "=f"(d[OFF + 29]), "=f"(d[OFF + 30]), "=f"(d[OFF + 31]), "=f"(d[OFF + 32]), "=f"(d[OFF + 33]), "=f"(d[OFF + 34]), "=f"(d[OFF + 35]), "=f"(d[OFF + 36]), "=f"(d[OFF + 37]), "=f"(d[OFF + 38]), "=f"(d[OFF + 39]), "=f"(d[OFF + 40]), "=f"(d[OFF + 41]), "=f"(d[OFF + 42]), "=f"(d[OFF + 43]), "=f"(d[OFF + 44]), "=f"(d[OFF + 45]), "=f"(d[OFF + 46]), "=f"(d[OFF + 47])
            : "r"(a0), "r"(a1), "r"(a2), "r"(a3), "l"(descB), "n"(0));
    }
};
template <int OFF, int NA> struct WG<96, OFF, true, NA> {
    static __device__ __forceinline__ void mma(float (&d)[NA], uint32_t a0, uint32_t a1, uint32_t a2, uint32_t a3, uint64_t descB) {
        asm volatile(
            "{\n"
            ".reg .pred p;\n"
            "setp.ne.b32 p, %53, 0;\n"
            "wgmma.mma_async.sync.aligned.m64n96k16.f32.bf16.bf16 "
            "{%0, %1, %2, %3, %4, %5, %6, %7, %8, %9, %10, %11, %12, %13, %14, %15, %16, %17, %18, %19, %20, %21, %22, %23, %24, %25, %26, %27, %28, %29, %30, %31, %32, %33, %34, %35, %36, %37, %38, %39, %40, %41, %42, %43, %44, %45, %46, %47}, "
            "{%48, %49, %50, %51}, %52, p, 1, 1, 0;\n"
            "}\n"
            : "+f"(d[OFF + 0]), "+f"(d[OFF + 1]), "+f"(d[OFF + 2]), "+f"(d[OFF + 3]), "+f"(d[OFF + 4]), "+f"(d[OFF + 5]), "+f"(d[OFF + 6]), "+f"(d[OFF + 7]), "+f"(d[OFF + 8]), "+f"(d[OFF + 9]), "+f"(d[OFF + 10]), "+f"(d[OFF + 11]), "+f"(d[OFF + 12]), "+f"(d[OFF + 13]), "+f"(d[OFF + 14]), "+f"(d[OFF + 15]), "+f"(d[OFF + 16]), "+f"(d[OFF + 17]), "+f"(d[OFF + 18]), "+f"(d[OFF + 19]), "+f"(d[OFF + 20]), "+f"(d[OFF + 21]), "+f"(d[OFF + 22]), "+f"(d[OFF + 23]), "+f"(d[OFF + 24]), "+f"(d[OFF + 25]), "+f"(d[OFF + 26]), "+f"(d[OFF + 27]), "+f"(d[OFF + 28]), "+f"(d[OFF + 29]), "+f"(d[OFF + 30]), "+f"(d[OFF + 31]), "+f"(d[OFF + 32]), "+f"(d[OFF + 33]), "+f"(d[OFF + 34]), "+f"(d[OFF + 35]), "+f"(d[OFF + 36]), "+f"(d[OFF + 37]), "+f"(d[OFF + 38]), "+f"(d[OFF + 39]), "+f"(d[OFF + 40]), "+f"(d[OFF + 41]), "+f"(d[OFF + 42]), "+f"(d[OFF + 43]), "+f"(d[OFF + 44]), "+f"(d[OFF + 45]), "+f"(d[OFF + 46]), "+f"(d[OFF + 47])
            : "r"(a0), "r"(a1), "r"(a2), "r"(a3), "l"(descB), "n"(1));
    }
};
template <int OFF, int NA> struct WG<64, OFF, true, NA> {
    static __device__ __forceinline__ void mma(float (&d)[NA], uint32_t a0, uint32_t a1, uint32_t a2, uint32_t a3, uint64_t descB) {
        asm volatile(
            "{\n"
            ".reg .pred p;\n"
            "setp.ne.b32 p, %37, 0;\n"
            "wgmma.mma_async.sync.aligned.m64n64k16.f32.bf16.bf16 "
            "{%0, %1, %2, %3, %4, %5, %6, %7, %8, %9, %10, %11, %12, %13, %14, %15, %16, %17, %18, %19, %20, %21, %22, %23, %24, %25, %26, %27, %28, %29, %30, %31}, "
            "{%32, %33, %34, %35}, %36, p, 1, 1, 0;\n"
            "}\n"
            : "+f"(d[OFF + 0]), "+f"(d[OFF + 1]), "+f"(d[OFF + 2]), "+f"(d[OFF + 3]), "+f"(d[OFF + 4]), "+f"(d[OFF + 5]), "+f"(d[OFF + 6]), "+f"(d[OFF + 7]), "+f"(d[OFF + 8]), "+f"(d[OFF + 9]), "+f"(d[OFF + 10]), "+f"(d[OFF + 11]), "+f"(d[OFF + 12]), "+f"(d[OFF + 13]), "+f"(d[OFF + 14]), "+f"(d[OFF + 15]), "+f"(d[OFF + 16]), "+f"(d[OFF + 17]), "+f"(d[OFF + 18]), "+f"(d[OFF + 19]), "+f"(d[OFF + 20]), "+f"(d[OFF + 21]), "+f"(d[OFF + 22]), "+f"(d[OFF + 23]), "+f"(d[OFF + 24]), "+f"(d[OFF + 25]), "+f"(d[OFF + 26]), "+f"(d[OFF + 27]), "+f"(d[OFF + 28]), "+f"(d[OFF + 29]), "+f"(d[OFF + 30]), "+f"(d[OFF + 31])
            : "r"(a0), "r"(a1), "r"(a2), "r"(a3), "l"(descB), "n"(1));
    }
};
template <int OFF, int NA> struct WG<48, OFF, true, NA> {
    static __device__ __forceinline__ void mma(float (&d)[NA], uint32_t a0, uint32_t a1, uint32_t a2, uint32_t a3, uint64_t descB) {
        asm volatile(
            "{\n"
            ".reg .pred p;\n"
            "setp.ne.b32 p, %29, 0;\n"
            "wgmma.mma_async.sync.aligned.m64n48k16.f32.bf16.bf16 "
            "{%0, %1, %2, %3, %4, %5, %6, %7, %8, %9, %10, %11, %12, %13, %14, %15, %16, %17, %18, %19, %20, %21, %22, %23}, "
            "{%24, %25, %26, %27}, %28, p, 1, 1, 0;\n"
            "}\n"
            : "+f"(d[OFF + 0]), "+f"(d[OFF + 1]), "+f"(d[OFF + 2]), "+f"(d[OFF + 3]), "+f"(d[OFF + 4]), "+f"(d[OFF + 5]), "+f"(d[OFF + 6]), "+f"(d[OFF + 7]), "+f"(d[OFF + 8]), "+f"(d[OFF + 9]), "+f"(d[OFF + 10]), "+f"(d[OFF + 11]), "+f"(d[OFF + 12]), "+f"(d[OFF + 13]), "+f"(d[OFF + 14]), "+f"(d[OFF + 15]), "+f"(d[OFF + 16]), "+f"(d[OFF + 17]), "+f"(d[OFF + 18]), "+f"(d[OFF + 19]), "+f"(d[OFF + 20]), "+f"(d[OFF + 21]), "+f"(d[OFF + 22]), "+f"(d[OFF + 23])
            : "r"(a0), "r"(a1), "r"(a2), "r"(a3), "l"(descB), "n"(1));
    }
};
template <int OFF, int NA> struct WG<32, OFF, true, NA> {
    static __device__ __forceinline__ void mma(float (&d)[NA], uint32_t a0, uint32_t a1, uint32_t a2, uint32_t a3, uint64_t descB) {
        asm volatile(
            "{\n"
            ".reg .pred p;\n"
            "setp.ne.b32 p, %21, 0;\n"
            "wgmma.mma_async.sync.aligned.m64n32k16.f32.bf16.bf16 "
            "{%0, %1, %2, %3, %4, %5, %6, %7, %8, %9, %10, %11, %12, %13, %14, %15}, "
            "{%16, %17, %18, %19}, %20, p, 1, 1, 0;\n"
            "}\n"
            : "+f"(d[OFF + 0]), "+f"(d[OFF + 1]), "+f"(d[OFF + 2]), "+f"(d[OFF + 3]), "+f"(d[OFF + 4]), "+f"(d[OFF + 5]), "+f"(d[OFF + 6]), "+f"(d[OFF + 7]), "+f"(d[OFF + 8]), "+f"(d[OFF + 9]), "+f"(d[OFF + 10]), "+f"(d[OFF + 11]), "+f"(d[OFF + 12]), "+f"(d[OFF + 13]), "+f"(d[OFF + 14]), "+f"(d[OFF + 15])
            : "r"(a0), "r"(a1), "r"(a2), "r"(a3), "l"(descB), "n"(1));
    }
};


__host__ __device__ constexpr int gate_time(int d) { return d == 0 ? DLY_POLL : DLY_P1 + (d - 1) * DLY_PS; }
__device__ __forceinline__ void unit_pos(uint32_t u, uint32_t& q, uint32_t& fg) {
    static_assert(W1_FG == 64 && W2_FG == 48, "unit order");
    const uint32_t r = u - NQ * W1_FG, q2 = (r * 1366) >> 16;
    q = u < NQ * W1_FG ? u >> 6 : q2;
    fg = u < NQ * W1_FG ? u & 63 : W1_FG + r - q2 * 48;
}
template <class T> __device__ __forceinline__ T* add_off(T* p, uint32_t bytes) {
    uint64_t r;
    asm("{\n.reg .b64 o;\ncvt.u64.u32 o, %2;\nadd.u64 %0, %1, o;\n}\n" : "=l"(r) : "l"(p), "r"(bytes));
    return (T*)r;
}
__device__ __forceinline__ uint32_t unit_src(uint32_t q, uint32_t fg) { return q * (32 * kN * 4) + fg * 128; }
__device__ __forceinline__ uint32_t lane_src(int lane) { return (lane >> 3) * (2 * kN * 4) + (lane & 7) * 16; }
__device__ __forceinline__ uint32_t unit_dst(uint32_t q, uint32_t fg) {
    return ((fg >> 2) * KSTEPS + (q >> 1)) * 8192 + (fg & 3) * 2048 + (q & 1) * 512;
}
__device__ __forceinline__ uint32_t lane_dst(int lane) { return ((lane >> 2) & 1) * 1024 + (lane & 3) * 64 + (lane >> 3) * 16; }
__device__ __forceinline__ uint32_t lane_unit(int lane) {
    return ((lane >> 3) & 1) * 256 + (((lane >> 4) ^ (lane >> 3)) & 1) * 64 + (lane & 3) * 16 + ((lane >> 2) & 1) * 8;
}
__device__ __forceinline__ constexpr int unit_row(int i) { return 16 * (i >> 2) + 8 * ((i >> 1) & 1) + (i & 1); }
__device__ __forceinline__ void load_unit(uint4 (&v)[8], const int* p) {
#pragma unroll
    for (int i = 0; i < 8; i++) v[i] = ldg_stream(p + (size_t)unit_row(i) * kN);
}
__device__ __forceinline__ uint32_t bytes4(uint32_t v0, uint32_t v1, uint32_t v2, uint32_t v3) {
    return prmt(prmt(v0, v1, 0x0040), prmt(v2, v3, 0x0040), 0x5410);
}
__device__ __forceinline__ void pk_gather(uint32_t (&e)[4], uint32_t (&o)[4], const uint4 (&v)[8]) {
    e[0] = bytes4(v[0].x, v[2].x, v[4].x, v[6].x); o[0] = bytes4(v[1].x, v[3].x, v[5].x, v[7].x);
    e[1] = bytes4(v[0].y, v[2].y, v[4].y, v[6].y); o[1] = bytes4(v[1].y, v[3].y, v[5].y, v[7].y);
    e[2] = bytes4(v[0].z, v[2].z, v[4].z, v[6].z); o[2] = bytes4(v[1].z, v[3].z, v[5].z, v[7].z);
    e[3] = bytes4(v[0].w, v[2].w, v[4].w, v[6].w); o[3] = bytes4(v[1].w, v[3].w, v[5].w, v[7].w);
}

__device__ __forceinline__ void tile0_of(int c, int& fp, int& m0) {
    const int t = c - 4, k = ((t - 32) * 37) >> 8;
    fp = t < 0 ? 0 : t < 32 ? t & 7 : t < 60 ? t - 31 - 7 * k : t - 54;
    m0 = (t < 0 ? 4 + c : t < 32 ? t >> 3 : 4 + k) * N0;
}
__device__ __forceinline__ void tile1_of(int c, int& fp, int& m0) {
    if (c < 6) { fp = c; m0 = 8 * N0; }
    else { fp = 8 + (c - 6) / 10; m0 = ((c - 6) % 10) * N1; }
}

__device__ __forceinline__ void ll_fetch(u64 (&c)[4], const char* p) {
    asm volatile("ld.relaxed.gpu.global.b64 %0, [%4];\nld.relaxed.gpu.global.b64 %1, [%4 + 128];\n"
                 "ld.relaxed.gpu.global.b64 %2, [%4 + 512];\nld.relaxed.gpu.global.b64 %3, [%4 + 640];"
                 : "=l"(c[0]), "=l"(c[1]), "=l"(c[2]), "=l"(c[3]) : "l"(p) : "memory");
}
__device__ __forceinline__ void ll_copy(uint32_t dst, const char* src, uint32_t bar) {
    asm volatile("{\n.reg .pred p;\nelect.sync _|p, 0xffffffff;\n"
                 "@p cp.async.bulk.shared::cluster.global.mbarrier::complete_tx::bytes [%0], [%1], 1024, [%2];\n}\n"
                 ::"r"(dst), "l"(src), "r"(bar) : "memory");
}
__device__ __forceinline__ void ll_read(u64 (&c)[4], uint32_t a) {
    asm volatile("ld.volatile.shared.b64 %0, [%4];\nld.volatile.shared.b64 %1, [%4 + 128];\n"
                 "ld.volatile.shared.b64 %2, [%4 + 512];\nld.volatile.shared.b64 %3, [%4 + 640];"
                 : "=l"(c[0]), "=l"(c[1]), "=l"(c[2]), "=l"(c[3]) : "r"(a) : "memory");
}
template <int OFF>
__device__ __forceinline__ void ll_check(u64 (&c)[4], uint32_t a, const char* p, uint32_t tag) {
    asm volatile(
        "{\n.reg .pred p, q;\n.reg .b32 l, h0, h1, h2, h3, x, i, o;\n.reg .b64 g;\n"
        "mov.u32 i, 0;\n"
        "L_%=:\n"
        "mov.b64 {l, h0}, %0;\nmov.b64 {l, h1}, %1;\nmov.b64 {l, h2}, %2;\nmov.b64 {l, h3}, %3;\n"
        "lop3.b32 x, %6, h0, h1, 0x7e;\n"
        "lop3.b32 x, x, %6, h2, 0xf6;\n"
        "lop3.b32 x, x, %6, h3, 0xf6;\n"
        "setp.ne.u32 p, x, 0;\n"
        "vote.sync.any.pred p, p, 0xffffffff;\n"
        "@!p bra D_%=;\n"
        "and.b32 o, %4, 1023;\ncvt.u64.u32 g, o;\nadd.u64 g, g, %5;\n"
        "setp.ge.u32 q, x, 16;\n"
        "setp.ge.or.u32 q, i, %8, q;\n"
        "vote.sync.any.pred q, q, 0xffffffff;\n"
        "@!q ld.volatile.shared.b64 %0, [%4 + %9];\n@!q ld.volatile.shared.b64 %1, [%4 + %9 + 128];\n"
        "@!q ld.volatile.shared.b64 %2, [%4 + %9 + 512];\n@!q ld.volatile.shared.b64 %3, [%4 + %9 + 640];\n"
        "@q ld.relaxed.gpu.global.b64 %0, [g];\n@q ld.relaxed.gpu.global.b64 %1, [g + 128];\n"
        "@q ld.relaxed.gpu.global.b64 %2, [g + 512];\n@q ld.relaxed.gpu.global.b64 %3, [g + 640];\n"
        "add.u32 i, i, 1;\n"
        "setp.lt.u32 p, i, %7;\n"
        "@p bra L_%=;\n"
        "D_%=:\n}\n"
        : "+l"(c[0]), "+l"(c[1]), "+l"(c[2]), "+l"(c[3])
        : "r"(a), "l"(p), "r"(tag), "n"(SPIN_LIMIT >> 4), "n"(NSPIN), "n"(OFF) : "memory");
}
__device__ __forceinline__ void ll_poll(u64 (&c)[4], const char* p, uint32_t tag) {
    unsigned it = 0;
    while (__any_sync(0xffffffffu, (((uint32_t)(c[0] >> 32) ^ tag) | ((uint32_t)(c[1] >> 32) ^ tag) |
                                    ((uint32_t)(c[2] >> 32) ^ tag) | ((uint32_t)(c[3] >> 32) ^ tag)) != 0) &&
           ++it < (SPIN_LIMIT >> 4))
        ll_fetch(c, p);
}
__device__ __forceinline__ void decode_alu(uint32_t& r0, uint32_t& r1, uint32_t& r2, uint32_t& r3, uint32_t w,
                                           const uint32_t (&lt)[8]) {
    const uint32_t s0 = w & 0x77777777u, s1 = s0 >> 16, w4 = w * 16;
    const uint32_t m0 = prmt(w4, w, 0xd9c8), m1 = prmt(w4, w, 0xfbea);
    const uint32_t l0 = (prmt(lt[0], lt[1], s0) & ~m0) | (prmt(lt[2], lt[3], s0) & m0);
    const uint32_t h0 = (prmt(lt[4], lt[5], s0) & ~m0) | (prmt(lt[6], lt[7], s0) & m0);
    const uint32_t l1 = (prmt(lt[0], lt[1], s1) & ~m1) | (prmt(lt[2], lt[3], s1) & m1);
    const uint32_t h1 = (prmt(lt[4], lt[5], s1) & ~m1) | (prmt(lt[6], lt[7], s1) & m1);
    r0 = prmt(l0, h0, 0x5140); r1 = prmt(l0, h0, 0x7362);
    r2 = prmt(l1, h1, 0x5140); r3 = prmt(l1, h1, 0x7362);
}
template <int I0, int DI>
__device__ __forceinline__ void decode(uint32_t (&a)[16], const u64 (&c)[4], uint32_t tblv, const uint32_t (&lt)[8],
                                       const uint32_t (&mu)[4]) {
#pragma unroll
    for (int i = I0; i < 4; i += DI) {
        const int b = (i >> 1) * 8 + (i & 1);
        if (i < 4 - NALU) {
#pragma unroll
            for (int j = 0; j < 4; j++) a[b + 2 * j] = lds32(dp4a_u((uint32_t)c[i], mu[j], tblv));
        } else {
            decode_alu(a[b], a[b + 2], a[b + 4], a[b + 6], (uint32_t)c[i], lt);
        }
    }
}

__host__ __device__ constexpr int slot_of(int j) { return j < 16 ? j % 6 : (int)(0x2651032651032610ull >> (4 * (j - 16))) & 7; }
constexpr int STGA = 4, STGB = 3;
__host__ __device__ constexpr int slot_addr(int t, int s) {
    return t && (s < 2 || s == 6) ? (s == 6 ? 1 : 2 * s) * N1 * 128 : SLOT_OFF + s * SLOT_BYTES;
}
__host__ __device__ constexpr int stg_slot(int w) { return w ? STGB : STGA; }
__host__ __device__ constexpr int stg_uses(int w) {
    int n = stg_slot(w) == 4 || stg_slot(w) == 5;
    for (int i = 0; i < NSL; i++) n += slot_of(i) == stg_slot(w);
    return n;
}
__host__ __device__ constexpr bool reused(int j) {
    for (int i = j + 1; i < NSL; i++) if (slot_of(i) == slot_of(j)) return true;
    return j < 16 || slot_of(j) == STGA || slot_of(j) == STGB;
}
constexpr int STG_C0 = slot_addr(0, 6) - 2 * E0 * 128, STG_C1 = slot_addr(0, 4);
__host__ __device__ constexpr int loads_before(int j) {
    int n = 0;
    for (int i = 0; i < j; i++) n += slot_of(i) == slot_of(j);
    return n;
}
__host__ __device__ constexpr int uses_before(int j) {
    return loads_before(j) + (j >= 16 && (slot_of(j) == 4 || slot_of(j) == 5));
}
__host__ __device__ constexpr uint64_t prod_tbl(int j0) {
    uint64_t t = 0;
    for (int j = j0; j < j0 + 16; j++) t |= (uint64_t)(slot_of(j) | (((uses_before(j) + 1) & 1) << 3)) << (4 * (j - j0));
    return t;
}
__host__ __device__ constexpr uint64_t addr_tbl(int t) {
    uint64_t r = 0;
    for (int s = 0; s < NSLOTS; s++) r |= (uint64_t)(slot_addr(t, s) / 1024) << (8 * s);
    return r;
}
__host__ __device__ constexpr int dec_upto(int j) {
    return j < 14 ? j + 1 + (j >= RAMP1) + (j >= RAMP2) : j + 2 + (j >= RAMP3) + (JW == 5 && j >= RAMP4);
}
__host__ __device__ constexpr bool ramp_first(int d) {
    return d == RAMP1 + 1 || d == RAMP2 + 2 || d == RAMP3 + 2 || (JW == 5 && d == RAMP4 + 3);
}
__host__ __device__ constexpr int abuf(int j) { return JW == 5 && j >= RAMP4 + 4 ? (j == RAMP4 + 4 ? 4 : (j - 1) % 4) : j % 4; }
__host__ __device__ constexpr bool read_early(int d) {
    return d > RLATE && d < NSL && !ramp_first(d - 2) && !ramp_first(d - 3) && d != 18 && d != 20 && d != 21;
}
__host__ __device__ constexpr bool get_early(int d) { return ramp_first(d); }

__device__ __forceinline__ void fence_a(uint32_t (&a)[16]) {
#pragma unroll
    for (int i = 0; i < 16; i++) asm volatile("" : "+r"(a[i])::"memory");
}
template <int J, int N, int COL>
__device__ __forceinline__ void mma_slice(float (&acc)[N0 / 2], uint32_t (&a)[JW][16]) {
    constexpr int off = (slot_addr(J / KSTEPS, slot_of(J)) + COL * 128) / 16, b = abuf(J);
    constexpr uint64_t d0 = make_desc(SMEM_BASE);
    WG<N, COL / 2, (J % KSTEPS) != 0, N0 / 2>::mma(acc, a[b][0], a[b][1], a[b][2], a[b][3], d0 + off);
    WG<N, COL / 2, true, N0 / 2>::mma(acc, a[b][4], a[b][5], a[b][6], a[b][7], d0 + (off + 2));
    WG<N, COL / 2, true, N0 / 2>::mma(acc, a[b][8], a[b][9], a[b][10], a[b][11], d0 + (off + 4));
    WG<N, COL / 2, true, N0 / 2>::mma(acc, a[b][12], a[b][13], a[b][14], a[b][15], d0 + (off + 6));
}
template <int N> __device__ __forceinline__ void rename_acc(float (&acc)[N0 / 2]) {
#pragma unroll
    for (int i = 0; i < N / 2; i++) asm volatile("mov.b32 %0, %1;" : "=f"(acc[i]) : "f"(acc[i]) : "memory");
}
template <int N, int COL, bool FENCE>
__device__ __forceinline__ void stage_out(float (&acc)[N0 / 2], uint32_t sa, const float s0, const float s1) {
#pragma unroll
    for (int i = COL / 2; i < (COL + N) / 2; i++) asm volatile("" : "+f"(acc[i])::"memory");
#pragma unroll
    for (int j = COL / 8; j + 1 < (COL + N) / 8; j += 2) {
        const uint32_t r0 = pack_bf16x2(acc[4 * j + 0] * s0, acc[4 * j + 1] * s0);
        const uint32_t r1 = pack_bf16x2(acc[4 * j + 2] * s1, acc[4 * j + 3] * s1);
        const uint32_t r2 = pack_bf16x2(acc[4 * j + 4] * s0, acc[4 * j + 5] * s0);
        const uint32_t r3 = pack_bf16x2(acc[4 * j + 6] * s1, acc[4 * j + 7] * s1);
        asm volatile("stmatrix.sync.aligned.m8n8.x4.trans.shared.b16 [%0], {%1, %2, %3, %4};"
                     ::"r"(sa + j * 1024), "r"(r0), "r"(r1), "r"(r2), "r"(r3) : "memory");
    }
    if constexpr ((N / 8) & 1) {
        constexpr int j = (COL + N) / 8 - 1;
        const uint32_t r0 = pack_bf16x2(acc[4 * j + 0] * s0, acc[4 * j + 1] * s0);
        const uint32_t r1 = pack_bf16x2(acc[4 * j + 2] * s1, acc[4 * j + 3] * s1);
        asm volatile("stmatrix.sync.aligned.m8n8.x2.trans.shared.b16 [%0], {%1, %2};"
                     ::"r"(sa + j * 1024), "r"(r0), "r"(r1) : "memory");
    }
    if constexpr (FENCE) asm volatile("fence.proxy.async.shared::cta;" ::: "memory");
}

struct Maps { CUtensorMap m[4 + NCH]; };

__global__ void __cluster_dims__(2, 1, 1) __launch_bounds__(NUM_THREADS, 1)
nf4_gemm_kernel(const int* __restrict__ qw, u64* __restrict__ ll, unsigned* __restrict__ epoch,
                const __nv_bfloat16* __restrict__ lut, const __nv_bfloat16* __restrict__ scales,
                const __grid_constant__ Maps tm) {
    extern __shared__ __align__(1024) uint8_t smem_raw[];
    const uint32_t t_start = clock32();
    const int lane = threadIdx.x & 31;
    if (threadIdx.x < 32)
        asm volatile("prefetch.global.L2 [%0];" ::"l"(add_off(qw, unit_src(blockIdx.x / W1_FG, blockIdx.x % W1_FG) + lane * (kN * 4))) : "memory");
    const int warp = __shfl_sync(0xffffffffu, threadIdx.x >> 5, 0);
    const uint32_t sb = smem_u32(smem_raw);
    const uint32_t bar_full = sb + BAR_OFF;
    const uint32_t bar_empty = bar_full + NSLOTS * 8;
    const uint32_t bar_tbl = bar_empty + NSLOTS * 8;
    const uint32_t bar_code = bar_tbl + 8;
    const uint32_t bar_stg = bar_code + 8;

    if (warp == 1) {
        if (lane == 0) {
            for (int i = 0; i < 2 * (2 + NCH); i++) mbar_init(bar_stg + i * 8, 128);
            asm volatile("fence.mbarrier_init.release.cluster;" ::: "memory");
        }
        __syncwarp();
    }
    if (warp != 8) cluster_arrive_relaxed();
    const int crank = blockIdx.x & 1, cluster = blockIdx.x >> 1;
    if (warp < 8) {
        const int wg = warp >> 2;
        const uint32_t tagl = ld_ca_u32(epoch + lane);
        const uint32_t lv = ldg_u16(reinterpret_cast<const unsigned short*>(lut) + (lane & 15));
        int fp0, fp1, mm;
        tile0_of(cluster, fp0, mm);
        tile1_of(cluster, fp1, mm);
        const int ft0 = fp0 * 2 + crank, ft1 = fp1 * 2 + crank;
        const unsigned short* sc16 = reinterpret_cast<const unsigned short*>(scales) + warp * 16 + (lane >> 2);
        uint32_t sc0 = ldg_u16(sc16 + ft0 * FT), sc0h = ldg_u16(sc16 + ft0 * FT + 8);
        uint32_t sc1 = ldg_u16(sc16 + ft1 * FT), sc1h = ldg_u16(sc16 + ft1 * FT + 8);
        {
            constexpr int EPS = 128 / TBLC;
#pragma unroll
            for (int k = 0; k < 32 / EPS; k++) {
                const int e = warp * 32 + k * EPS + lane / (TBLC / 4);
                const uint32_t v = __shfl_sync(0xffffffffu, lv, e & 15) | (__shfl_sync(0xffffffffu, lv, e >> 4) << 16);
                asm volatile("st.shared.v4.u32 [%0], {%1, %1, %1, %1};"
                             ::"r"(sb + TBL_OFF + warp * (TBLC * 128) + k * 512 + lane * 16), "r"(v) : "memory");
            }
        }
        asm volatile("setmaxnreg.inc.sync.aligned.u32 %0;" ::"n"(CREGS));
        cluster_wait();
        mbar_arrive(bar_tbl);
        sc0 |= sc0h << 16;
        sc1 |= sc1h << 16;
        const char* ll0 = keep(reinterpret_cast<const char*>(ll) + (ft0 * (KSTEPS * 8192) + warp * 1024 + lane), 0);
        const char* ll1 = keep(reinterpret_cast<const char*>(ll) + (ft1 * (KSTEPS * 8192) + warp * 1024 + lane), 0);
        const uint32_t cbuf = sb + COD_OFF + warp * 1024;
        const uint32_t tblv = keep(sb + TBL_OFF + (lane % TBLC) * 4, lane);
        const uint32_t cempty = keep(lane < 2 ? mapa(bar_empty, lane) : 0, lane);
        const uint32_t sa0 = keep(sb + (((lane >> 4) * 8 + (lane & 7)) * 128) +
                                  ((((warp & 3) * 2 + ((lane >> 3) & 1)) ^ (lane & 7)) << 4), lane);
        uint32_t lt[8];
        {
            const uint32_t p01 = __shfl_sync(0xffffffffu, lv, 4 * lane) | (__shfl_sync(0xffffffffu, lv, 4 * lane + 1) << 16);
            const uint32_t p23 = __shfl_sync(0xffffffffu, lv, 4 * lane + 2) | (__shfl_sync(0xffffffffu, lv, 4 * lane + 3) << 16);
            const uint32_t pl = prmt(p01, p23, lane & 4 ? 0x7531 : 0x6420);
#pragma unroll
            for (int i = 0; i < 8; i++) lt[i] = __shfl_sync(0xffffffffu, pl, i & 1 ? i : i + (lane & 24));
        }
        uint32_t mu[4];
#pragma unroll
        for (int j = 0; j < 4; j++) mu[j] = keep(((uint32_t)(TBLC * 4) << (8 * j)) + lane, 0);
        uint32_t a[JW][16];
        float acc[N0 / 2];

        auto src = [&](auto dc) {
            constexpr int D = decltype(dc)::value;
            return (D < KSTEPS ? ll0 : ll1) + (D % KSTEPS) * 8192;
        };
        const uint32_t tag = __shfl_sync(0xffffffffu, tagl, 0);
        u64 c[4], ch[4];
        const uint32_t aw = keep(cbuf + lane_unit(lane), lane);
#pragma unroll
        for (int i = 0; i < 4; i++)
            asm volatile("st.shared.v4.u32 [%0], {%1, %1, %1, %1};" ::"r"(cbuf + (i >> 1) * 8192 + (i & 1) * 512 + lane * 16), "r"(tag) : "memory");
        asm volatile("fence.proxy.async.shared::cta;" ::: "memory");
        __syncwarp();
        auto fetch = [&](auto dc) {
            constexpr int D = decltype(dc)::value;
            if constexpr (D < NGATE) delay_until(t_start, gate_time(D));
            if constexpr (D < NSL) ll_copy(cbuf + (D & 1) * 8192, src(dc), bar_code);
        };
        auto get = [&](auto dc) {
            constexpr int D = decltype(dc)::value;
            if constexpr (D + 1 <= FLATE) fetch(IC<D + 1>{});
            if constexpr (!read_early(D)) ll_read(c, aw + (D & 1) * 8192);
            ll_check<(D & 1) * 8192>(c, aw, src(dc), tag + D % KSTEPS);
            if constexpr (D + 2 >= NGATE) fetch(IC<D + 2>{});
        };
        auto dec = [&](auto dc) {
            constexpr int D = decltype(dc)::value;
            if constexpr (HALF && ramp_first(D - 1)) {
                decode<0, 2>(a[abuf(D)], c, tblv, lt, mu);
                ch[1] = (uint32_t)c[1]; ch[3] = (uint32_t)c[3];
            } else {
                if constexpr (HALF && ramp_first(D - 2)) decode<1, 2>(a[abuf(D - 1)], ch, tblv, lt, mu);
                decode<0, 1>(a[abuf(D)], c, tblv, lt, mu);
            }
            if constexpr (D + 2 > FLATE && D + 2 < NGATE) fetch(IC<D + 2>{});
            if constexpr (read_early(D + 1)) ll_read(c, aw + ((D + 1) & 1) * 8192);
            if constexpr (get_early(D + 1)) get(IC<D + 1>{});
        };
        auto wait_full = [&](auto jc) {
            constexpr int J = decltype(jc)::value;
            mbar_wait(bar_full + slot_of(J) * 8, loads_before(J) & 1);
        };
        auto release = [&](auto jc) {
            constexpr int J = decltype(jc)::value;
            if constexpr (reused(J)) mbar_arrive_pair(cempty + slot_of(J) * 8, cempty);
        };
        auto step = [&](auto jc) {
            constexpr int J = decltype(jc)::value, D = dec_upto(J - 1) + 1;
            fence_a(a[abuf(J)]);
            wgmma_fence();
            mma_slice<J, (J < KSTEPS ? N0 : N1), 0>(acc, a);
            wgmma_commit();
            if constexpr (!get_early(D)) get(IC<D>{});
            if constexpr (J >= NEARLY) wait_full(IC<J + 1>{});
            wgmma_wait<1>();
            if constexpr (J != 0 && J != 18) release(IC<J - 1>{});
            dec(IC<D>{});
            if constexpr (dec_upto(J) > D) { get(IC<D + 1>{}); dec(IC<D + 1>{}); }
            if constexpr (J < NEARLY) wait_full(IC<J + 1>{});
        };
        static_assert(FLATE >= 1 && FLATE < NGATE && RLATE >= FLATE && RLATE < RAMP1 && RAMP1 + 2 < RAMP2 && RAMP2 < 14 &&
                      RAMP3 > 20 && RAMP3 < 28 && (!HALF || (RAMP2 < 13 && (JW == 4 ? RAMP3 < 27 : RAMP4 < 26))), "code schedule");
        static_assert(slot_of(10) == 4 && slot_of(11) == 5 && uses_before(11) == 1 && STG_C1 + 2 * E1 * 128 <= STG_C0, "staging");

        mbar_wait(bar_tbl, 0);
        delay_until(t_start, gate_time(0));
        ll_fetch(c, src(IC<0>{}) + (aw & 1023));
        fetch(IC<1>{});
        ll_poll(c, src(IC<0>{}) + (aw & 1023), tag);
        dec(IC<0>{});
        wait_full(IC<0>{});
        static_for<0, 14>(step);
        {
            const float s0 = __uint_as_float(sc0 << 16), s1 = __uint_as_float(sc0 & 0xffff0000u);
            const uint32_t sa = sa0 + STG_C0 + wg * (E0 * 128), sc = sa0 + STG_C1 - E0 * 128 + wg * (E1 * 128);
            auto group = [&](auto jc, auto nc, auto cc) {
                fence_a(a[decltype(jc)::value % 4]);
                wgmma_fence();
                mma_slice<decltype(jc)::value, decltype(nc)::value, decltype(cc)::value>(acc, a);
                wgmma_commit();
            };
            wait_full(IC<15>{});
            wgmma_wait<0>();
            rename_acc<N0>(acc);
            group(IC<14>{}, IC<E0>{}, IC<0>{});
            release(IC<13>{});
            get(IC<17>{});
            mbar_wait(bar_empty + 5 * 8, 1);
            group(IC<15>{}, IC<E0>{}, IC<0>{});
            dec(IC<17>{});
            group(IC<14>{}, IC<E1>{}, IC<E0>{});
            wgmma_wait<1>();
            stage_out<EI, 0, false>(acc, sa, s0, s1);
            group(IC<15>{}, IC<E1>{}, IC<E0>{});
            wait_full(IC<16>{});
            wgmma_wait<1>();
            release(IC<14>{});
            stage_out<E0 - EI, EI, true>(acc, sa, s0, s1);
            mbar_arrive(bar_stg + wg * 8);
            group(IC<16>{}, IC<S0>{}, IC<0>{});
            wait_full(IC<17>{});
            wgmma_wait<1>();
            release(IC<15>{});
            stage_out<EI, E0, false>(acc, sc, s0, s1);
            group(IC<17>{}, IC<S0>{}, IC<0>{});
            stage_out<E1 - EI, E0 + EI, true>(acc, sc, s0, s1);
            mbar_arrive(bar_stg + 16 + wg * 8);
            group(IC<16>{}, IC<S1>{}, IC<S0>{});
            get(IC<18>{}); dec(IC<18>{});
            group(IC<17>{}, IC<S1>{}, IC<S0>{});
            get(IC<19>{});
            wait_full(IC<18>{});
            wgmma_wait<1>();
            release(IC<16>{});
            dec(IC<19>{});
            wgmma_wait<0>();
            rename_acc<N1>(acc);
            release(IC<17>{});
        }
        static_for<18, NSL - JW>(step);
        {
            constexpr int J0 = NSL - JW;
            const float s0 = __uint_as_float(sc1 << 16), s1 = __uint_as_float(sc1 & 0xffff0000u);
            const uint32_t sa = sa0 + (wg ? slot_addr(1, STGB) : slot_addr(1, STGA));
            static_for<J0 + 1, NSL - 1>(wait_full);
            static_for<J0, NSL - 1>([&](auto jc) { fence_a(a[abuf(decltype(jc)::value)]); });
            wgmma_wait<0>();
            rename_acc<N1>(acc);
            wgmma_fence();
            mma_slice<J0, chunk_n(0), 0>(acc, a);
            release(IC<J0 - 1>{});
            get(IC<NSL - 1>{}); dec(IC<NSL - 1>{});
            asm volatile("{\n.reg .pred p;\nelect.sync _|p, 0xffffffff;\n"
                         "@p mbarrier.arrive.expect_tx.shared::cta.b64 _, [%0], %1;\n}\n" ::"r"(bar_code), "n"((NSL - 1) * 1024) : "memory");
            wgmma_fence();
            static_for<J0 + 1, NSL - 1>([&](auto jc) { mma_slice<decltype(jc)::value, chunk_n(0), 0>(acc, a); });
            wait_full(IC<NSL - 1>{});
            fence_a(a[abuf(NSL - 1)]);
            wgmma_fence();
            mma_slice<NSL - 1, chunk_n(0), 0>(acc, a);
            wgmma_commit();
            static_for<1, NCH + 1>([&](auto cc) {
                constexpr int C = decltype(cc)::value;
                if constexpr (C < NCH) {
                    wgmma_fence();
                    mma_slice<J0, chunk_n(C), chunk_col(C)>(acc, a);
                    wgmma_commit();
                    if constexpr (C == 1)
                        mbar_wait(bar_empty + (wg ? STGB : STGA) * 8, (wg ? stg_uses(1) - 1 : stg_uses(0) - 1) & 1);
                    wgmma_wait<1>();
                } else {
                    wgmma_wait<0>();
                }
                stage_out<chunk_n(C - 1), chunk_col(C - 1), true>(acc, sa, s0, s1);
                mbar_arrive(bar_stg + (1 + C) * 16 + wg * 8);
                if constexpr (C < NCH) {
                    wgmma_fence();
                    static_for<J0 + 1, NSL>([&](auto jc) { mma_slice<decltype(jc)::value, chunk_n(C), chunk_col(C)>(acc, a); });
                    wgmma_commit();
                }
            });
        }
    } else {
      if (warp >= 9) {
        {
            const int pw = warp - 9;
            int u = pw * NUM_CTAS + blockIdx.x;
            uint32_t q = u / W1_FG, fg = u % W1_FG;
            const int* qwk = keep(add_off(qw, lane_src(lane)), lane);
            u64* llk = keep(add_off(ll, lane_dst(lane)), lane);
            const unsigned* ep = epoch + lane;
            asm volatile("setmaxnreg.dec.sync.aligned.u32 %0;" ::"n"(504 - 2 * CREGS));
            const uint32_t tag = ld_ca_u32(ep);
            if (pw > 0) delay_until(t_start, DLY_R0 + pw * DLY_R);
            uint4 v[8];
            load_unit(v, add_off(qwk, unit_src(q, fg)));
#pragma unroll 1
            for (;;) {
                u64* dst = add_off(llk, unit_dst(q, fg));
                const uint32_t sl = q >> 1;
                static_assert(RSTOP % NUM_AUX == 0, "pack rounds");
                u += u < (RSTOP - 1) * NUM_CTAS ? NUM_AUX * NUM_CTAS : pw == 2 ? NUM_UNITS : 2 * NUM_CTAS;
                unit_pos(min(u, NUM_UNITS - 1), q, fg);
                const int* p = add_off(qwk, unit_src(q, fg));
                uint32_t e[4], o[4], w[4];
                pk_gather(e, o, v);
#pragma unroll
                for (int k = 0; k < 4; k++)
                    asm("lop3.b32 %0, %1, %2, 0x0f0f0f0f, 0xe4;" : "=r"(w[k]) : "r"(e[k]), "r"(o[k] << 4));
                ll_store2(dst, w[0], w[1], tag + sl);
                ll_store2((u64*)((uint64_t)dst ^ 320), w[2], w[3], tag + sl);
                if (u >= NUM_UNITS) break;
                load_unit(v, p);
            }
        }
        const CUtensorMap* maps = keep(&tm.m[3] + lane, 0);
        named_bar_arrive<4, 128>();
        cluster_wait();
        int fp, m0;
        if (warp == 11) {
            tile0_of(cluster, fp, m0);
            const int f0 = (fp * 2 + crank) * FT;
#pragma unroll 1
            for (int ch = 0; ch < 2; ch++) {
                const uint32_t src = sb + (ch ? STG_C1 : STG_C0);
                const int rows = ch ? E1 : E0;
                int h = 0;
#pragma unroll 1
                for (unsigned it = 0; it < 16 * SPIN_LIMIT && !mbar_test(bar_stg + ch * 16 + h * 8, 0); it++) { h ^= 1; __nanosleep(20); }
#pragma unroll 1
                for (int k = 0; k < 2; k++, h ^= 1) {
                    mbar_wait(bar_stg + ch * 16 + h * 8, 0);
#pragma unroll 1
                    for (int r = 0; r < rows; r += 8) {
                        asm volatile("{\n.reg .pred p;\nelect.sync _|p, 0xffffffff;\n"
                                     "@p cp.async.bulk.tensor.2d.global.shared::cta.bulk_group [%0, {%2, %3}], [%1];\n"
                                     "cp.async.bulk.commit_group;\ncp.async.bulk.wait_group.read 1;\n}\n"
                                     ::"l"(maps), "r"(src + (h * rows + r) * 128), "r"(f0 + h * 64), "r"(m0 + ch * E0 + r)
                                     : "memory");
                    }
                }
                asm volatile("cp.async.bulk.wait_group.read 0;" ::: "memory");
                __syncwarp();
                if (lane < 2) mbar_arrive_cluster_n(mapa(bar_empty + (5 - ch) * 8, lane), 8);
            }
        } else {
            const int wg = warp - 9;
            tile1_of(cluster, fp, m0);
            const int f0 = (fp * 2 + crank) * FT + wg * 64;
            const uint32_t src = sb + (wg ? slot_addr(1, STGB) : slot_addr(1, STGA));
            int r0 = 0;
#pragma unroll 1
            for (int ch = 0; ch < NCH; ch++) {
                mbar_wait(bar_stg + (2 + ch) * 16 + wg * 8, 0);
                asm volatile("{\n.reg .pred p;\nelect.sync _|p, 0xffffffff;\n"
                             "@p cp.async.bulk.tensor.2d.global.shared::cta.bulk_group [%0, {%2, %3}], [%1];\n}\n"
                             ::"l"(maps + 1 + ch), "r"(src + r0 * 128), "r"(f0), "r"(m0 + r0) : "memory");
                r0 += ((CHK >> (4 * ch)) & 15) * 8;
            }
            asm volatile("cp.async.bulk.commit_group;\ncp.async.bulk.wait_group.read 0;" ::: "memory");
        }
      } else {
        asm volatile("setmaxnreg.dec.sync.aligned.u32 %0;" ::"n"(504 - 2 * CREGS));
        if ((sb & 0xFFFFFF) != SMEM_BASE) __trap();
        if (lane == 0) {
            for (int s = 0; s < NSLOTS; s++) {
                mbar_init(bar_full + s * 8, 1);
                mbar_init(bar_empty + s * 8, 16);
            }
            mbar_init(bar_tbl, 256);
            mbar_init(bar_code, 8);
            asm volatile("fence.mbarrier_init.release.cluster;" ::: "memory");
        }
        __syncwarp();
        cluster_arrive_relaxed();
        const CUtensorMap* maps = keep(&tm.m[0] + lane, 0);
        unsigned* epk = keep(epoch + lane, 0);
        if (lane == 0) prefetch_map(maps + crank);
        int fp, m0;
        tile0_of(cluster, fp, m0);
        cluster_wait();
#pragma unroll 1
        for (int t = 0; t < 2; t++) {
            const int lo = t == 0 ? 120 : 104, row = m0 + crank * lo;
            const CUtensorMap* map = maps + (t ? 2 : crank);
            const uint32_t bytes = (t ? N1 : N0) * 128, dst = sb + crank * lo * 128;
            uint64_t tbl = t ? prod_tbl(16) : prod_tbl(0);
            const uint64_t adr = t ? addr_tbl(1) : addr_tbl(0);
#pragma unroll 1
            for (int ks = 0; ks < KSTEPS; ks++, tbl >>= 4) {
                const uint32_t slot = (uint32_t)tbl & 7;
                if (t == 0 && ks > 0 && ks < 6) delay_until(t_start, DLY_X0 + ks * DLY_XS);
                mbar_wait(bar_empty + slot * 8, ((uint32_t)tbl >> 3) & 1);
                asm volatile(
                    "{\n.reg .pred p;\nelect.sync _|p, 0xffffffff;\n"
                    "@p mbarrier.arrive.expect_tx.shared::cta.b64 _, [%2], %5;\n"
                    "@p cp.async.bulk.tensor.2d.shared::cluster.global.mbarrier::complete_tx::bytes.multicast::cluster"
                    " [%0], [%1, {%3, %4}], [%2], %6;\n}\n"
                    ::"r"(dst + (((uint32_t)(adr >> (8 * slot)) & 255) << 10)), "l"(map), "r"(bar_full + slot * 8), "r"(ks * BK), "r"(row), "r"(bytes),
                    "h"((uint16_t)3) : "memory");
            }
            tile1_of(cluster, fp, m0);
            if (t == 0 && lane >= 2 && lane < 4 + NCH) prefetch_map(maps + lane);
        }
        named_bar_sync<4, 128>();
        const uint32_t tag = ld_ca_u32(epk + lane);
        unsigned old = 0;
        if (lane == 0) old = atomicAdd(epk + 32, tag != 0 ? 1u : 0u);
        if (__shfl_sync(0xffffffffu, old, 0) == NUM_CTAS - 1) {
            if (lane == 0) epk[32] = 0;
            epk[lane] = tag == 0xfffffff0u ? 16 : tag + 16;
        }
        mbar_wait(bar_code, 0);
      }
    }
}

__global__ void generic_kernel(const __nv_bfloat16* __restrict__ x, const int* __restrict__ qw,
                               const __nv_bfloat16* __restrict__ lut, const __nv_bfloat16* __restrict__ scales,
                               __nv_bfloat16* __restrict__ out, int M, int N, int K, int G) {
    const int n = blockIdx.x * blockDim.x + threadIdx.x;
    const int m = blockIdx.y;
    if (n >= N) return;
    float acc = 0.f;
    for (int k = 0; k < K; k++) {
        const float l = __bfloat162float(lut[qw[(size_t)k * N + n] & 15]);
        const float s = __bfloat162float(scales[(size_t)(k / G) * N + n]);
        const float w = __bfloat162float(__float2bfloat16_rn(l * s));
        acc += __bfloat162float(x[(size_t)m * K + k]) * w;
    }
    out[(size_t)m * N + n] = __float2bfloat16_rn(acc);
}

typedef CUresult (*PFN_encodeTiled)(CUtensorMap*, CUtensorMapDataType, cuuint32_t, void*, const cuuint64_t*,
                                    const cuuint64_t*, const cuuint32_t*, const cuuint32_t*, CUtensorMapInterleave,
                                    CUtensorMapSwizzle, CUtensorMapL2promotion, CUtensorMapFloatOOBfill);

bool make_map_2d(PFN_encodeTiled fn, CUtensorMap* map, void* base, uint64_t inner, uint64_t outer, uint32_t box_inner,
                 uint32_t box_outer) {
    cuuint64_t dims[2] = {inner, outer};
    cuuint64_t strides[1] = {inner * 2};
    cuuint32_t box[2] = {box_inner, box_outer};
    cuuint32_t estr[2] = {1, 1};
    return fn(map, CU_TENSOR_MAP_DATA_TYPE_BFLOAT16, 2, base, dims, strides, box, estr, CU_TENSOR_MAP_INTERLEAVE_NONE,
              CU_TENSOR_MAP_SWIZZLE_128B, CU_TENSOR_MAP_L2_PROMOTION_L2_128B,
              CU_TENSOR_MAP_FLOAT_OOB_FILL_NONE) == CUDA_SUCCESS;
}

}

extern "C" void kernel_launch(void* const* d_in, const int* in_sizes, int n_in, void* d_out, int out_size) {
    const __nv_bfloat16* x = (const __nv_bfloat16*)d_in[0];
    const int* qw = (const int*)d_in[1];
    const __nv_bfloat16* lut = (const __nv_bfloat16*)d_in[2];
    const __nv_bfloat16* scales = (const __nv_bfloat16*)d_in[3];
    __nv_bfloat16* out = (__nv_bfloat16*)d_out;

    const double Kd = sqrt((double)in_sizes[0] * (double)in_sizes[1] / (double)out_size);
    const int K = (int)(Kd + 0.5);
    const int M = in_sizes[0] / K, N = in_sizes[1] / K;
    const int ng = in_sizes[3] / N;
    const int G = K / ng;

    bool fast = (M == kM && N == kN && K == kK && ng == 1 && in_sizes[2] >= 16);
    PFN_encodeTiled enc = nullptr;
    Maps tm;
    void *ll = nullptr, *epoch = nullptr;
    if (fast) {
        cudaDriverEntryPointQueryResult qres;
        void* fp = nullptr;
        if (cudaGetDriverEntryPoint("cuTensorMapEncodeTiled", &fp, cudaEnableDefault, &qres) != cudaSuccess || !fp) fast = false;
        enc = (PFN_encodeTiled)fp;
    }
    if (fast) {
        fast = make_map_2d(enc, &tm.m[0], (void*)x, kK, kM, BK, 120) &&
               make_map_2d(enc, &tm.m[1], (void*)x, kK, kM, BK, 112) &&
               make_map_2d(enc, &tm.m[2], (void*)x, kK, kM, BK, 104) &&
               make_map_2d(enc, &tm.m[3], (void*)out, kN, kM, 64, 8) &&
               cudaGetSymbolAddress(&ll, g_ll) == cudaSuccess && cudaGetSymbolAddress(&epoch, g_epoch) == cudaSuccess;
    }
    for (int c = 0; c < NCH && fast; c++) fast = make_map_2d(enc, &tm.m[4 + c], (void*)out, kN, kM, 64, chunk_n(c));
    cudaLaunchConfig_t cfg = {};
    cfg.gridDim = dim3(NUM_CTAS);
    cfg.blockDim = dim3(NUM_THREADS);
    cfg.dynamicSmemBytes = SMEM_TOTAL;
    cfg.stream = cudaStreamPerThread;
    if (fast) {
        int nclusters = 0;
        fast = cudaFuncSetAttribute(nf4_gemm_kernel, cudaFuncAttributeMaxDynamicSharedMemorySize, SMEM_TOTAL) == cudaSuccess &&
               cudaOccupancyMaxActiveClusters(&nclusters, nf4_gemm_kernel, &cfg) == cudaSuccess &&
               nclusters >= NUM_CTAS / 2;
    }
    if (!fast) {
        generic_kernel<<<dim3((N + 127) / 128, M), 128>>>(x, qw, lut, scales, out, M, N, K, G);
        return;
    }
    cudaLaunchKernelEx(&cfg, nf4_gemm_kernel, qw, (u64*)ll, (unsigned*)epoch, lut, scales, tm);
}
```

```cpp
#include <cuda_runtime.h>
#include <cuda_bf16.h>
#include <cuda.h>
#include <stdint.h>
#include <stdio.h>
#include <math.h>

namespace {

constexpr int kM = 2048, kN = 3584, kK = 1024;
constexpr int FT = 128;
constexpr int N0 = 232, N1 = 208;
constexpr int BK = 64, KSTEPS = kK / BK;
constexpr int NSL = 2 * KSTEPS;
constexpr int NSLOTS = 7;
constexpr int SLOT_BYTES = N0 * 128;
constexpr int SLOT_OFF = 3 * N1 * 128 - 2 * SLOT_BYTES;
constexpr int TBLC = 16;
constexpr int TBL_OFF = SLOT_OFF + 6 * SLOT_BYTES;
constexpr int COD_OFF = TBL_OFF + TBLC * 1024;
constexpr int BAR_OFF = COD_OFF + 2 * 8192;
constexpr int SMEM_TOTAL = BAR_OFF + 256;
constexpr int NUM_THREADS = 384;
constexpr int NUM_CTAS = 132;
constexpr int NUM_AUX = 3;
constexpr int CREGS = 224;
constexpr int NQ = kK / 32, NUM_UNITS = NQ * (kN / 32);
constexpr int W1_FG = 64, W2_FG = kN / 32 - W1_FG;
constexpr int DLY_R0 = 0;
constexpr int DLY_R = 600;
constexpr int DLY_X0 = 1000;
constexpr int DLY_XS = 900;
constexpr int DLY_POLL = 2600;
constexpr int DLY_P1 = 3250;
constexpr int DLY_PS = 700;
constexpr int NGATE = 4;
constexpr int FLATE = 3;
constexpr int RLATE = 5;
constexpr int NEARLY = 2;
constexpr int RAMP1 = 9;
constexpr int RAMP2 = 12;
constexpr int RAMP3 = 22;
constexpr int NSPIN = 24;
constexpr int RSTOP = 21;
constexpr int JW = 5;
constexpr int RAMP4 = 25;
constexpr int HALF = 1;
constexpr int NSPLIT = 5;
constexpr int EI = 80;
constexpr int E0 = 120, E1 = N0 - E0, S0 = 112, S1 = N1 - S0;
constexpr int CHK = 0x4688;
__host__ __device__ constexpr int chunk_n(int c) { return ((CHK >> (4 * c)) & 15) * 8; }
__host__ __device__ constexpr int chunk_col(int c) { return c ? chunk_col(c - 1) + chunk_n(c - 1) : 0; }
constexpr int NCH = CHK > 0xfffff ? 6 : CHK > 0xffff ? 5 : CHK > 0xfff ? 4 : 3;
static_assert(chunk_col(NCH) == N1 && S0 <= E0, "chunks");
constexpr unsigned SPIN_LIMIT = 1u << 20;

__device__ __align__(1024) unsigned long long g_ll[(size_t)(kN / FT) * NQ * FT * 4];
__device__ __align__(256) unsigned int g_epoch[64] = {16, 16, 16, 16, 16, 16, 16, 16, 16, 16, 16, 16, 16, 16, 16, 16,
                                                      16, 16, 16, 16, 16, 16, 16, 16, 16, 16, 16, 16, 16, 16, 16, 16};

template <int I> struct IC { static constexpr int value = I; };
template <int B, int E, class F> __device__ __forceinline__ void static_for(F&& f) {
    if constexpr (B < E) { f(IC<B>{}); static_for<B + 1, E>(f); }
}

__device__ __forceinline__ uint32_t smem_u32(const void* p) { return (uint32_t)__cvta_generic_to_shared(p); }
__device__ __forceinline__ uint32_t keep(uint32_t v, int lane) {
    asm volatile("shfl.sync.idx.b32 %0, %0, %1, 0x1f, 0xffffffff;" : "+r"(v) : "r"(lane));
    return v;
}
template <class T> __device__ __forceinline__ T* keep(T* p, int lane) {
    const uint64_t v = (uint64_t)p;
    return (T*)(((uint64_t)keep((uint32_t)(v >> 32), lane) << 32) | keep((uint32_t)v, lane));
}
__device__ __forceinline__ void mbar_init(uint32_t bar, uint32_t count) {
    asm volatile("mbarrier.init.shared::cta.b64 [%0], %1;" ::"r"(bar), "r"(count) : "memory");
}
__device__ __forceinline__ uint32_t clock32() { uint64_t c; asm volatile("mov.u64 %0, %%clock64;" : "=l"(c)); return (uint32_t)c; }
__device__ __forceinline__ void mbar_arrive(uint32_t bar) {
    asm volatile("mbarrier.arrive.shared::cta.b64 _, [%0];" ::"r"(bar) : "memory");
}
__device__ __forceinline__ uint32_t mapa(uint32_t a, uint32_t rank) {
    uint32_t r;
    asm("mapa.shared::cluster.u32 %0, %1, %2;" : "=r"(r) : "r"(a), "r"(rank));
    return r;
}
__device__ __forceinline__ void mbar_arrive_pair(uint32_t cbar, uint32_t base) {
    asm volatile("{\n.reg .pred p;\nsetp.ne.u32 p, %1, 0;\n@p mbarrier.arrive.shared::cluster.b64 _, [%0];\n}\n"
                 ::"r"(cbar), "r"(base) : "memory");
}
__device__ __forceinline__ void mbar_arrive_cluster_n(uint32_t cbar, uint32_t n) {
    asm volatile("mbarrier.arrive.shared::cluster.b64 _, [%0], %1;" ::"r"(cbar), "r"(n) : "memory");
}
__device__ __forceinline__ void delay_until(uint32_t t0, int clks) {
    while (__any_sync(0xffffffffu, (int)(clock32() - t0) < clks)) {}
}
__device__ __forceinline__ bool mbar_test(uint32_t bar, uint32_t parity) {
    uint32_t ok;
    asm volatile("{\n.reg .pred p;\nmbarrier.test_wait.parity.shared::cta.b64 p, [%1], %2;\nvote.sync.all.pred p, p, 0xffffffff;\nselp.u32 %0, 1, 0, p;\n}\n"
                 : "=r"(ok) : "r"(bar), "r"(parity) : "memory");
    return ok != 0;
}
__device__ __forceinline__ void mbar_wait(uint32_t bar, uint32_t parity) {
    asm volatile(
        "{\n.reg .pred p;\n.reg .u32 i;\n"
        "mbarrier.try_wait.parity.shared::cta.b64 p, [%0], %1;\n"
        "@p bra D_%=;\n"
        "mov.u32 i, 0;\n"
        "L_%=:\n"
        "mbarrier.try_wait.parity.shared::cta.b64 p, [%0], %1;\n"
        "@p bra D_%=;\n"
        "add.u32 i, i, 1;\n"
        "setp.lt.u32 p, i, %2;\n"
        "@p bra L_%=;\n"
        "D_%=:\n}\n"
        ::"r"(bar), "r"(parity), "n"(SPIN_LIMIT) : "memory");
}
__device__ __forceinline__ void prefetch_map(const CUtensorMap* map) {
    asm volatile("prefetch.tensormap [%0];" ::"l"(map) : "memory");
}
constexpr uint32_t SMEM_BASE = 1024;
__host__ __device__ constexpr uint64_t make_desc(uint32_t saddr) {
    return (uint64_t)((saddr & 0x3FFFF) >> 4) | ((uint64_t)1 << 16) | ((uint64_t)(1024 >> 4) << 32) | ((uint64_t)1 << 62);
}
__device__ __forceinline__ void wgmma_fence() { asm volatile("wgmma.fence.sync.aligned;" ::: "memory"); }
__device__ __forceinline__ void wgmma_commit() { asm volatile("wgmma.commit_group.sync.aligned;" ::: "memory"); }
template <int N> __device__ __forceinline__ void wgmma_wait() {
    asm volatile("wgmma.wait_group.sync.aligned %0;" ::"n"(N) : "memory");
}
__device__ __forceinline__ uint32_t pack_bf16x2(float lo, float hi) {
    uint32_t r;
    asm("cvt.rn.bf16x2.f32 %0, %1, %2;" : "=r"(r) : "f"(hi), "f"(lo));
    return r;
}
__device__ __forceinline__ uint32_t lds32(uint32_t addr) {
    uint32_t v;
    asm("ld.shared.u32 %0, [%1];" : "=r"(v) : "r"(addr));
    return v;
}
__device__ __forceinline__ uint32_t dp4a_u(uint32_t a, uint32_t b, uint32_t c) {
    uint32_t d;
    asm("dp4a.u32.u32 %0, %1, %2, %3;" : "=r"(d) : "r"(a), "r"(b), "r"(c));
    return d;
}
__device__ __forceinline__ uint32_t prmt(uint32_t a, uint32_t b, uint32_t s) {
    uint32_t d;
    asm("prmt.b32 %0, %1, %2, %3;" : "=r"(d) : "r"(a), "r"(b), "r"(s));
    return d;
}
template <int ID, int NT> __device__ __forceinline__ void named_bar_sync() {
    asm volatile("bar.sync %0, %1;" ::"n"(ID), "n"(NT) : "memory");
}
template <int ID, int NT> __device__ __forceinline__ void named_bar_arrive() {
    asm volatile("bar.arrive %0, %1;" ::"n"(ID), "n"(NT) : "memory");
}
__device__ __forceinline__ void cluster_arrive_relaxed() { asm volatile("barrier.cluster.arrive.relaxed.aligned;" ::: "memory"); }
__device__ __forceinline__ void cluster_wait() { asm volatile("barrier.cluster.wait.acquire.aligned;" ::: "memory"); }
__device__ __forceinline__ uint4 ldg_stream(const int* p) {
    uint4 v;
    asm volatile("ld.global.L1::no_allocate.L2::128B.v4.u32 {%0, %1, %2, %3}, [%4];"
                 : "=r"(v.x), "=r"(v.y), "=r"(v.z), "=r"(v.w) : "l"(p));
    return v;
}
__device__ __forceinline__ uint32_t ldg_u16(const unsigned short* p) {
    uint32_t v;
    asm volatile("ld.global.nc.u16 %0, [%1];" : "=r"(v) : "l"(p));
    return v;
}
__device__ __forceinline__ unsigned ld_ca_u32(const unsigned* p) {
    unsigned v;
    asm volatile("ld.global.ca.u32 %0, [%1];" : "=r"(v) : "l"(p) : "memory");
    return v;
}
typedef unsigned long long u64;
__device__ __forceinline__ void ll_store2(u64* p, uint32_t w0, uint32_t w1, uint32_t tag) {
    asm volatile("{\n.reg .b64 a, b;\nmov.b64 a, {%1, %3};\nmov.b64 b, {%2, %3};\n"
                 "st.relaxed.gpu.global.v2.b64 [%0], {a, b};\n}\n" ::"l"(p), "r"(w0), "r"(w1), "r"(tag) : "memory");
}

template <int N, int OFF, bool ACC, int NA> struct WG;
template <int OFF, int NA> struct WG<232, OFF, false, NA> {
    static __device__ __forceinline__ void mma(float (&d)[NA], uint32_t a0, uint32_t a1, uint32_t a2, uint32_t a3, uint64_t descB) {
        asm volatile(
            "{\n"
            ".reg .pred p;\n"
            "setp.ne.b32 p, %121, 0;\n"
            "wgmma.mma_async.sync.aligned.m64n232k16.f32.bf16.bf16 "
            "{%0, %1, %2, %3, %4, %5, %6, %7, %8, %9, %10, %11, %12, %13, %14, %15, %16, %17, %18, %19, %20, %21, %22, %23, %24, %25, %26, %27, %28, %29, %30, %31, %32, %33, %34, %35, %36, %37, %38, %39, %40, %41, %42, %43, %44, %45, %46, %47, %48, %49, %50, %51, %52, %53, %54, %55, %56, %57, %58, %59, %60, %61, %62, %63, %64, %65, %66, %67, %68, %69, %70, %71, %72, %73, %74, %75, %76, %77, %78, %79, %80, %81, %82, %83, %84, %85, %86, %87, %88, %89, %90, %91, %92, %93, %94, %95, %96, %97, %98, %99, %100, %101, %102, %103, %104, %105, %106, %107, %108, %109, %110, %111, %112, %113, %114, %115}, "
            "{%116, %117, %118, %119}, %120, p, 1, 1, 0;\n"
            "}\n"
            : "=f"(d[OFF + 0]), "=f"(d[OFF + 1]), "=f"(d[OFF + 2]), "=f"(d[OFF + 3]), "=f"(d[OFF + 4]), "=f"(d[OFF + 5]), "=f"(d[OFF + 6]), "=f"(d[OFF + 7]), "=f"(d[OFF + 8]), "=f"(d[OFF + 9]), "=f"(d[OFF + 10]), "=f"(d[OFF + 11]), "=f"(d[OFF + 12]), "=f"(d[OFF + 13]), "=f"(d[OFF + 14]), "=f"(d[OFF + 15]), "=f"(d[OFF + 16]), "=f"(d[OFF + 17]), "=f"(d[OFF + 18]), "=f"(d[OFF + 19]), "=f"(d[OFF + 20]), "=f"(d[OFF + 21]), "=f"(d[OFF + 22]), "=f"(d[OFF + 23]), "=f"(d[OFF + 24]), "=f"(d[OFF + 25]), "=f"(d[OFF + 26]), "=f"(d[OFF + 27]), "=f"(d[OFF + 28]), "=f"(d[OFF + 29]), "=f"(d[OFF + 30]), "=f"(d[OFF + 31]), "=f"(d[OFF + 32]), "=f"(d[OFF + 33]), "=f"(d[OFF + 34]), "=f"(d[OFF + 35]), "=f"(d[OFF + 36]), "=f"(d[OFF + 37]), "=f"(d[OFF + 38]), "=f"(d[OFF + 39]), "=f"(d[OFF + 40]), "=f"(d[OFF + 41]), "=f"(d[OFF + 42]), "=f"(d[OFF + 43]), "=f"(d[OFF + 44]), "=f"(d[OFF + 45]), "=f"(d[OFF + 46]), "=f"(d[OFF + 47]), "=f"(d[OFF + 48]), "=f"(d[OFF + 49]), "=f"(d[OFF + 50]), "=f"(d[OFF + 51]), "=f"(d[OFF + 52]), "=f"(d[OFF + 53]), "=f"(d[OFF + 54]), "=f"(d[OFF + 55]), "=f"(d[OFF + 56]), "=f"(d[OFF + 57]), "=f"(d[OFF + 58]), "=f"(d[OFF + 59]), "=f"(d[OFF + 60]), "=f"(d[OFF + 61]), "=f"(d[OFF + 62]), "=f"(d[OFF + 63]), "=f"(d[OFF + 64]), "=f"(d[OFF + 65]), "=f"(d[OFF + 66]), "=f"(d[OFF + 67]), "=f"(d[OFF + 68]), "=f"(d[OFF + 69]), "=f"(d[OFF + 70]), "=f"(d[OFF + 71]), "=f"(d[OFF + 72]), "=f"(d[OFF + 73]), "=f"(d[OFF + 74]), "=f"(d[OFF + 75]), "=f"(d[OFF + 76]), "=f"(d[OFF + 77]), "=f"(d[OFF + 78]), "=f"(d[OFF + 79]), "=f"(d[OFF + 80]), "=f"(d[OFF + 81]), "=f"(d[OFF + 82]), "=f"(d[OFF + 83]), "=f"(d[OFF + 84]), "=f"(d[OFF + 85]), "=f"(d[OFF + 86]), "=f"(d[OFF + 87]), "=f"(d[OFF + 88]), "=f"(d[OFF + 89]), "=f"(d[OFF + 90]), "=f"(d[OFF + 91]), "=f"(d[OFF + 92]), "=f"(d[OFF + 93]), "=f"(d[OFF + 94]), "=f"(d[OFF + 95]), "=f"(d[OFF + 96]), "=f"(d[OFF + 97]), "=f"(d[OFF + 98]), "=f"(d[OFF + 99]), "=f"(d[OFF + 100]), "=f"(d[OFF + 101]), "=f"(d[OFF + 102]), "=f"(d[OFF + 103]), "=f"(d[OFF + 104]), "=f"(d[OFF + 105]), "=f"(d[OFF + 106]), "=f"(d[OFF + 107]), "=f"(d[OFF + 108]), "=f"(d[OFF + 109]), "=f"(d[OFF + 110]), "=f"(d[OFF + 111]), "=f"(d[OFF + 112]), "=f"(d[OFF + 113]), "=f"(d[OFF + 114]), "=f"(d[OFF + 115])
            : "r"(a0), "r"(a1), "r"(a2), "r"(a3), "l"(descB), "n"(0));
    }
};
template <int OFF, int NA> struct WG<232, OFF, true, NA> {
    static __device__ __forceinline__ void mma(float (&d)[NA], uint32_t a0, uint32_t a1, uint32_t a2, uint32_t a3, uint64_t descB) {
        asm volatile(
            "{\n"
            ".reg .pred p;\n"
            "setp.ne.b32 p, %121, 0;\n"
            "wgmma.mma_async.sync.aligned.m64n232k16.f32.bf16.bf16 "
            "{%0, %1, %2, %3, %4, %5, %6, %7, %8, %9, %10, %11, %12, %13, %14, %15, %16, %17, %18, %19, %20, %21, %22, %23, %24, %25, %26, %27, %28, %29, %30, %31, %32, %33, %34, %35, %36, %37, %38, %39, %40, %41, %42, %43, %44, %45, %46, %47, %48, %49, %50, %51, %52, %53, %54, %55, %56, %57, %58, %59, %60, %61, %62, %63, %64, %65, %66, %67, %68, %69, %70, %71, %72, %73, %74, %75, %76, %77, %78, %79, %80, %81, %82, %83, %84, %85, %86, %87, %88, %89, %90, %91, %92, %93, %94, %95, %96, %97, %98, %99, %100, %101, %102, %103, %104, %105, %106, %107, %108, %109, %110, %111, %112, %113, %114, %115}, "
            "{%116, %117, %118, %119}, %120, p, 1, 1, 0;\n"
            "}\n"
            : "+f"(d[OFF + 0]), "+f"(d[OFF + 1]), "+f"(d[OFF + 2]), "+f"(d[OFF + 3]), "+f"(d[OFF + 4]), "+f"(d[OFF + 5]), "+f"(d[OFF + 6]), "+f"(d[OFF + 7]), "+f"(d[OFF + 8]), "+f"(d[OFF + 9]), "+f"(d[OFF + 10]), "+f"(d[OFF + 11]), "+f"(d[OFF + 12]), "+f"(d[OFF + 13]), "+f"(d[OFF + 14]), "+f"(d[OFF + 15]), "+f"(d[OFF + 16]), "+f"(d[OFF + 17]), "+f"(d[OFF + 18]), "+f"(d[OFF + 19]), "+f"(d[OFF + 20]), "+f"(d[OFF + 21]), "+f"(d[OFF + 22]), "+f"(d[OFF + 23]), "+f"(d[OFF + 24]), "+f"(d[OFF + 25]), "+f"(d[OFF + 26]), "+f"(d[OFF + 27]), "+f"(d[OFF + 28]), "+f"(d[OFF + 29]), "+f"(d[OFF + 30]), "+f"(d[OFF + 31]), "+f"(d[OFF + 32]), "+f"(d[OFF + 33]), "+f"(d[OFF + 34]), "+f"(d[OFF + 35]), "+f"(d[OFF + 36]), "+f"(d[OFF + 37]), "+f"(d[OFF + 38]), "+f"(d[OFF + 39]), "+f"(d[OFF + 40]), "+f"(d[OFF + 41]), "+f"(d[OFF + 42]), "+f"(d[OFF + 43]), "+f"(d[OFF + 44]), "+f"(d[OFF + 45]), "+f"(d[OFF + 46]), "+f"(d[OFF + 47]), "+f"(d[OFF + 48]), "+f"(d[OFF + 49]), "+f"(d[OFF + 50]), "+f"(d[OFF + 51]), "+f"(d[OFF + 52]), "+f"(d[OFF + 53]), "+f"(d[OFF + 54]), "+f"(d[OFF + 55]), "+f"(d[OFF + 56]), "+f"(d[OFF + 57]), "+f"(d[OFF + 58]), "+f"(d[OFF + 59]), "+f"(d[OFF + 60]), "+f"(d[OFF + 61]), "+f"(d[OFF + 62]), "+f"(d[OFF + 63]), "+f"(d[OFF + 64]), "+f"(d[OFF + 65]), "+f"(d[OFF + 66]), "+f"(d[OFF + 67]), "+f"(d[OFF + 68]), "+f"(d[OFF + 69]), "+f"(d[OFF + 70]), "+f"(d[OFF + 71]), "+f"(d[OFF + 72]), "+f"(d[OFF + 73]), "+f"(d[OFF + 74]), "+f"(d[OFF + 75]), "+f"(d[OFF + 76]), "+f"(d[OFF + 77]), "+f"(d[OFF + 78]), "+f"(d[OFF + 79]), "+f"(d[OFF + 80]), "+f"(d[OFF + 81]), "+f"(d[OFF + 82]), "+f"(d[OFF + 83]), "+f"(d[OFF + 84]), "+f"(d[OFF + 85]), "+f"(d[OFF + 86]), "+f"(d[OFF + 87]), "+f"(d[OFF + 88]), "+f"(d[OFF + 89]), "+f"(d[OFF + 90]), "+f"(d[OFF + 91]), "+f"(d[OFF + 92]), "+f"(d[OFF + 93]), "+f"(d[OFF + 94]), "+f"(d[OFF + 95]), "+f"(d[OFF + 96]), "+f"(d[OFF + 97]), "+f"(d[OFF + 98]), "+f"(d[OFF + 99]), "+f"(d[OFF + 100]), "+f"(d[OFF + 101]), "+f"(d[OFF + 102]), "+f"(d[OFF + 103]), "+f"(d[OFF + 104]), "+f"(d[OFF + 105]), "+f"(d[OFF + 106]), "+f"(d[OFF + 107]), "+f"(d[OFF + 108]), "+f"(d[OFF + 109]), "+f"(d[OFF + 110]), "+f"(d[OFF + 111]), "+f"(d[OFF + 112]), "+f"(d[OFF + 113]), "+f"(d[OFF + 114]), "+f"(d[OFF + 115])
            : "r"(a0), "r"(a1), "r"(a2), "r"(a3), "l"(descB), "n"(1));
    }
};
template <int OFF, int NA> struct WG<208, OFF, false, NA> {
    static __device__ __forceinline__ void mma(float (&d)[NA], uint32_t a0, uint32_t a1, uint32_t a2, uint32_t a3, uint64_t descB) {
        asm volatile(
            "{\n"
            ".reg .pred p;\n"
            "setp.ne.b32 p, %109, 0;\n"
            "wgmma.mma_async.sync.aligned.m64n208k16.f32.bf16.bf16 "
            "{%0, %1, %2, %3, %4, %5, %6, %7, %8, %9, %10, %11, %12, %13, %14, %15, %16, %17, %18, %19, %20, %21, %22, %23, %24, %25, %26, %27, %28, %29, %30, %31, %32, %33, %34, %35, %36, %37, %38, %39, %40, %41, %42, %43, %44, %45, %46, %47, %48, %49, %50, %51, %52, %53, %54, %55, %56, %57, %58, %59, %60, %61, %62, %63, %64, %65, %66, %67, %68, %69, %70, %71, %72, %73, %74, %75, %76, %77, %78, %79, %80, %81, %82, %83, %84, %85, %86, %87, %88, %89, %90, %91, %92, %93, %94, %95, %96, %97, %98, %99, %100, %101, %102, %103}, "
            "{%104, %105, %106, %107}, %108, p, 1, 1, 0;\n"
            "}\n"
            : "=f"(d[OFF + 0]), "=f"(d[OFF + 1]), "=f"(d[OFF + 2]), "=f"(d[OFF + 3]), "=f"(d[OFF + 4]), "=f"(d[OFF + 5]), "=f"(d[OFF + 6]), "=f"(d[OFF + 7]), "=f"(d[OFF + 8]), "=f"(d[OFF + 9]), "=f"(d[OFF + 10]), "=f"(d[OFF + 11]), "=f"(d[OFF + 12]), "=f"(d[OFF + 13]), "=f"(d[OFF + 14]), "=f"(d[OFF + 15]), "=f"(d[OFF + 16]), "=f"(d[OFF + 17]), "=f"(d[OFF + 18]), "=f"(d[OFF + 19]), "=f"(d[OFF + 20]), "=f"(d[OFF + 21]), "=f"(d[OFF + 22]), "=f"(d[OFF + 23]), "=f"(d[OFF + 24]), "=f"(d[OFF + 25]), "=f"(d[OFF + 26]), "=f"(d[OFF + 27]), "=f"(d[OFF + 28]), "=f"(d[OFF + 29]), "=f"(d[OFF + 30]), "=f"(d[OFF + 31]), "=f"(d[OFF + 32]), "=f"(d[OFF + 33]), "=f"(d[OFF + 34]), "=f"(d[OFF + 35]), "=f"(d[OFF + 36]), "=f"(d[OFF + 37]), "=f"(d[OFF + 38]), "=f"(d[OFF + 39]), "=f"(d[OFF + 40]), "=f"(d[OFF + 41]), "=f"(d[OFF + 42]), "=f"(d[OFF + 43]), "=f"(d[OFF + 44]), "=f"(d[OFF + 45]), "=f"(d[OFF + 46]), "=f"(d[OFF + 47]), "=f"(d[OFF + 48]), "=f"(d[OFF + 49]), "=f"(d[OFF + 50]), "=f"(d[OFF + 51]), "=f"(d[OFF + 52]), "=f"(d[OFF + 53]), "=f"(d[OFF + 54]), "=f"(d[OFF + 55]), "=f"(d[OFF + 56]), "=f"(d[OFF + 57]), "=f"(d[OFF + 58]), "=f"(d[OFF + 59]), "=f"(d[OFF + 60]), "=f"(d[OFF + 61]), "=f"(d[OFF + 62]), "=f"(d[OFF + 63]), "=f"(d[OFF + 64]), "=f"(d[OFF + 65]), "=f"(d[OFF + 66]), "=f"(d[OFF + 67]), "=f"(d[OFF + 68]), "=f"(d[OFF + 69]), "=f"(d[OFF + 70]), "=f"(d[OFF + 71]), "=f"(d[OFF + 72]), "=f"(d[OFF + 73]), "=f"(d[OFF + 74]), "=f"(d[OFF + 75]), "=f"(d[OFF + 76]), "=f"(d[OFF + 77]), "=f"(d[OFF + 78]), "=f"(d[OFF + 79]), "=f"(d[OFF + 80]), "=f"(d[OFF + 81]), "=f"(d[OFF + 82]), "=f"(d[OFF + 83]), "=f"(d[OFF + 84]), "=f"(d[OFF + 85]), "=f"(d[OFF + 86]), "=f"(d[OFF + 87]), "=f"(d[OFF + 88]), "=f"(d[OFF + 89]), "=f"(d[OFF + 90]), "=f"(d[OFF + 91]), "=f"(d[OFF + 92]), "=f"(d[OFF + 93]), "=f"(d[OFF + 94]), "=f"(d[OFF + 95]), "=f"(d[OFF + 96]), "=f"(d[OFF + 97]), "=f"(d[OFF + 98]), "=f"(d[OFF + 99]), "=f"(d[OFF + 100]), "=f"(d[OFF + 101]), "=f"(d[OFF + 102]), "=f"(d[OFF + 103])
            : "r"(a0), "r"(a1), "r"(a2), "r"(a3), "l"(descB), "n"(0));
    }
};
template <int OFF, int NA> struct WG<208, OFF, true, NA> {
    static __device__ __forceinline__ void mma(float (&d)[NA], uint32_t a0, uint32_t a1, uint32_t a2, uint32_t a3, uint64_t descB) {
        asm volatile(
            "{\n"
            ".reg .pred p;\n"
            "setp.ne.b32 p, %109, 0;\n"
            "wgmma.mma_async.sync.aligned.m64n208k16.f32.bf16.bf16 "
            "{%0, %1, %2, %3, %4, %5, %6, %7, %8, %9, %10, %11, %12, %13, %14, %15, %16, %17, %18, %19, %20, %21, %22, %23, %24, %25, %26, %27, %28, %29, %30, %31, %32, %33, %34, %35, %36, %37, %38, %39, %40, %41, %42, %43, %44, %45, %46, %47, %48, %49, %50, %51, %52, %53, %54, %55, %56, %57, %58, %59, %60, %61, %62, %63, %64, %65, %66, %67, %68, %69, %70, %71, %72, %73, %74, %75, %76, %77, %78, %79, %80, %81, %82, %83, %84, %85, %86, %87, %88, %89, %90, %91, %92, %93, %94, %95, %96, %97, %98, %99, %100, %101, %102, %103}, "
            "{%104, %105, %106, %107}, %108, p, 1, 1, 0;\n"
            "}\n"
            : "+f"(d[OFF + 0]), "+f"(d[OFF + 1]), "+f"(d[OFF + 2]), "+f"(d[OFF + 3]), "+f"(d[OFF + 4]), "+f"(d[OFF + 5]), "+f"(d[OFF + 6]), "+f"(d[OFF + 7]), "+f"(d[OFF + 8]), "+f"(d[OFF + 9]), "+f"(d[OFF + 10]), "+f"(d[OFF + 11]), "+f"(d[OFF + 12]), "+f"(d[OFF + 13]), "+f"(d[OFF + 14]), "+f"(d[OFF + 15]), "+f"(d[OFF + 16]), "+f"(d[OFF + 17]), "+f"(d[OFF + 18]), "+f"(d[OFF + 19]), "+f"(d[OFF + 20]), "+f"(d[OFF + 21]), "+f"(d[OFF + 22]), "+f"(d[OFF + 23]), "+f"(d[OFF + 24]), "+f"(d[OFF + 25]), "+f"(d[OFF + 26]), "+f"(d[OFF + 27]), "+f"(d[OFF + 28]), "+f"(d[OFF + 29]), "+f"(d[OFF + 30]), "+f"(d[OFF + 31]), "+f"(d[OFF + 32]), "+f"(d[OFF + 33]), "+f"(d[OFF + 34]), "+f"(d[OFF + 35]), "+f"(d[OFF + 36]), "+f"(d[OFF + 37]), "+f"(d[OFF + 38]), "+f"(d[OFF + 39]), "+f"(d[OFF + 40]), "+f"(d[OFF + 41]), "+f"(d[OFF + 42]), "+f"(d[OFF + 43]), "+f"(d[OFF + 44]), "+f"(d[OFF + 45]), "+f"(d[OFF + 46]), "+f"(d[OFF + 47]), "+f"(d[OFF + 48]), "+f"(d[OFF + 49]), "+f"(d[OFF + 50]), "+f"(d[OFF + 51]), "+f"(d[OFF + 52]), "+f"(d[OFF + 53]), "+f"(d[OFF + 54]), "+f"(d[OFF + 55]), "+f"(d[OFF + 56]), "+f"(d[OFF + 57]), "+f"(d[OFF + 58]), "+f"(d[OFF + 59]), "+f"(d[OFF + 60]), "+f"(d[OFF + 61]), "+f"(d[OFF + 62]), "+f"(d[OFF + 63]), "+f"(d[OFF + 64]), "+f"(d[OFF + 65]), "+f"(d[OFF + 66]), "+f"(d[OFF + 67]), "+f"(d[OFF + 68]), "+f"(d[OFF + 69]), "+f"(d[OFF + 70]), "+f"(d[OFF + 71]), "+f"(d[OFF + 72]), "+f"(d[OFF + 73]), "+f"(d[OFF + 74]), "+f"(d[OFF + 75]), "+f"(d[OFF + 76]), "+f"(d[OFF + 77]), "+f"(d[OFF + 78]), "+f"(d[OFF + 79]), "+f"(d[OFF + 80]), "+f"(d[OFF + 81]), "+f"(d[OFF + 82]), "+f"(d[OFF + 83]), "+f"(d[OFF + 84]), "+f"(d[OFF + 85]), "+f"(d[OFF + 86]), "+f"(d[OFF + 87]), "+f"(d[OFF + 88]), "+f"(d[OFF + 89]), "+f"(d[OFF + 90]), "+f"(d[OFF + 91]), "+f"(d[OFF + 92]), "+f"(d[OFF + 93]), "+f"(d[OFF + 94]), "+f"(d[OFF + 95]), "+f"(d[OFF + 96]), "+f"(d[OFF + 97]), "+f"(d[OFF + 98]), "+f"(d[OFF + 99]), "+f"(d[OFF + 100]), "+f"(d[OFF + 101]), "+f"(d[OFF + 102]), "+f"(d[OFF + 103])
            : "r"(a0), "r"(a1), "r"(a2), "r"(a3), "l"(descB), "n"(1));
    }
};
template <int OFF, int NA> struct WG<120, OFF, false, NA> {
    static __device__ __forceinline__ void mma(float (&d)[NA], uint32_t a0, uint32_t a1, uint32_t a2, uint32_t a3, uint64_t descB) {
        asm volatile(
            "{\n"
            ".reg .pred p;\n"
            "setp.ne.b32 p, %65, 0;\n"
            "wgmma.mma_async.sync.aligned.m64n120k16.f32.bf16.bf16 "
            "{%0, %1, %2, %3, %4, %5, %6, %7, %8, %9, %10, %11, %12, %13, %14, %15, %16, %17, %18, %19, %20, %21, %22, %23, %24, %25, %26, %27, %28, %29, %30, %31, %32, %33, %34, %35, %36, %37, %38, %39, %40, %41, %42, %43, %44, %45, %46, %47, %48, %49, %50, %51, %52, %53, %54, %55, %56, %57, %58, %59}, "
            "{%60, %61, %62, %63}, %64, p, 1, 1, 0;\n"
            "}\n"
            : "=f"(d[OFF + 0]), "=f"(d[OFF + 1]), "=f"(d[OFF + 2]), "=f"(d[OFF + 3]), "=f"(d[OFF + 4]), "=f"(d[OFF + 5]), "=f"(d[OFF + 6]), "=f"(d[OFF + 7]), "=f"(d[OFF + 8]), "=f"(d[OFF + 9]), "=f"(d[OFF + 10]), "=f"(d[OFF + 11]), "=f"(d[OFF + 12]), "=f"(d[OFF + 13]), "=f"(d[OFF + 14]), "=f"(d[OFF + 15]), "=f"(d[OFF + 16]), "=f"(d[OFF + 17]), "=f"(d[OFF + 18]), "=f"(d[OFF + 19]), "=f"(d[OFF + 20]), "=f"(d[OFF + 21]), "=f"(d[OFF + 22]), "=f"(d[OFF + 23]), "=f"(d[OFF + 24]), "=f"(d[OFF + 25]), "=f"(d[OFF + 26]), "=f"(d[OFF + 27]), "=f"(d[OFF + 28]), "=f"(d[OFF + 29]), "=f"(d[OFF + 30]), "=f"(d[OFF + 31]), "=f"(d[OFF + 32]), "=f"(d[OFF + 33]), "=f"(d[OFF + 34]), "=f"(d[OFF + 35]), "=f"(d[OFF + 36]), "=f"(d[OFF + 37]), "=f"(d[OFF + 38]), "=f"(d[OFF + 39]), "=f"(d[OFF + 40]), "=f"(d[OFF + 41]), "=f"(d[OFF + 42]), "=f"(d[OFF + 43]), "=f"(d[OFF + 44]), "=f"(d[OFF + 45]), "=f"(d[OFF + 46]), "=f"(d[OFF + 47]), "=f"(d[OFF + 48]), "=f"(d[OFF + 49]), "=f"(d[OFF + 50]), "=f"(d[OFF + 51]), "=f"(d[OFF + 52]), "=f"(d[OFF + 53]), "=f"(d[OFF + 54]), "=f"(d[OFF + 55]), "=f"(d[OFF + 56]), "=f"(d[OFF + 57]), "=f"(d[OFF + 58]), "=f"(d[OFF + 59])
            : "r"(a0), "r"(a1), "r"(a2), "r"(a3), "l"(descB), "n"(0));
    }
};
template <int OFF, int NA> struct WG<120, OFF, true, NA> {
    static __device__ __forceinline__ void mma(float (&d)[NA], uint32_t a0, uint32_t a1, uint32_t a2, uint32_t a3, uint64_t descB) {
        asm volatile(
            "{\n"
            ".reg .pred p;\n"
            "setp.ne.b32 p, %65, 0;\n"
            "wgmma.mma_async.sync.aligned.m64n120k16.f32.bf16.bf16 "
            "{%0, %1, %2, %3, %4, %5, %6, %7, %8, %9, %10, %11, %12, %13, %14, %15, %16, %17, %18, %19, %20, %21, %22, %23, %24, %25, %26, %27, %28, %29, %30, %31, %32, %33, %34, %35, %36, %37, %38, %39, %40, %41, %42, %43, %44, %45, %46, %47, %48, %49, %50, %51, %52, %53, %54, %55, %56, %57, %58, %59}, "
            "{%60, %61, %62, %63}, %64, p, 1, 1, 0;\n"
            "}\n"
            : "+f"(d[OFF + 0]), "+f"(d[OFF + 1]), "+f"(d[OFF + 2]), "+f"(d[OFF + 3]), "+f"(d[OFF + 4]), "+f"(d[OFF + 5]), "+f"(d[OFF + 6]), "+f"(d[OFF + 7]), "+f"(d[OFF + 8]), "+f"(d[OFF + 9]), "+f"(d[OFF + 10]), "+f"(d[OFF + 11]), "+f"(d[OFF + 12]), "+f"(d[OFF + 13]), "+f"(d[OFF + 14]), "+f"(d[OFF + 15]), "+f"(d[OFF + 16]), "+f"(d[OFF + 17]), "+f"(d[OFF + 18]), "+f"(d[OFF + 19]), "+f"(d[OFF + 20]), "+f"(d[OFF + 21]), "+f"(d[OFF + 22]), "+f"(d[OFF + 23]), "+f"(d[OFF + 24]), "+f"(d[OFF + 25]), "+f"(d[OFF + 26]), "+f"(d[OFF + 27]), "+f"(d[OFF + 28]), "+f"(d[OFF + 29]), "+f"(d[OFF + 30]), "+f"(d[OFF + 31]), "+f"(d[OFF + 32]), "+f"(d[OFF + 33]), "+f"(d[OFF + 34]), "+f"(d[OFF + 35]), "+f"(d[OFF + 36]), "+f"(d[OFF + 37]), "+f"(d[OFF + 38]), "+f"(d[OFF + 39]), "+f"(d[OFF + 40]), "+f"(d[OFF + 41]), "+f"(d[OFF + 42]), "+f"(d[OFF + 43]), "+f"(d[OFF + 44]), "+f"(d[OFF + 45]), "+f"(d[OFF + 46]), "+f"(d[OFF + 47]), "+f"(d[OFF + 48]), "+f"(d[OFF + 49]), "+f"(d[OFF + 50]), "+f"(d[OFF + 51]), "+f"(d[OFF + 52]), "+f"(d[OFF + 53]), "+f"(d[OFF + 54]), "+f"(d[OFF + 55]), "+f"(d[OFF + 56]), "+f"(d[OFF + 57]), "+f"(d[OFF + 58]), "+f"(d[OFF + 59])
            : "r"(a0), "r"(a1), "r"(a2), "r"(a3), "l"(descB), "n"(1));
    }
};
template <int OFF, int NA> struct WG<112, OFF, false, NA> {
    static __device__ __forceinline__ void mma(float (&d)[NA], uint32_t a0, uint32_t a1, uint32_t a2, uint32_t a3, uint64_t descB) {
        asm volatile(
            "{\n"
            ".reg .pred p;\n"
            "setp.ne.b32 p, %61, 0;\n"
            "wgmma.mma_async.sync.aligned.m64n112k16.f32.bf16.bf16 "
            "{%0, %1, %2, %3, %4, %5, %6, %7, %8, %9, %10, %11, %12, %13, %14, %15, %16, %17, %18, %19, %20, %21, %22, %23, %24, %25, %26, %27, %28, %29, %30, %31, %32, %33, %34, %35, %36, %37, %38, %39, %40, %41, %42, %43, %44, %45, %46, %47, %48, %49, %50, %51, %52, %53, %54, %55}, "
            "{%56, %57, %58, %59}, %60, p, 1, 1, 0;\n"
            "}\n"
            : "=f"(d[OFF + 0]), "=f"(d[OFF + 1]), "=f"(d[OFF + 2]), "=f"(d[OFF + 3]), "=f"(d[OFF + 4]), "=f"(d[OFF + 5]), "=f"(d[OFF + 6]), "=f"(d[OFF + 7]), "=f"(d[OFF + 8]), "=f"(d[OFF + 9]), "=f"(d[OFF + 10]), "=f"(d[OFF + 11]), "=f"(d[OFF + 12]), "=f"(d[OFF + 13]), "=f"(d[OFF + 14]), "=f"(d[OFF + 15]), "=f"(d[OFF + 16]), "=f"(d[OFF + 17]), "=f"(d[OFF + 18]), "=f"(d[OFF + 19]), "=f"(d[OFF + 20]), "=f"(d[OFF + 21]), "=f"(d[OFF + 22]), "=f"(d[OFF + 23]), "=f"(d[OFF + 24]), "=f"(d[OFF + 25]), "=f"(d[OFF + 26]), "=f"(d[OFF + 27]), "=f"(d[OFF + 28]), "=f"(d[OFF + 29]), "=f"(d[OFF + 30]), "=f"(d[OFF + 31]), "=f"(d[OFF + 32]), "=f"(d[OFF + 33]), "=f"(d[OFF + 34]), "=f"(d[OFF + 35]), "=f"(d[OFF + 36]), "=f"(d[OFF + 37]), "=f"(d[OFF + 38]), "=f"(d[OFF + 39]), "=f"(d[OFF + 40]), "=f"(d[OFF + 41]), "=f"(d[OFF + 42]), "=f"(d[OFF + 43]), "=f"(d[OFF + 44]), "=f"(d[OFF + 45]), "=f"(d[OFF + 46]), "=f"(d[OFF + 47]), "=f"(d[OFF + 48]), "=f"(d[OFF + 49]), "=f"(d[OFF + 50]), "=f"(d[OFF + 51]), "=f"(d[OFF + 52]), "=f"(d[OFF + 53]), "=f"(d[OFF + 54]), "=f"(d[OFF + 55])
            : "r"(a0), "r"(a1), "r"(a2), "r"(a3), "l"(descB), "n"(0));
    }
};
template <int OFF, int NA> struct WG<112, OFF, true, NA> {
    static __device__ __forceinline__ void mma(float (&d)[NA], uint32_t a0, uint32_t a1, uint32_t a2, uint32_t a3, uint64_t descB) {
        asm volatile(
            "{\n"
            ".reg .pred p;\n"
            "setp.ne.b32 p, %61, 0;\n"
            "wgmma.mma_async.sync.aligned.m64n112k16.f32.bf16.bf16 "
            "{%0, %1, %2, %3, %4, %5, %6, %7, %8, %9, %10, %11, %12, %13, %14, %15, %16, %17, %18, %19, %20, %21, %22, %23, %24, %25, %26, %27, %28, %29, %30, %31, %32, %33, %34, %35, %36, %37, %38, %39, %40, %41, %42, %43, %44, %45, %46, %47, %48, %49, %50, %51, %52, %53, %54, %55}, "
            "{%56, %57, %58, %59}, %60, p, 1, 1, 0;\n"
            "}\n"
            : "+f"(d[OFF + 0]), "+f"(d[OFF + 1]), "+f"(d[OFF + 2]), "+f"(d[OFF + 3]), "+f"(d[OFF + 4]), "+f"(d[OFF + 5]), "+f"(d[OFF + 6]), "+f"(d[OFF + 7]), "+f"(d[OFF + 8]), "+f"(d[OFF + 9]), "+f"(d[OFF + 10]), "+f"(d[OFF + 11]), "+f"(d[OFF + 12]), "+f"(d[OFF + 13]), "+f"(d[OFF + 14]), "+f"(d[OFF + 15]), "+f"(d[OFF + 16]), "+f"(d[OFF + 17]), "+f"(d[OFF + 18]), "+f"(d[OFF + 19]), "+f"(d[OFF + 20]), "+f"(d[OFF + 21]), "+f"(d[OFF + 22]), "+f"(d[OFF + 23]), "+f"(d[OFF + 24]), "+f"(d[OFF + 25]), "+f"(d[OFF + 26]), "+f"(d[OFF + 27]), "+f"(d[OFF + 28]), "+f"(d[OFF + 29]), "+f"(d[OFF + 30]), "+f"(d[OFF + 31]), "+f"(d[OFF + 32]), "+f"(d[OFF + 33]), "+f"(d[OFF + 34]), "+f"(d[OFF + 35]), "+f"(d[OFF + 36]), "+f"(d[OFF + 37]), "+f"(d[OFF + 38]), "+f"(d[OFF + 39]), "+f"(d[OFF + 40]), "+f"(d[OFF + 41]), "+f"(d[OFF + 42]), "+f"(d[OFF + 43]), "+f"(d[OFF + 44]), "+f"(d[OFF + 45]), "+f"(d[OFF + 46]), "+f"(d[OFF + 47]), "+f"(d[OFF + 48]), "+f"(d[OFF + 49]), "+f"(d[OFF + 50]), "+f"(d[OFF + 51]), "+f"(d[OFF + 52]), "+f"(d[OFF + 53]), "+f"(d[OFF + 54]), "+f"(d[OFF + 55])
            : "r"(a0), "r"(a1), "r"(a2), "r"(a3), "l"(descB), "n"(1));
    }
};
template <int OFF, int NA> struct WG<96, OFF, false, NA> {
    static __device__ __forceinline__ void mma(float (&d)[NA], uint32_t a0, uint32_t a1, uint32_t a2, uint32_t a3, uint64_t descB) {
        asm volatile(
            "{\n"
            ".reg .pred p;\n"
            "setp.ne.b32 p, %53, 0;\n"
            "wgmma.mma_async.sync.aligned.m64n96k16.f32.bf16.bf16 "
            "{%0, %1, %2, %3, %4, %5, %6, %7, %8, %9, %10, %11, %12, %13, %14, %15, %16, %17, %18, %19, %20, %21, %22, %23, %24, %25, %26, %27, %28, %29, %30, %31, %32, %33, %34, %35, %36, %37, %38, %39, %40, %41, %42, %43, %44, %45, %46, %47}, "
            "{%48, %49, %50, %51}, %52, p, 1, 1, 0;\n"
            "}\n"
            : "=f"(d[OFF + 0]), "=f"(d[OFF + 1]), "=f"(d[OFF + 2]), "=f"(d[OFF + 3]), "=f"(d[OFF + 4]), "=f"(d[OFF + 5]), "=f"(d[OFF + 6]), "=f"(d[OFF + 7]), "=f"(d[OFF + 8]), "=f"(d[OFF + 9]), "=f"(d[OFF + 10]), "=f"(d[OFF + 11]), "=f"(d[OFF + 12]), "=f"(d[OFF + 13]), "=f"(d[OFF + 14]), "=f"(d[OFF + 15]), "=f"(d[OFF + 16]), "=f"(d[OFF + 17]), "=f"(d[OFF + 18]), "=f"(d[OFF + 19]), "=f"(d[OFF + 20]), "=f"(d[OFF + 21]), "=f"(d[OFF + 22]), "=f"(d[OFF + 23]), "=f"(d[OFF + 24]), "=f"(d[OFF + 25]), "=f"(d[OFF + 26]), "=f"(d[OFF + 27]), "=f"(d[OFF + 28]), "=f"(d[OFF + 29]), "=f"(d[OFF + 30]), "=f"(d[OFF + 31]), "=f"(d[OFF + 32]), "=f"(d[OFF + 33]), "=f"(d[OFF + 34]), "=f"(d[OFF + 35]), "=f"(d[OFF + 36]), "=f"(d[OFF + 37]), "=f"(d[OFF + 38]), "=f"(d[OFF + 39]), "=f"(d[OFF + 40]), "=f"(d[OFF + 41]), "=f"(d[OFF + 42]), "=f"(d[OFF + 43]), "=f"(d[OFF + 44]), "=f"(d[OFF + 45]), "=f"(d[OFF + 46]), "=f"(d[OFF + 47])
            : "r"(a0), "r"(a1), "r"(a2), "r"(a3), "l"(descB), "n"(0));
    }
};
template <int OFF, int NA> struct WG<96, OFF, true, NA> {
    static __device__ __forceinline__ void mma(float (&d)[NA], uint32_t a0, uint32_t a1, uint32_t a2, uint32_t a3, uint64_t descB) {
        asm volatile(
            "{\n"
            ".reg .pred p;\n"
            "setp.ne.b32 p, %53, 0;\n"
            "wgmma.mma_async.sync.aligned.m64n96k16.f32.bf16.bf16 "
            "{%0, %1, %2, %3, %4, %5, %6, %7, %8, %9, %10, %11, %12, %13, %14, %15, %16, %17, %18, %19, %20, %21, %22, %23, %24, %25, %26, %27, %28, %29, %30, %31, %32, %33, %34, %35, %36, %37, %38, %39, %40, %41, %42, %43, %44, %45, %46, %47}, "
            "{%48, %49, %50, %51}, %52, p, 1, 1, 0;\n"
            "}\n"
            : "+f"(d[OFF + 0]), "+f"(d[OFF + 1]), "+f"(d[OFF + 2]), "+f"(d[OFF + 3]), "+f"(d[OFF + 4]), "+f"(d[OFF + 5]), "+f"(d[OFF + 6]), "+f"(d[OFF + 7]), "+f"(d[OFF + 8]), "+f"(d[OFF + 9]), "+f"(d[OFF + 10]), "+f"(d[OFF + 11]), "+f"(d[OFF + 12]), "+f"(d[OFF + 13]), "+f"(d[OFF + 14]), "+f"(d[OFF + 15]), "+f"(d[OFF + 16]), "+f"(d[OFF + 17]), "+f"(d[OFF + 18]), "+f"(d[OFF + 19]), "+f"(d[OFF + 20]), "+f"(d[OFF + 21]), "+f"(d[OFF + 22]), "+f"(d[OFF + 23]), "+f"(d[OFF + 24]), "+f"(d[OFF + 25]), "+f"(d[OFF + 26]), "+f"(d[OFF + 27]), "+f"(d[OFF + 28]), "+f"(d[OFF + 29]), "+f"(d[OFF + 30]), "+f"(d[OFF + 31]), "+f"(d[OFF + 32]), "+f"(d[OFF + 33]), "+f"(d[OFF + 34]), "+f"(d[OFF + 35]), "+f"(d[OFF + 36]), "+f"(d[OFF + 37]), "+f"(d[OFF + 38]), "+f"(d[OFF + 39]), "+f"(d[OFF + 40]), "+f"(d[OFF + 41]), "+f"(d[OFF + 42]), "+f"(d[OFF + 43]), "+f"(d[OFF + 44]), "+f"(d[OFF + 45]), "+f"(d[OFF + 46]), "+f"(d[OFF + 47])
            : "r"(a0), "r"(a1), "r"(a2), "r"(a3), "l"(descB), "n"(1));
    }
};
template <int OFF, int NA> struct WG<64, OFF, true, NA> {
    static __device__ __forceinline__ void mma(float (&d)[NA], uint32_t a0, uint32_t a1, uint32_t a2, uint32_t a3, uint64_t descB) {
        asm volatile(
            "{\n"
            ".reg .pred p;\n"
            "setp.ne.b32 p, %37, 0;\n"
            "wgmma.mma_async.sync.aligned.m64n64k16.f32.bf16.bf16 "
            "{%0, %1, %2, %3, %4, %5, %6, %7, %8, %9, %10, %11, %12, %13, %14, %15, %16, %17, %18, %19, %20, %21, %22, %23, %24, %25, %26, %27, %28, %29, %30, %31}, "
            "{%32, %33, %34, %35}, %36, p, 1, 1, 0;\n"
            "}\n"
            : "+f"(d[OFF + 0]), "+f"(d[OFF + 1]), "+f"(d[OFF + 2]), "+f"(d[OFF + 3]), "+f"(d[OFF + 4]), "+f"(d[OFF + 5]), "+f"(d[OFF + 6]), "+f"(d[OFF + 7]), "+f"(d[OFF + 8]), "+f"(d[OFF + 9]), "+f"(d[OFF + 10]), "+f"(d[OFF + 11]), "+f"(d[OFF + 12]), "+f"(d[OFF + 13]), "+f"(d[OFF + 14]), "+f"(d[OFF + 15]), "+f"(d[OFF + 16]), "+f"(d[OFF + 17]), "+f"(d[OFF + 18]), "+f"(d[OFF + 19]), "+f"(d[OFF + 20]), "+f"(d[OFF + 21]), "+f"(d[OFF + 22]), "+f"(d[OFF + 23]), "+f"(d[OFF + 24]), "+f"(d[OFF + 25]), "+f"(d[OFF + 26]), "+f"(d[OFF + 27]), "+f"(d[OFF + 28]), "+f"(d[OFF + 29]), "+f"(d[OFF + 30]), "+f"(d[OFF + 31])
            : "r"(a0), "r"(a1), "r"(a2), "r"(a3), "l"(descB), "n"(1));
    }
};
template <int OFF, int NA> struct WG<48, OFF, true, NA> {
    static __device__ __forceinline__ void mma(float (&d)[NA], uint32_t a0, uint32_t a1, uint32_t a2, uint32_t a3, uint64_t descB) {
        asm volatile(
            "{\n"
            ".reg .pred p;\n"
            "setp.ne.b32 p, %29, 0;\n"
            "wgmma.mma_async.sync.aligned.m64n48k16.f32.bf16.bf16 "
            "{%0, %1, %2, %3, %4, %5, %6, %7, %8, %9, %10, %11, %12, %13, %14, %15, %16, %17, %18, %19, %20, %21, %22, %23}, "
            "{%24, %25, %26, %27}, %28, p, 1, 1, 0;\n"
            "}\n"
            : "+f"(d[OFF + 0]), "+f"(d[OFF + 1]), "+f"(d[OFF + 2]), "+f"(d[OFF + 3]), "+f"(d[OFF + 4]), "+f"(d[OFF + 5]), "+f"(d[OFF + 6]), "+f"(d[OFF + 7]), "+f"(d[OFF + 8]), "+f"(d[OFF + 9]), "+f"(d[OFF + 10]), "+f"(d[OFF + 11]), "+f"(d[OFF + 12]), "+f"(d[OFF + 13]), "+f"(d[OFF + 14]), "+f"(d[OFF + 15]), "+f"(d[OFF + 16]), "+f"(d[OFF + 17]), "+f"(d[OFF + 18]), "+f"(d[OFF + 19]), "+f"(d[OFF + 20]), "+f"(d[OFF + 21]), "+f"(d[OFF + 22]), "+f"(d[OFF + 23])
            : "r"(a0), "r"(a1), "r"(a2), "r"(a3), "l"(descB), "n"(1));
    }
};
template <int OFF, int NA> struct WG<32, OFF, true, NA> {
    static __device__ __forceinline__ void mma(float (&d)[NA], uint32_t a0, uint32_t a1, uint32_t a2, uint32_t a3, uint64_t descB) {
        asm volatile(
            "{\n"
            ".reg .pred p;\n"
            "setp.ne.b32 p, %21, 0;\n"
            "wgmma.mma_async.sync.aligned.m64n32k16.f32.bf16.bf16 "
            "{%0, %1, %2, %3, %4, %5, %6, %7, %8, %9, %10, %11, %12, %13, %14, %15}, "
            "{%16, %17, %18, %19}, %20, p, 1, 1, 0;\n"
            "}\n"
            : "+f"(d[OFF + 0]), "+f"(d[OFF + 1]), "+f"(d[OFF + 2]), "+f"(d[OFF + 3]), "+f"(d[OFF + 4]), "+f"(d[OFF + 5]), "+f"(d[OFF + 6]), "+f"(d[OFF + 7]), "+f"(d[OFF + 8]), "+f"(d[OFF + 9]), "+f"(d[OFF + 10]), "+f"(d[OFF + 11]), "+f"(d[OFF + 12]), "+f"(d[OFF + 13]), "+f"(d[OFF + 14]), "+f"(d[OFF + 15])
            : "r"(a0), "r"(a1), "r"(a2), "r"(a3), "l"(descB), "n"(1));
    }
};


__host__ __device__ constexpr int gate_time(int d) { return d == 0 ? DLY_POLL : DLY_P1 + (d - 1) * DLY_PS; }
__device__ __forceinline__ void unit_pos(uint32_t u, uint32_t& q, uint32_t& fg) {
    static_assert(W1_FG == 64 && W2_FG == 48, "unit order");
    const uint32_t r = u - NQ * W1_FG, q2 = (r * 1366) >> 16;
    q = u < NQ * W1_FG ? u >> 6 : q2;
    fg = u < NQ * W1_FG ? u & 63 : W1_FG + r - q2 * 48;
}
template <class T> __device__ __forceinline__ T* add_off(T* p, uint32_t bytes) {
    uint64_t r;
    asm("{\n.reg .b64 o;\ncvt.u64.u32 o, %2;\nadd.u64 %0, %1, o;\n}\n" : "=l"(r) : "l"(p), "r"(bytes));
    return (T*)r;
}
__device__ __forceinline__ uint32_t unit_src(uint32_t q, uint32_t fg) { return q * (32 * kN * 4) + fg * 128; }
__device__ __forceinline__ uint32_t lane_src(int lane) { return (lane >> 3) * (2 * kN * 4) + (lane & 7) * 16; }
__device__ __forceinline__ uint32_t unit_dst(uint32_t q, uint32_t fg) {
    return ((fg >> 2) * KSTEPS + (q >> 1)) * 8192 + (fg & 3) * 2048 + (q & 1) * 512;
}
__device__ __forceinline__ uint32_t lane_dst(int lane) { return ((lane >> 2) & 1) * 1024 + (lane & 3) * 64 + (lane >> 3) * 16; }
__device__ __forceinline__ uint32_t lane_unit(int lane) {
    return ((lane >> 3) & 1) * 256 + (((lane >> 4) ^ (lane >> 3)) & 1) * 64 + (lane & 3) * 16 + ((lane >> 2) & 1) * 8;
}
__device__ __forceinline__ constexpr int unit_row(int i) { return 16 * (i >> 2) + 8 * ((i >> 1) & 1) + (i & 1); }
__device__ __forceinline__ void load_unit(uint4 (&v)[8], const int* p) {
#pragma unroll
    for (int i = 0; i < 8; i++) v[i] = ldg_stream(p + (size_t)unit_row(i) * kN);
}
__device__ __forceinline__ uint32_t bytes4(uint32_t v0, uint32_t v1, uint32_t v2, uint32_t v3) {
    return prmt(prmt(v0, v1, 0x0040), prmt(v2, v3, 0x0040), 0x5410);
}
__device__ __forceinline__ void pk_gather(uint32_t (&e)[4], uint32_t (&o)[4], const uint4 (&v)[8]) {
    e[0] = bytes4(v[0].x, v[2].x, v[4].x, v[6].x); o[0] = bytes4(v[1].x, v[3].x, v[5].x, v[7].x);
    e[1] = bytes4(v[0].y, v[2].y, v[4].y, v[6].y); o[1] = bytes4(v[1].y, v[3].y, v[5].y, v[7].y);
    e[2] = bytes4(v[0].z, v[2].z, v[4].z, v[6].z); o[2] = bytes4(v[1].z, v[3].z, v[5].z, v[7].z);
    e[3] = bytes4(v[0].w, v[2].w, v[4].w, v[6].w); o[3] = bytes4(v[1].w, v[3].w, v[5].w, v[7].w);
}

__device__ __forceinline__ void tile0_of(int c, int& fp, int& m0) {
    const int t = c - 4, k = ((t - 32) * 37) >> 8;
    fp = t < 0 ? 0 : t < 32 ? t & 7 : t < 60 ? t - 31 - 7 * k : t - 54;
    m0 = (t < 0 ? 4 + c : t < 32 ? t >> 3 : 4 + k) * N0;
}
__device__ __forceinline__ void tile1_of(int c, int& fp, int& m0) {
    if (c < 6) { fp = c; m0 = 8 * N0; }
    else { fp = 8 + (c - 6) / 10; m0 = ((c - 6) % 10) * N1; }
}

__device__ __forceinline__ void ll_fetch(u64 (&c)[4], const char* p) {
    asm volatile("ld.relaxed.gpu.global.b64 %0, [%4];\nld.relaxed.gpu.global.b64 %1, [%4 + 128];\n"
                 "ld.relaxed.gpu.global.b64 %2, [%4 + 512];\nld.relaxed.gpu.global.b64 %3, [%4 + 640];"
                 : "=l"(c[0]), "=l"(c[1]), "=l"(c[2]), "=l"(c[3]) : "l"(p) : "memory");
}
__device__ __forceinline__ void ll_copy(uint32_t dst, const char* src, uint32_t bar) {
    asm volatile("{\n.reg .pred p;\nelect.sync _|p, 0xffffffff;\n"
                 "@p cp.async.bulk.shared::cluster.global.mbarrier::complete_tx::bytes [%0], [%1], 1024, [%2];\n}\n"
                 ::"r"(dst), "l"(src), "r"(bar) : "memory");
}
__device__ __forceinline__ void ll_read(u64 (&c)[4], uint32_t a) {
    asm volatile("ld.volatile.shared.b64 %0, [%4];\nld.volatile.shared.b64 %1, [%4 + 128];\n"
                 "ld.volatile.shared.b64 %2, [%4 + 512];\nld.volatile.shared.b64 %3, [%4 + 640];"
                 : "=l"(c[0]), "=l"(c[1]), "=l"(c[2]), "=l"(c[3]) : "r"(a) : "memory");
}
template <int OFF>
__device__ __forceinline__ void ll_check(u64 (&c)[4], uint32_t a, const char* p, uint32_t tag) {
    asm volatile(
        "{\n.reg .pred p, q;\n.reg .b32 l, h0, h1, h2, h3, x, i, o;\n.reg .b64 g;\n"
        "mov.u32 i, 0;\n"
        "L_%=:\n"
        "mov.b64 {l, h0}, %0;\nmov.b64 {l, h1}, %1;\nmov.b64 {l, h2}, %2;\nmov.b64 {l, h3}, %3;\n"
        "lop3.b32 x, %6, h0, h1, 0x7e;\n"
        "lop3.b32 x, x, %6, h2, 0xf6;\n"
        "lop3.b32 x, x, %6, h3, 0xf6;\n"
        "setp.ne.u32 p, x, 0;\n"
        "vote.sync.any.pred p, p, 0xffffffff;\n"
        "@!p bra D_%=;\n"
        "and.b32 o, %4, 1023;\ncvt.u64.u32 g, o;\nadd.u64 g, g, %5;\n"
        "setp.ge.u32 q, x, 16;\n"
        "setp.ge.or.u32 q, i, %8, q;\n"
        "vote.sync.any.pred q, q, 0xffffffff;\n"
        "@!q ld.volatile.shared.b64 %0, [%4 + %9];\n@!q ld.volatile.shared.b64 %1, [%4 + %9 + 128];\n"
        "@!q ld.volatile.shared.b64 %2, [%4 + %9 + 512];\n@!q ld.volatile.shared.b64 %3, [%4 + %9 + 640];\n"
        "@q ld.relaxed.gpu.global.b64 %0, [g];\n@q ld.relaxed.gpu.global.b64 %1, [g + 128];\n"
        "@q ld.relaxed.gpu.global.b64 %2, [g + 512];\n@q ld.relaxed.gpu.global.b64 %3, [g + 640];\n"
        "add.u32 i, i, 1;\n"
        "setp.lt.u32 p, i, %7;\n"
        "@p bra L_%=;\n"
        "D_%=:\n}\n"
        : "+l"(c[0]), "+l"(c[1]), "+l"(c[2]), "+l"(c[3])
        : "r"(a), "l"(p), "r"(tag), "n"(SPIN_LIMIT >> 4), "n"(NSPIN), "n"(OFF) : "memory");
}
__device__ __forceinline__ void ll_poll(u64 (&c)[4], const char* p, uint32_t tag) {
    unsigned it = 0;
    while (__any_sync(0xffffffffu, (((uint32_t)(c[0] >> 32) ^ tag) | ((uint32_t)(c[1] >> 32) ^ tag) |
                                    ((uint32_t)(c[2] >> 32) ^ tag) | ((uint32_t)(c[3] >> 32) ^ tag)) != 0) &&
           ++it < (SPIN_LIMIT >> 4))
        ll_fetch(c, p);
}
__device__ __forceinline__ void decode_alu(uint32_t& r0, uint32_t& r1, uint32_t& r2, uint32_t& r3, uint32_t w,
                                           const uint32_t (&lt)[8]) {
    const uint32_t s0 = w & 0x77777777u, s1 = s0 >> 16, w4 = w * 16;
    const uint32_t m0 = prmt(w4, w, 0xd9c8), m1 = prmt(w4, w, 0xfbea);
    const uint32_t l0 = (prmt(lt[0], lt[1], s0) & ~m0) | (prmt(lt[2], lt[3], s0) & m0);
    const uint32_t h0 = (prmt(lt[4], lt[5], s0) & ~m0) | (prmt(lt[6], lt[7], s0) & m0);
    const uint32_t l1 = (prmt(lt[0], lt[1], s1) & ~m1) | (prmt(lt[2], lt[3], s1) & m1);
    const uint32_t h1 = (prmt(lt[4], lt[5], s1) & ~m1) | (prmt(lt[6], lt[7], s1) & m1);
    r0 = prmt(l0, h0, 0x5140); r1 = prmt(l0, h0, 0x7362);
    r2 = prmt(l1, h1, 0x5140); r3 = prmt(l1, h1, 0x7362);
}
template <int WM, int AM>
__device__ __forceinline__ void decode(uint32_t (&a)[16], const u64 (&c)[4], uint32_t tblv, const uint32_t (&lt)[8],
                                       const uint32_t (&mu)[4]) {
#pragma unroll
    for (int i = 0; i < 4; i++) {
        const int b = (i >> 1) * 8 + (i & 1);
        if (!((WM >> i) & 1)) continue;
        if (!((AM >> i) & 1)) {
#pragma unroll
            for (int j = 0; j < 4; j++) a[b + 2 * j] = lds32(dp4a_u((uint32_t)c[i], mu[j], tblv));
        } else {
            decode_alu(a[b], a[b + 2], a[b + 4], a[b + 6], (uint32_t)c[i], lt);
        }
    }
}

__host__ __device__ constexpr int slot_of(int j) { return j < 16 ? j % 6 : (int)(0x2651032651032610ull >> (4 * (j - 16))) & 7; }
constexpr int STGA = 4, STGB = 3;
__host__ __device__ constexpr int slot_addr(int t, int s) {
    return t && (s < 2 || s == 6) ? (s == 6 ? 1 : 2 * s) * N1 * 128 : SLOT_OFF + s * SLOT_BYTES;
}
__host__ __device__ constexpr int stg_slot(int w) { return w ? STGB : STGA; }
__host__ __device__ constexpr int stg_uses(int w) {
    int n = stg_slot(w) == 4 || stg_slot(w) == 5;
    for (int i = 0; i < NSL; i++) n += slot_of(i) == stg_slot(w);
    return n;
}
__host__ __device__ constexpr bool reused(int j) {
    for (int i = j + 1; i < NSL; i++) if (slot_of(i) == slot_of(j)) return true;
    return j < 16 || slot_of(j) == STGA || slot_of(j) == STGB;
}
constexpr int STG_C0 = slot_addr(0, 6) - 2 * E0 * 128, STG_C1 = slot_addr(0, 4);
__host__ __device__ constexpr int loads_before(int j) {
    int n = 0;
    for (int i = 0; i < j; i++) n += slot_of(i) == slot_of(j);
    return n;
}
__host__ __device__ constexpr int uses_before(int j) {
    return loads_before(j) + (j >= 16 && (slot_of(j) == 4 || slot_of(j) == 5));
}
__host__ __device__ constexpr uint64_t prod_tbl(int j0) {
    uint64_t t = 0;
    for (int j = j0; j < j0 + 16; j++) t |= (uint64_t)(slot_of(j) | (((uses_before(j) + 1) & 1) << 3)) << (4 * (j - j0));
    return t;
}
__host__ __device__ constexpr uint64_t addr_tbl(int t) {
    uint64_t r = 0;
    for (int s = 0; s < NSLOTS; s++) r |= (uint64_t)(slot_addr(t, s) / 1024) << (8 * s);
    return r;
}
__host__ __device__ constexpr int dec_upto(int j) {
    return j < 14 ? j + 1 + (j >= RAMP1) + (j >= RAMP2) : j + 2 + (j >= RAMP3) + (JW == 5 && j >= RAMP4);
}
__host__ __device__ constexpr bool ramp_first(int d) {
    return d == RAMP1 + 1 || d == RAMP2 + 2 || d == RAMP3 + 2 || (JW == 5 && d == RAMP4 + 3);
}
__host__ __device__ constexpr int abuf(int j) { return JW == 5 && j >= RAMP4 + 4 ? (j == RAMP4 + 4 ? 4 : (j - 1) % 4) : j % 4; }
__host__ __device__ constexpr bool read_early(int d) {
    return d > RLATE && d < NSL && !ramp_first(d - 2) && !ramp_first(d - 3) && d != 18 && d != 20 && d != 21;
}
__host__ __device__ constexpr bool get_early(int d) { return ramp_first(d); }

__device__ __forceinline__ void fence_a(uint32_t (&a)[16]) {
#pragma unroll
    for (int i = 0; i < 16; i++) asm volatile("" : "+r"(a[i])::"memory");
}
template <int J, int N, int COL>
__device__ __forceinline__ void mma_slice(float (&acc)[N0 / 2], uint32_t (&a)[JW][16]) {
    constexpr int off = (slot_addr(J / KSTEPS, slot_of(J)) + COL * 128) / 16, b = abuf(J);
    constexpr uint64_t d0 = make_desc(SMEM_BASE);
    WG<N, COL / 2, (J % KSTEPS) != 0, N0 / 2>::mma(acc, a[b][0], a[b][1], a[b][2], a[b][3], d0 + off);
    WG<N, COL / 2, true, N0 / 2>::mma(acc, a[b][4], a[b][5], a[b][6], a[b][7], d0 + (off + 2));
    WG<N, COL / 2, true, N0 / 2>::mma(acc, a[b][8], a[b][9], a[b][10], a[b][11], d0 + (off + 4));
    WG<N, COL / 2, true, N0 / 2>::mma(acc, a[b][12], a[b][13], a[b][14], a[b][15], d0 + (off + 6));
}
template <int N> __device__ __forceinline__ void rename_acc(float (&acc)[N0 / 2]) {
#pragma unroll
    for (int i = 0; i < N / 2; i++) asm volatile("mov.b32 %0, %1;" : "=f"(acc[i]) : "f"(acc[i]) : "memory");
}
template <int N, int COL, bool FENCE>
__device__ __forceinline__ void stage_out(float (&acc)[N0 / 2], uint32_t sa, const float s0, const float s1) {
#pragma unroll
    for (int i = COL / 2; i < (COL + N) / 2; i++) asm volatile("" : "+f"(acc[i])::"memory");
#pragma unroll
    for (int j = COL / 8; j + 1 < (COL + N) / 8; j += 2) {
        const uint32_t r0 = pack_bf16x2(acc[4 * j + 0] * s0, acc[4 * j + 1] * s0);
        const uint32_t r1 = pack_bf16x2(acc[4 * j + 2] * s1, acc[4 * j + 3] * s1);
        const uint32_t r2 = pack_bf16x2(acc[4 * j + 4] * s0, acc[4 * j + 5] * s0);
        const uint32_t r3 = pack_bf16x2(acc[4 * j + 6] * s1, acc[4 * j + 7] * s1);
        asm volatile("stmatrix.sync.aligned.m8n8.x4.trans.shared.b16 [%0], {%1, %2, %3, %4};"
                     ::"r"(sa + j * 1024), "r"(r0), "r"(r1), "r"(r2), "r"(r3) : "memory");
    }
    if constexpr ((N / 8) & 1) {
        constexpr int j = (COL + N) / 8 - 1;
        const uint32_t r0 = pack_bf16x2(acc[4 * j + 0] * s0, acc[4 * j + 1] * s0);
        const uint32_t r1 = pack_bf16x2(acc[4 * j + 2] * s1, acc[4 * j + 3] * s1);
        asm volatile("stmatrix.sync.aligned.m8n8.x2.trans.shared.b16 [%0], {%1, %2};"
                     ::"r"(sa + j * 1024), "r"(r0), "r"(r1) : "memory");
    }
    if constexpr (FENCE) asm volatile("fence.proxy.async.shared::cta;" ::: "memory");
}

struct Maps { CUtensorMap m[4 + NCH]; };

__global__ void __cluster_dims__(2, 1, 1) __launch_bounds__(NUM_THREADS, 1)
nf4_gemm_kernel(const int* __restrict__ qw, u64* __restrict__ ll, unsigned* __restrict__ epoch,
                const __nv_bfloat16* __restrict__ lut, const __nv_bfloat16* __restrict__ scales,
                const __grid_constant__ Maps tm) {
    extern __shared__ __align__(1024) uint8_t smem_raw[];
    const uint32_t t_start = clock32();
    const int lane = threadIdx.x & 31;
    if (threadIdx.x < 32)
        asm volatile("prefetch.global.L2 [%0];" ::"l"(add_off(qw, unit_src(blockIdx.x / W1_FG, blockIdx.x % W1_FG) + lane * (kN * 4))) : "memory");
    const int warp = __shfl_sync(0xffffffffu, threadIdx.x >> 5, 0);
    const uint32_t sb = smem_u32(smem_raw);
    const uint32_t bar_full = sb + BAR_OFF;
    const uint32_t bar_empty = bar_full + NSLOTS * 8;
    const uint32_t bar_tbl = bar_empty + NSLOTS * 8;
    const uint32_t bar_code = bar_tbl + 8;
    const uint32_t bar_stg = bar_code + 8;

    if (warp == 1) {
        if (lane == 0) {
            for (int i = 0; i < 2 * (2 + NCH); i++) mbar_init(bar_stg + i * 8, 128);
            asm volatile("fence.mbarrier_init.release.cluster;" ::: "memory");
        }
        __syncwarp();
    }
    if (warp != 8) cluster_arrive_relaxed();
    const int crank = blockIdx.x & 1, cluster = blockIdx.x >> 1;
    if (warp < 8) {
        const int wg = warp >> 2;
        const uint32_t tagl = ld_ca_u32(epoch + lane);
        const uint32_t lv = ldg_u16(reinterpret_cast<const unsigned short*>(lut) + (lane & 15));
        int fp0, fp1, mm;
        tile0_of(cluster, fp0, mm);
        tile1_of(cluster, fp1, mm);
        const int ft0 = fp0 * 2 + crank, ft1 = fp1 * 2 + crank;
        const unsigned short* sc16 = reinterpret_cast<const unsigned short*>(scales) + warp * 16 + (lane >> 2);
        uint32_t sc0 = ldg_u16(sc16 + ft0 * FT), sc0h = ldg_u16(sc16 + ft0 * FT + 8);
        uint32_t sc1 = ldg_u16(sc16 + ft1 * FT), sc1h = ldg_u16(sc16 + ft1 * FT + 8);
        {
            constexpr int EPS = 128 / TBLC;
#pragma unroll
            for (int k = 0; k < 32 / EPS; k++) {
                const int e = warp * 32 + k * EPS + lane / (TBLC / 4);
                const uint32_t v = __shfl_sync(0xffffffffu, lv, e & 15) | (__shfl_sync(0xffffffffu, lv, e >> 4) << 16);
                asm volatile("st.shared.v4.u32 [%0], {%1, %1, %1, %1};"
                             ::"r"(sb + TBL_OFF + warp * (TBLC * 128) + k * 512 + lane * 16), "r"(v) : "memory");
            }
        }
        asm volatile("setmaxnreg.inc.sync.aligned.u32 %0;" ::"n"(CREGS));
        cluster_wait();
        mbar_arrive(bar_tbl);
        sc0 |= sc0h << 16;
        sc1 |= sc1h << 16;
        const char* ll0 = keep(reinterpret_cast<const char*>(ll) + (ft0 * (KSTEPS * 8192) + warp * 1024 + lane), 0);
        const char* ll1 = keep(reinterpret_cast<const char*>(ll) + (ft1 * (KSTEPS * 8192) + warp * 1024 + lane), 0);
        const uint32_t cbuf = sb + COD_OFF + warp * 1024;
        const uint32_t tblv = keep(sb + TBL_OFF + (lane % TBLC) * 4, lane);
        const uint32_t cempty = keep(lane < 2 ? mapa(bar_empty, lane) : 0, lane);
        const uint32_t sa0 = keep(sb + (((lane >> 4) * 8 + (lane & 7)) * 128) +
                                  ((((warp & 3) * 2 + ((lane >> 3) & 1)) ^ (lane & 7)) << 4), lane);
        uint32_t lt[8];
        {
            const uint32_t p01 = __shfl_sync(0xffffffffu, lv, 4 * lane) | (__shfl_sync(0xffffffffu, lv, 4 * lane + 1) << 16);
            const uint32_t p23 = __shfl_sync(0xffffffffu, lv, 4 * lane + 2) | (__shfl_sync(0xffffffffu, lv, 4 * lane + 3) << 16);
            const uint32_t pl = prmt(p01, p23, lane & 4 ? 0x7531 : 0x6420);
#pragma unroll
            for (int i = 0; i < 8; i++) lt[i] = __shfl_sync(0xffffffffu, pl, i & 1 ? i : i + (lane & 24));
        }
        uint32_t mu[4];
#pragma unroll
        for (int j = 0; j < 4; j++) mu[j] = keep(((uint32_t)(TBLC * 4) << (8 * j)) + lane, 0);
        uint32_t a[JW][16];
        float acc[N0 / 2];

        auto src = [&](auto dc) {
            constexpr int D = decltype(dc)::value;
            return (D < KSTEPS ? ll0 : ll1) + (D % KSTEPS) * 8192;
        };
        const uint32_t tag = __shfl_sync(0xffffffffu, tagl, 0);
        u64 c[4], ch[4];
        const uint32_t aw = keep(cbuf + lane_unit(lane), lane);
#pragma unroll
        for (int i = 0; i < 4; i++)
            asm volatile("st.shared.v4.u32 [%0], {%1, %1, %1, %1};" ::"r"(cbuf + (i >> 1) * 8192 + (i & 1) * 512 + lane * 16), "r"(tag) : "memory");
        asm volatile("fence.proxy.async.shared::cta;" ::: "memory");
        __syncwarp();
        auto fetch = [&](auto dc) {
            constexpr int D = decltype(dc)::value;
            if constexpr (D < NGATE) delay_until(t_start, gate_time(D));
            if constexpr (D < NSL) ll_copy(cbuf + (D & 1) * 8192, src(dc), bar_code);
        };
        auto check = [&](auto dc) {
            constexpr int D = decltype(dc)::value;
            ll_check<(D & 1) * 8192>(c, aw, src(dc), tag + D % KSTEPS);
            if constexpr (D + 2 >= NGATE) fetch(IC<D + 2>{});
        };
        auto get = [&](auto dc) {
            constexpr int D = decltype(dc)::value;
            if constexpr (D + 1 <= FLATE) fetch(IC<D + 1>{});
            if constexpr (!read_early(D)) ll_read(c, aw + (D & 1) * 8192);
            check(dc);
        };
        auto dec = [&](auto dc) {
            constexpr int D = decltype(dc)::value;
            if constexpr (HALF && ramp_first(D - 1)) {
                decode<5, 12>(a[abuf(D)], c, tblv, lt, mu);
                ch[1] = (uint32_t)c[1]; ch[3] = (uint32_t)c[3];
            } else {
                if constexpr (HALF && ramp_first(D - 2)) decode<10, 12>(a[abuf(D - 1)], ch, tblv, lt, mu);
                decode<(D < NSPLIT ? 3 : 15), (D < NSPLIT ? 10 : 12)>(a[abuf(D)], c, tblv, lt, mu);
                if constexpr (D < NSPLIT) { ch[2] = (uint32_t)c[2]; ch[3] = (uint32_t)c[3]; }
            }
            if constexpr (D + 2 > FLATE && D + 2 < NGATE) fetch(IC<D + 2>{});
            if constexpr (read_early(D + 1)) ll_read(c, aw + ((D + 1) & 1) * 8192);
            if constexpr (get_early(D + 1)) get(IC<D + 1>{});
        };
        auto wait_full = [&](auto jc) {
            constexpr int J = decltype(jc)::value;
            mbar_wait(bar_full + slot_of(J) * 8, loads_before(J) & 1);
        };
        auto release = [&](auto jc) {
            constexpr int J = decltype(jc)::value;
            if constexpr (reused(J)) mbar_arrive_pair(cempty + slot_of(J) * 8, cempty);
        };
        auto step = [&](auto jc) {
            constexpr int J = decltype(jc)::value, D = dec_upto(J - 1) + 1;
            if constexpr (J < NSPLIT) {
                constexpr uint64_t d = make_desc(SMEM_BASE + slot_addr(0, slot_of(J)));
                uint32_t (&f)[16] = a[abuf(J)];
#pragma unroll
                for (int i = 0; i < 8; i++) asm volatile("" : "+r"(f[i])::"memory");
                wgmma_fence();
                WG<N0, 0, J != 0, N0 / 2>::mma(acc, f[0], f[1], f[2], f[3], d);
                WG<N0, 0, true, N0 / 2>::mma(acc, f[4], f[5], f[6], f[7], d + 2);
                decode<12, 10>(f, ch, tblv, lt, mu);
#pragma unroll
                for (int i = 8; i < 16; i++) asm volatile("" : "+r"(f[i])::"memory");
                wgmma_fence();
                WG<N0, 0, true, N0 / 2>::mma(acc, f[8], f[9], f[10], f[11], d + 4);
                WG<N0, 0, true, N0 / 2>::mma(acc, f[12], f[13], f[14], f[15], d + 6);
            } else {
                fence_a(a[abuf(J)]);
                wgmma_fence();
                mma_slice<J, (J < KSTEPS ? N0 : N1), 0>(acc, a);
            }
            wgmma_commit();
            constexpr bool WF = J >= NEARLY && !get_early(D) && !read_early(D) && D + 1 > FLATE;
            if constexpr (WF) { ll_read(c, aw + (D & 1) * 8192); wait_full(IC<J + 1>{}); check(IC<D>{}); }
            if constexpr (!WF && !get_early(D)) get(IC<D>{});
            if constexpr (!WF && J >= NEARLY) wait_full(IC<J + 1>{});
            wgmma_wait<1>();
            if constexpr (J != 0 && J != 18) release(IC<J - 1>{});
            dec(IC<D>{});
            if constexpr (dec_upto(J) > D) { get(IC<D + 1>{}); dec(IC<D + 1>{}); }
            if constexpr (J < NEARLY) wait_full(IC<J + 1>{});
        };
        static_assert(NSPLIT <= RAMP1 + 1 && FLATE >= 1 && FLATE < NGATE && RLATE >= FLATE && RLATE < RAMP1 && RAMP1 + 2 < RAMP2 && RAMP2 < 14 &&
                      RAMP3 > 20 && RAMP3 < 28 && (!HALF || (RAMP2 < 13 && (JW == 4 ? RAMP3 < 27 : RAMP4 < 26))), "code schedule");
        static_assert(slot_of(10) == 4 && slot_of(11) == 5 && uses_before(11) == 1 && STG_C1 + 2 * E1 * 128 <= STG_C0, "staging");

        mbar_wait(bar_tbl, 0);
        delay_until(t_start, gate_time(0));
        ll_fetch(c, src(IC<0>{}) + (aw & 1023));
        fetch(IC<1>{});
        ll_poll(c, src(IC<0>{}) + (aw & 1023), tag);
        dec(IC<0>{});
        wait_full(IC<0>{});
        static_for<0, 14>(step);
        {
            const float s0 = __uint_as_float(sc0 << 16), s1 = __uint_as_float(sc0 & 0xffff0000u);
            const uint32_t sa = sa0 + STG_C0 + wg * (E0 * 128), sc = sa0 + STG_C1 - E0 * 128 + wg * (E1 * 128);
            auto group = [&](auto jc, auto nc, auto cc) {
                fence_a(a[decltype(jc)::value % 4]);
                wgmma_fence();
                mma_slice<decltype(jc)::value, decltype(nc)::value, decltype(cc)::value>(acc, a);
                wgmma_commit();
            };
            wait_full(IC<15>{});
            wgmma_wait<0>();
            rename_acc<N0>(acc);
            group(IC<14>{}, IC<E0>{}, IC<0>{});
            release(IC<13>{});
            get(IC<17>{});
            mbar_wait(bar_empty + 5 * 8, 1);
            group(IC<15>{}, IC<E0>{}, IC<0>{});
            dec(IC<17>{});
            group(IC<14>{}, IC<E1>{}, IC<E0>{});
            wgmma_wait<1>();
            stage_out<EI, 0, false>(acc, sa, s0, s1);
            group(IC<15>{}, IC<E1>{}, IC<E0>{});
            wait_full(IC<16>{});
            wgmma_wait<1>();
            release(IC<14>{});
            stage_out<E0 - EI, EI, true>(acc, sa, s0, s1);
            mbar_arrive(bar_stg + wg * 8);
            group(IC<16>{}, IC<S0>{}, IC<0>{});
            wait_full(IC<17>{});
            wgmma_wait<1>();
            release(IC<15>{});
            stage_out<EI, E0, false>(acc, sc, s0, s1);
            group(IC<17>{}, IC<S0>{}, IC<0>{});
            stage_out<E1 - EI, E0 + EI, true>(acc, sc, s0, s1);
            mbar_arrive(bar_stg + 16 + wg * 8);
            group(IC<16>{}, IC<S1>{}, IC<S0>{});
            get(IC<18>{});
            dec(IC<18>{});
            group(IC<17>{}, IC<S1>{}, IC<S0>{});
            get(IC<19>{});
            wait_full(IC<18>{});
            wgmma_wait<1>();
            release(IC<16>{});
            dec(IC<19>{});
            wgmma_wait<0>();
            rename_acc<N1>(acc);
            release(IC<17>{});
        }
        static_for<18, NSL - JW>(step);
        {
            constexpr int J0 = NSL - JW;
            const float s0 = __uint_as_float(sc1 << 16), s1 = __uint_as_float(sc1 & 0xffff0000u);
            const uint32_t sa = sa0 + (wg ? slot_addr(1, STGB) : slot_addr(1, STGA));
            static_for<J0 + 1, NSL - 1>(wait_full);
            static_for<J0, NSL - 1>([&](auto jc) { fence_a(a[abuf(decltype(jc)::value)]); });
            wgmma_wait<0>();
            rename_acc<N1>(acc);
            wgmma_fence();
            mma_slice<J0, chunk_n(0), 0>(acc, a);
            release(IC<J0 - 1>{});
            get(IC<NSL - 1>{}); dec(IC<NSL - 1>{});
            asm volatile("{\n.reg .pred p;\nelect.sync _|p, 0xffffffff;\n"
                         "@p mbarrier.arrive.expect_tx.shared::cta.b64 _, [%0], %1;\n}\n" ::"r"(bar_code), "n"((NSL - 1) * 1024) : "memory");
            wgmma_fence();
            static_for<J0 + 1, NSL - 1>([&](auto jc) { mma_slice<decltype(jc)::value, chunk_n(0), 0>(acc, a); });
            wait_full(IC<NSL - 1>{});
            fence_a(a[abuf(NSL - 1)]);
            wgmma_fence();
            mma_slice<NSL - 1, chunk_n(0), 0>(acc, a);
            wgmma_commit();
            static_for<1, NCH + 1>([&](auto cc) {
                constexpr int C = decltype(cc)::value;
                if constexpr (C < NCH) {
                    wgmma_fence();
                    mma_slice<J0, chunk_n(C), chunk_col(C)>(acc, a);
                    wgmma_commit();
                    if constexpr (C == 1)
                        mbar_wait(bar_empty + (wg ? STGB : STGA) * 8, (wg ? stg_uses(1) - 1 : stg_uses(0) - 1) & 1);
                    wgmma_wait<1>();
                } else {
                    wgmma_wait<0>();
                }
                stage_out<chunk_n(C - 1), chunk_col(C - 1), true>(acc, sa, s0, s1);
                mbar_arrive(bar_stg + (1 + C) * 16 + wg * 8);
                if constexpr (C < NCH) {
                    wgmma_fence();
                    static_for<J0 + 1, NSL>([&](auto jc) { mma_slice<decltype(jc)::value, chunk_n(C), chunk_col(C)>(acc, a); });
                    wgmma_commit();
                }
            });
        }
    } else {
      if (warp >= 9) {
        {
            const int pw = warp - 9;
            int u = pw * NUM_CTAS + blockIdx.x;
            uint32_t q = u / W1_FG, fg = u % W1_FG;
            const int* qwk = keep(add_off(qw, lane_src(lane)), lane);
            u64* llk = keep(add_off(ll, lane_dst(lane)), lane);
            const unsigned* ep = epoch + lane;
            asm volatile("setmaxnreg.dec.sync.aligned.u32 %0;" ::"n"(504 - 2 * CREGS));
            const uint32_t tag = ld_ca_u32(ep);
            if (pw > 0) delay_until(t_start, DLY_R0 + pw * DLY_R);
            uint4 v[8];
            load_unit(v, add_off(qwk, unit_src(q, fg)));
#pragma unroll 1
            for (;;) {
                u64* dst = add_off(llk, unit_dst(q, fg));
                const uint32_t sl = q >> 1;
                static_assert(RSTOP % NUM_AUX == 0, "pack rounds");
                u += u < (RSTOP - 1) * NUM_CTAS ? NUM_AUX * NUM_CTAS : pw == 2 ? NUM_UNITS : 2 * NUM_CTAS;
                unit_pos(min(u, NUM_UNITS - 1), q, fg);
                const int* p = add_off(qwk, unit_src(q, fg));
                uint32_t e[4], o[4], w[4];
                pk_gather(e, o, v);
#pragma unroll
                for (int k = 0; k < 4; k++)
                    asm("lop3.b32 %0, %1, %2, 0x0f0f0f0f, 0xe4;" : "=r"(w[k]) : "r"(e[k]), "r"(o[k] << 4));
                ll_store2(dst, w[0], w[1], tag + sl);
                ll_store2((u64*)((uint64_t)dst ^ 320), w[2], w[3], tag + sl);
                if (u >= NUM_UNITS) break;
                load_unit(v, p);
            }
        }
        const CUtensorMap* maps = keep(&tm.m[3] + lane, 0);
        named_bar_arrive<4, 128>();
        cluster_wait();
        int fp, m0;
        if (warp == 11) {
            tile0_of(cluster, fp, m0);
            const int f0 = (fp * 2 + crank) * FT;
#pragma unroll 1
            for (int ch = 0; ch < 2; ch++) {
                const uint32_t src = sb + (ch ? STG_C1 : STG_C0);
                const int rows = ch ? E1 : E0;
                int h = 0;
#pragma unroll 1
                for (unsigned it = 0; it < 16 * SPIN_LIMIT && !mbar_test(bar_stg + ch * 16 + h * 8, 0); it++) { h ^= 1; __nanosleep(20); }
#pragma unroll 1
                for (int k = 0; k < 2; k++, h ^= 1) {
                    mbar_wait(bar_stg + ch * 16 + h * 8, 0);
#pragma unroll 1
                    for (int r = 0; r < rows; r += 8) {
                        asm volatile("{\n.reg .pred p;\nelect.sync _|p, 0xffffffff;\n"
                                     "@p cp.async.bulk.tensor.2d.global.shared::cta.bulk_group [%0, {%2, %3}], [%1];\n"
                                     "cp.async.bulk.commit_group;\ncp.async.bulk.wait_group.read 1;\n}\n"
                                     ::"l"(maps), "r"(src + (h * rows + r) * 128), "r"(f0 + h * 64), "r"(m0 + ch * E0 + r)
                                     : "memory");
                    }
                }
                asm volatile("cp.async.bulk.wait_group.read 0;" ::: "memory");
                __syncwarp();
                if (lane < 2) mbar_arrive_cluster_n(mapa(bar_empty + (5 - ch) * 8, lane), 8);
            }
        } else {
            const int wg = warp - 9;
            tile1_of(cluster, fp, m0);
            const int f0 = (fp * 2 + crank) * FT + wg * 64;
            const uint32_t src = sb + (wg ? slot_addr(1, STGB) : slot_addr(1, STGA));
            int r0 = 0;
#pragma unroll 1
            for (int ch = 0; ch < NCH; ch++) {
                mbar_wait(bar_stg + (2 + ch) * 16 + wg * 8, 0);
                asm volatile("{\n.reg .pred p;\nelect.sync _|p, 0xffffffff;\n"
                             "@p cp.async.bulk.tensor.2d.global.shared::cta.bulk_group [%0, {%2, %3}], [%1];\n}\n"
                             ::"l"(maps + 1 + ch), "r"(src + r0 * 128), "r"(f0), "r"(m0 + r0) : "memory");
                r0 += ((CHK >> (4 * ch)) & 15) * 8;
            }
            asm volatile("cp.async.bulk.commit_group;\ncp.async.bulk.wait_group.read 0;" ::: "memory");
        }
      } else {
        asm volatile("setmaxnreg.dec.sync.aligned.u32 %0;" ::"n"(504 - 2 * CREGS));
        if ((sb & 0xFFFFFF) != SMEM_BASE) __trap();
        if (lane == 0) {
            for (int s = 0; s < NSLOTS; s++) {
                mbar_init(bar_full + s * 8, 1);
                mbar_init(bar_empty + s * 8, 16);
            }
            mbar_init(bar_tbl, 256);
            mbar_init(bar_code, 8);
            asm volatile("fence.mbarrier_init.release.cluster;" ::: "memory");
        }
        __syncwarp();
        cluster_arrive_relaxed();
        const CUtensorMap* maps = keep(&tm.m[0] + lane, 0);
        unsigned* epk = keep(epoch + lane, 0);
        if (lane == 0) prefetch_map(maps + crank);
        int fp, m0;
        tile0_of(cluster, fp, m0);
        cluster_wait();
#pragma unroll 1
        for (int t = 0; t < 2; t++) {
            const int lo = t == 0 ? 120 : 104, row = m0 + crank * lo;
            const CUtensorMap* map = maps + (t ? 2 : crank);
            const uint32_t bytes = (t ? N1 : N0) * 128, dst = sb + crank * lo * 128;
            uint64_t tbl = t ? prod_tbl(16) : prod_tbl(0);
            const uint64_t adr = t ? addr_tbl(1) : addr_tbl(0);
#pragma unroll 1
            for (int ks = 0; ks < KSTEPS; ks++, tbl >>= 4) {
                const uint32_t slot = (uint32_t)tbl & 7;
                if (t == 0 && ks > 0 && ks < 6) delay_until(t_start, DLY_X0 + ks * DLY_XS);
                mbar_wait(bar_empty + slot * 8, ((uint32_t)tbl >> 3) & 1);
                asm volatile(
                    "{\n.reg .pred p;\nelect.sync _|p, 0xffffffff;\n"
                    "@p mbarrier.arrive.expect_tx.shared::cta.b64 _, [%2], %5;\n"
                    "@p cp.async.bulk.tensor.2d.shared::cluster.global.mbarrier::complete_tx::bytes.multicast::cluster"
                    " [%0], [%1, {%3, %4}], [%2], %6;\n}\n"
                    ::"r"(dst + (((uint32_t)(adr >> (8 * slot)) & 255) << 10)), "l"(map), "r"(bar_full + slot * 8), "r"(ks * BK), "r"(row), "r"(bytes),
                    "h"((uint16_t)3) : "memory");
            }
            tile1_of(cluster, fp, m0);
            if (t == 0 && lane >= 2 && lane < 4 + NCH) prefetch_map(maps + lane);
        }
        named_bar_sync<4, 128>();
        const uint32_t tag = ld_ca_u32(epk + lane);
        unsigned old = 0;
        if (lane == 0) old = atomicAdd(epk + 32, tag != 0 ? 1u : 0u);
        if (__shfl_sync(0xffffffffu, old, 0) == NUM_CTAS - 1) {
            if (lane == 0) epk[32] = 0;
            epk[lane] = tag == 0xfffffff0u ? 16 : tag + 16;
        }
        mbar_wait(bar_code, 0);
      }
    }
}

__global__ void generic_kernel(const __nv_bfloat16* __restrict__ x, const int* __restrict__ qw,
                               const __nv_bfloat16* __restrict__ lut, const __nv_bfloat16* __restrict__ scales,
                               __nv_bfloat16* __restrict__ out, int M, int N, int K, int G) {
    const int n = blockIdx.x * blockDim.x + threadIdx.x;
    const int m = blockIdx.y;
    if (n >= N) return;
    float acc = 0.f;
    for (int k = 0; k < K; k++) {
        const float l = __bfloat162float(lut[qw[(size_t)k * N + n] & 15]);
        const float s = __bfloat162float(scales[(size_t)(k / G) * N + n]);
        const float w = __bfloat162float(__float2bfloat16_rn(l * s));
        acc += __bfloat162float(x[(size_t)m * K + k]) * w;
    }
    out[(size_t)m * N + n] = __float2bfloat16_rn(acc);
}

typedef CUresult (*PFN_encodeTiled)(CUtensorMap*, CUtensorMapDataType, cuuint32_t, void*, const cuuint64_t*,
                                    const cuuint64_t*, const cuuint32_t*, const cuuint32_t*, CUtensorMapInterleave,
                                    CUtensorMapSwizzle, CUtensorMapL2promotion, CUtensorMapFloatOOBfill);

bool make_map_2d(PFN_encodeTiled fn, CUtensorMap* map, void* base, uint64_t inner, uint64_t outer, uint32_t box_inner,
                 uint32_t box_outer) {
    cuuint64_t dims[2] = {inner, outer};
    cuuint64_t strides[1] = {inner * 2};
    cuuint32_t box[2] = {box_inner, box_outer};
    cuuint32_t estr[2] = {1, 1};
    return fn(map, CU_TENSOR_MAP_DATA_TYPE_BFLOAT16, 2, base, dims, strides, box, estr, CU_TENSOR_MAP_INTERLEAVE_NONE,
              CU_TENSOR_MAP_SWIZZLE_128B, CU_TENSOR_MAP_L2_PROMOTION_L2_128B,
              CU_TENSOR_MAP_FLOAT_OOB_FILL_NONE) == CUDA_SUCCESS;
}

}

extern "C" void kernel_launch(void* const* d_in, const int* in_sizes, int n_in, void* d_out, int out_size) {
    const __nv_bfloat16* x = (const __nv_bfloat16*)d_in[0];
    const int* qw = (const int*)d_in[1];
    const __nv_bfloat16* lut = (const __nv_bfloat16*)d_in[2];
    const __nv_bfloat16* scales = (const __nv_bfloat16*)d_in[3];
    __nv_bfloat16* out = (__nv_bfloat16*)d_out;

    const double Kd = sqrt((double)in_sizes[0] * (double)in_sizes[1] / (double)out_size);
    const int K = (int)(Kd + 0.5);
    const int M = in_sizes[0] / K, N = in_sizes[1] / K;
    const int ng = in_sizes[3] / N;
    const int G = K / ng;

    bool fast = (M == kM && N == kN && K == kK && ng == 1 && in_sizes[2] >= 16);
    PFN_encodeTiled enc = nullptr;
    Maps tm;
    void *ll = nullptr, *epoch = nullptr;
    if (fast) {
        cudaDriverEntryPointQueryResult qres;
        void* fp = nullptr;
        if (cudaGetDriverEntryPoint("cuTensorMapEncodeTiled", &fp, cudaEnableDefault, &qres) != cudaSuccess || !fp) fast = false;
        enc = (PFN_encodeTiled)fp;
    }
    if (fast) {
        fast = make_map_2d(enc, &tm.m[0], (void*)x, kK, kM, BK, 120) &&
               make_map_2d(enc, &tm.m[1], (void*)x, kK, kM, BK, 112) &&
               make_map_2d(enc, &tm.m[2], (void*)x, kK, kM, BK, 104) &&
               make_map_2d(enc, &tm.m[3], (void*)out, kN, kM, 64, 8) &&
               cudaGetSymbolAddress(&ll, g_ll) == cudaSuccess && cudaGetSymbolAddress(&epoch, g_epoch) == cudaSuccess;
    }
    for (int c = 0; c < NCH && fast; c++) fast = make_map_2d(enc, &tm.m[4 + c], (void*)out, kN, kM, 64, chunk_n(c));
    cudaLaunchConfig_t cfg = {};
    cfg.gridDim = dim3(NUM_CTAS);
    cfg.blockDim = dim3(NUM_THREADS);
    cfg.dynamicSmemBytes = SMEM_TOTAL;
    cfg.stream = cudaStreamPerThread;
    if (fast) {
        int nclusters = 0;
        fast = cudaFuncSetAttribute(nf4_gemm_kernel, cudaFuncAttributeMaxDynamicSharedMemorySize, SMEM_TOTAL) == cudaSuccess &&
               cudaOccupancyMaxActiveClusters(&nclusters, nf4_gemm_kernel, &cfg) == cudaSuccess &&
               nclusters >= NUM_CTAS / 2;
    }
    if (!fast) {
        generic_kernel<<<dim3((N + 127) / 128, M), 128>>>(x, qw, lut, scales, out, M, N, K, G);
        return;
    }
    cudaLaunchKernelEx(&cfg, nf4_gemm_kernel, qw, (u64*)ll, (unsigned*)epoch, lut, scales, tm);
}
```
